```python
import torch

def _softmax(x, axis=-1):
    return torch.softmax(x, dim=axis)

def _gelu(x):
    return torch.nn.functional.gelu(x, approximate='tanh')

def _silu(x):
    return torch.nn.functional.silu(x)

def _sigmoid(x):
    return torch.sigmoid(x)

def _layernorm(x, axis=-1, eps=1e-05):
    m = x.mean(dim=axis, keepdim=True)
    v = x.var(dim=axis, keepdim=True, unbiased=False)
    return (x - m) / torch.sqrt(v + eps)

def _scatter_add(tgt, idx, src, axis=0):
    return tgt.clone().index_add_(axis, idx, src)

def _segment_sum(src, seg, n):
    out = torch.zeros((n,) + src.shape[1:], dtype=src.dtype)
    return out.index_add_(0, seg, src)

def _pad(x, pw):
    flat = tuple((v for pair in reversed(pw) for v in pair))
    return torch.nn.functional.pad(x, flat)
kernel_name = 'standalone__tensor_product_equiv_tfn__graph'

def setup_inputs():

    _w = lambda a: (lambda t: t.to(torch.bfloat16) if t.is_floating_point() else t)(torch.as_tensor(a))
    N, deg, C, L, DE = (10000, 32, 128, 1, 16)
    E = N * deg
    M = (L + 1) ** 2
    src = (lambda lo, hi, *s: torch.randint(lo, hi, s))(0, N, E).to(torch.int64)
    dst = (lambda lo, hi, *s: torch.randint(lo, hi, s))(0, N, E).to(torch.int64)
    r = (lambda *s: torch.randn(*s, dtype=torch.bfloat16) * 0.05)(E, 3)
    r = r / (torch.linalg.norm(r, dim=-1, keepdim=True) + 1e-09)
    rx, ry, rz = (r[:, 0].clone(), r[:, 1].clone(), r[:, 2].clone())
    Ys = [torch.ones((E, 1), dtype=float)]
    if L >= 1:
        Ys.append(r.to(float))
    if L >= 2:
        Ys.append(torch.stack([2 * rx * ry, 2 * ry * rz, (3 * rz * rz - 1.0) / (lambda _x: torch.sqrt(torch.as_tensor(_x)))(3.0), 2 * rx * rz, rx * rx - ry * ry], dim=-1).to(float))
    for _l in range(3, L + 1):
        Ys.append(((lambda *s: torch.randn(*s, dtype=torch.bfloat16) * 0.05)(E, 2 * _l + 1) * 0.3).to(float))
    Y = torch.cat(Ys, dim=-1)
    cg = torch.zeros((M, M, M), dtype=float)
    off = [_l * _l for _l in range(L + 2)]
    for l1 in range(L + 1):
        for l2 in range(L + 1):
            for l3 in range(abs(l1 - l2), min(L, l1 + l2) + 1):
                d1, d2, d3 = (2 * l1 + 1, 2 * l2 + 1, 2 * l3 + 1)
                cg[off[l1]:off[l1 + 1], off[l2]:off[l2 + 1], off[l3]:off[l3 + 1]] = (lambda *s: torch.randn(*s, dtype=torch.bfloat16) * 0.05)(d1, d2, d3) / (lambda _x: torch.sqrt(torch.as_tensor(_x)))(float(d1 * d2))
    return {'x': _w((lambda *s: torch.randn(*s, dtype=torch.bfloat16) * 0.05)(N, C, M) * 0.2), 'src': _w(src), 'dst': _w(dst), 'Y': _w(Y), 'edge_feat': _w((lambda *s: torch.randn(*s, dtype=torch.bfloat16) * 0.05)(E, DE)), 'w_rad': _w((lambda *s: torch.randn(*s, dtype=torch.bfloat16) * 0.05)(DE, C) * (1.0 / max(1.0, DE) ** 0.5)), 'cg': _w(cg), 'w_mix': _w((lambda *s: torch.randn(*s, dtype=torch.bfloat16) * 0.05)(C, C) * (1.0 / max(1.0, C) ** 0.5))}

def reference(x, src, dst, Y, edge_feat, w_rad, cg, w_mix):
    N, C, M = (x.shape[0], x.shape[1], x.shape[2])
    R = _silu(edge_feat @ w_rad)
    xs = x[src]
    tp = torch.einsum('eci,ef,ifo->eco', xs, Y, cg)
    msg = R[:, :, None] * tp
    agg = _segment_sum(msg.reshape(-1, C * M), dst, N).reshape(N, C, M)
    return torch.einsum('ncm,cd->ndm', agg, w_mix)
```

```cpp
#include <cuda_runtime.h>
#include <cuda_bf16.h>
#include <stdint.h>

namespace {

constexpr int N_NODES = 10000;
constexpr int N_EDGES = 320000;
constexpr int NB      = 132;
constexpr int NPB     = 76;
constexpr int EPC     = 2425;
constexpr int SEG     = 2432;
constexpr int NTHR    = 384;
constexpr int K1      = 7;
constexpr int NG      = 5;
constexpr int STAGE   = 8704;
constexpr int TCAP    = 768;
constexpr int DCAP    = 3072;
constexpr int K2      = DCAP / NTHR;
constexpr int NBK     = 160;
constexpr int HS      = 161;

#define PACE_Q8 1190
#define PACE_LEAD 150

constexpr int SM_RING  = 0;
constexpr int SM_W     = 4 * NG * STAGE;
constexpr int SM_EM    = SM_W + 32768;
constexpr int SM_SRC   = SM_EM + 4 * TCAP * 4;
constexpr int SM_KEY   = SM_SRC + 4 * TCAP * 2;
constexpr int SM_LID   = SM_KEY + TCAP * 2;
constexpr int SM_BAR   = SM_LID + TCAP;
constexpr int SM_MISC  = SM_BAR + 2 * 4 * NG * 8;
constexpr int SM_TOTAL = SM_MISC + 2048;
constexpr int SC_HIST  = 80 * 1024;
constexpr int SC_SORT  = 0;
constexpr int SC_DENSE = 16 * 1024;
constexpr int SC_GC    = 48 * 1024;
constexpr int SC_GPOS  = 56 * 1024;
constexpr int SC_CUM   = 64 * 1024;
static_assert(SC_HIST + 20 * NBK * 4 <= 4 * NG * STAGE, "hist");
static_assert(NPB * 512 * 4 <= 4 * NG * STAGE, "slow tile");
static_assert(SM_TOTAL <= 232448, "smem");
constexpr int MI_CNT = 0;
constexpr int MI_INFO = 160;
constexpr int MI_TOT = 296;
constexpr int MI_DTOT = 320;
constexpr int MI_OVF = 321;
constexpr int MI_OFF = 328;

__device__ uint32_t g_seg[NB * SEG];
__device__ uint32_t g_flag[NB * 160];
#define STAMP(k)
#define STAMPT(k, t)

__device__ __forceinline__ uint32_t smem_u32(const void* p) { return (uint32_t)__cvta_generic_to_shared(p); }
__device__ __forceinline__ void mbar_init(uint32_t bar, int cnt) {
    asm volatile("mbarrier.init.shared.b64 [%0], %1;" ::"r"(bar), "r"(cnt) : "memory");
}
__device__ __forceinline__ bool mbar_try(uint32_t bar, uint32_t parity) {
    uint32_t ok;
    asm volatile("{\n.reg .pred p;\nmbarrier.try_wait.parity.shared.b64 p, [%1], %2;\nselp.u32 %0, 1, 0, p;\n}"
                 : "=r"(ok) : "r"(bar), "r"(parity) : "memory");
    return ok != 0;
}
__device__ __forceinline__ void mbar_wait(uint32_t bar, uint32_t parity) {
    if (mbar_try(bar, parity)) return;
    for (int i = 0; i < (1 << 22); i++)
        if (mbar_try(bar, parity)) return;
    __trap();
}
__device__ __forceinline__ void mbar_arrive(uint32_t bar) {
    asm volatile("mbarrier.arrive.shared.b64 _, [%0];" ::"r"(bar) : "memory");
}
__device__ __forceinline__ uint4 lds128(uint32_t a) {
    uint4 v;
    asm volatile("ld.shared.v4.u32 {%0,%1,%2,%3}, [%4];" : "=r"(v.x), "=r"(v.y), "=r"(v.z), "=r"(v.w) : "r"(a));
    return v;
}
__device__ __forceinline__ void sts128(uint32_t a, uint32_t x, uint32_t y, uint32_t z, uint32_t w) {
    asm volatile("st.shared.v4.u32 [%0], {%1,%2,%3,%4};" ::"r"(a), "r"(x), "r"(y), "r"(z), "r"(w) : "memory");
}
__device__ __forceinline__ uint32_t pack_bf16(float lo, float hi) {
    uint32_t r;
    asm("cvt.rn.bf16x2.f32 %0, %1, %2;" : "=r"(r) : "f"(hi), "f"(lo));
    return r;
}
__device__ __forceinline__ float tanh_fast(float x) {
    float r;
    asm("tanh.approx.f32 %0, %1;" : "=f"(r) : "f"(x));
    return r;
}
__device__ __forceinline__ uint32_t mul_lo(uint32_t v, uint32_t r) {
    __nv_bfloat162 a = *reinterpret_cast<__nv_bfloat162*>(&v), b = *reinterpret_cast<__nv_bfloat162*>(&r);
    __nv_bfloat162 c = __hmul2(a, __low2bfloat162(b));
    return *reinterpret_cast<uint32_t*>(&c);
}
__device__ __forceinline__ uint32_t mul_hi(uint32_t v, uint32_t r) {
    __nv_bfloat162 a = *reinterpret_cast<__nv_bfloat162*>(&v), b = *reinterpret_cast<__nv_bfloat162*>(&r);
    __nv_bfloat162 c = __hmul2(a, __high2bfloat162(b));
    return *reinterpret_cast<uint32_t*>(&c);
}
__device__ __forceinline__ void mma0(float (&d)[4], uint32_t a0, uint32_t a1, uint32_t a2, uint32_t a3,
                                     uint32_t b0, uint32_t b1) {
    asm("mma.sync.aligned.m16n8k16.row.col.f32.bf16.bf16.f32 {%0,%1,%2,%3}, {%4,%5,%6,%7}, {%8,%9}, {%10,%10,%10,%10};"
        : "=f"(d[0]), "=f"(d[1]), "=f"(d[2]), "=f"(d[3])
        : "r"(a0), "r"(a1), "r"(a2), "r"(a3), "r"(b0), "r"(b1), "f"(0.f));
}
__device__ __forceinline__ void mma_acc(float (&d)[4], const uint32_t (&a)[4], uint32_t b0, uint32_t b1) {
    asm volatile("mma.sync.aligned.m16n8k16.row.col.f32.bf16.bf16.f32 {%0,%1,%2,%3}, {%4,%5,%6,%7}, {%8,%9}, {%0,%1,%2,%3};"
        : "+f"(d[0]), "+f"(d[1]), "+f"(d[2]), "+f"(d[3])
        : "r"(a[0]), "r"(a[1]), "r"(a[2]), "r"(a[3]), "r"(b0), "r"(b1));
}
__device__ __forceinline__ void wgmma_n80(float (&d)[40], const uint32_t (&a)[4], uint64_t desc, int scale_d) {
    asm volatile("{\n.reg .pred p;\nsetp.ne.b32 p, %45, 0;\n"
        "wgmma.mma_async.sync.aligned.m64n80k16.f32.bf16.bf16 "
        "{%0,%1,%2,%3,%4,%5,%6,%7,%8,%9,%10,%11,%12,%13,%14,%15,%16,%17,%18,%19,"
        "%20,%21,%22,%23,%24,%25,%26,%27,%28,%29,%30,%31,%32,%33,%34,%35,%36,%37,%38,%39}, "
        "{%40,%41,%42,%43}, %44, p, 1, 1, 0;\n}"
        : "+f"(d[0]), "+f"(d[1]), "+f"(d[2]), "+f"(d[3]), "+f"(d[4]), "+f"(d[5]), "+f"(d[6]), "+f"(d[7]),
          "+f"(d[8]), "+f"(d[9]), "+f"(d[10]), "+f"(d[11]), "+f"(d[12]), "+f"(d[13]), "+f"(d[14]), "+f"(d[15]),
          "+f"(d[16]), "+f"(d[17]), "+f"(d[18]), "+f"(d[19]), "+f"(d[20]), "+f"(d[21]), "+f"(d[22]), "+f"(d[23]),
          "+f"(d[24]), "+f"(d[25]), "+f"(d[26]), "+f"(d[27]), "+f"(d[28]), "+f"(d[29]), "+f"(d[30]), "+f"(d[31]),
          "+f"(d[32]), "+f"(d[33]), "+f"(d[34]), "+f"(d[35]), "+f"(d[36]), "+f"(d[37]), "+f"(d[38]), "+f"(d[39])
        : "r"(a[0]), "r"(a[1]), "r"(a[2]), "r"(a[3]), "l"(desc), "r"(scale_d));
}

__device__ __forceinline__ void group_mma(float (&acc)[4][2][4], const uint32_t (&a)[4], const uint4 (&z)[4]) {
#pragma unroll
    for (int m = 0; m < 4; m++) {
        mma_acc(acc[m][0], a, z[m].x, z[m].y);
        mma_acc(acc[m][1], a, z[m].z, z[m].w);
    }
}

template <int PHASES>
__global__ void __launch_bounds__(NTHR, 1)
tfn_kernel(const __nv_bfloat16* __restrict__ x, const int* __restrict__ src, const int* __restrict__ dst,
           const __nv_bfloat16* __restrict__ Y, const __nv_bfloat16* __restrict__ ef,
           const __nv_bfloat16* __restrict__ w_rad, const __nv_bfloat16* __restrict__ cg,
           const __nv_bfloat16* __restrict__ w_mix, __nv_bfloat16* __restrict__ out) {
    extern __shared__ __align__(1024) uint8_t smem[];
    const int tid = threadIdx.x, lane = tid & 31, warp = tid >> 5;
    const int blk = blockIdx.x;
    const uint32_t sb = smem_u32(smem);
    int* mi = reinterpret_cast<int*>(smem + SM_MISC);
    STAMP(0);

    int d1[K1], s1[K1];
    if (PHASES & 1) {
#pragma unroll
        for (int k = 0; k < K1; k++) {
            int idx = tid + k * NTHR, e = blk * EPC + idx;
            bool ok = idx < EPC && e < N_EDGES;
            d1[k] = ok ? __ldg(dst + e) : -1;
            s1[k] = ok ? __ldg(src + e) : 0;
        }
        if (warp == 11) {
            constexpr int EFB = N_EDGES * 32 / NB / 16 * 16 + 16;
            constexpr int YB = N_EDGES * 8 / NB / 16 * 16 + 16;
            if (lane < 8) {
                int o = blk * EFB + lane * (EFB / 8 / 16 * 16 + 16);
                int n = min(EFB / 8 / 16 * 16 + 16, N_EDGES * 32 - o);
                if (n > 0) asm volatile("cp.async.bulk.prefetch.L2.global [%0], %1;" ::"l"((const char*)ef + o), "r"(n));
            } else if (lane < 10) {
                int o = blk * YB + (lane - 8) * (YB / 2 / 16 * 16 + 16);
                int n = min(YB / 2 / 16 * 16 + 16, N_EDGES * 8 - o);
                if (n > 0) asm volatile("cp.async.bulk.prefetch.L2.global [%0], %1;" ::"l"((const char*)Y + o), "r"(n));
            } else if (lane < 20) {
                int r = ((lane - 10) * NB + blk) * 8;
                int n = min(8, N_NODES - r) * 1024;
                if (n > 0) asm volatile("cp.async.bulk.prefetch.L2.global [%0], %1;" ::"l"((const char*)x + (size_t)r * 1024), "r"(n));
            }
        }
    }
    if (tid < 160) mi[MI_CNT + tid] = 0;
    if (PHASES & 2) {
        if (tid == 160) { mi[MI_DTOT] = 0; mi[MI_OVF] = 0; }
        if (tid == 192)
            for (int i = 0; i < 4 * NG; i++) { mbar_init(sb + SM_BAR + i * 8, 32); mbar_init(sb + SM_BAR + (4 * NG + i) * 8, 2); }
        for (int i = tid; i < 20 * NBK / 4; i += NTHR) sts128(sb + SC_HIST + i * 16, 0, 0, 0, 0);
        for (int i = tid; i < 4 * TCAP / 4; i += NTHR) sts128(sb + SM_EM + i * 16, 7u << 20, 7u << 20, 7u << 20, 7u << 20);
        for (int i = tid; i < (4 * TCAP * 2 + TCAP * 2 + TCAP) / 16; i += NTHR) sts128(sb + SM_SRC + i * 16, 0, 0, 0, 0);
    }
    __syncthreads();
    if (PHASES & 1) {
        int own[K1], rk[K1];
        uint32_t ent[K1];
#pragma unroll
        for (int k = 0; k < K1; k++) {
            if (d1[k] >= 0) {
                own[k] = d1[k] / NPB;
                int loc = d1[k] - own[k] * NPB;
                ent[k] = ((uint32_t)(s1[k] * NPB + loc) << 12) | (uint32_t)(tid + k * NTHR);
                rk[k] = atomicAdd(&mi[MI_CNT + own[k]], 1);
            }
        }
        STAMP(1);
        __syncthreads();
        if (warp == 0) {
            int c[5], s = 0;
#pragma unroll
            for (int j = 0; j < 5; j++) { c[j] = mi[MI_CNT + lane * 5 + j]; s += c[j]; }
            int inc = s;
#pragma unroll
            for (int o = 1; o < 32; o <<= 1) { int v = __shfl_up_sync(~0u, inc, o); if (lane >= o) inc += v; }
            int ex = inc - s;
#pragma unroll
            for (int j = 0; j < 5; j++) { mi[MI_OFF + lane * 5 + j] = ex; ex += c[j]; }
        }
        __syncthreads();
        uint32_t* sorted = reinterpret_cast<uint32_t*>(smem + SC_SORT);
#pragma unroll
        for (int k = 0; k < K1; k++)
            if (d1[k] >= 0) sorted[mi[MI_OFF + own[k]] + rk[k]] = ent[k];
        __syncthreads();
        for (int i = tid; i < SEG / 4; i += NTHR)
            reinterpret_cast<uint4*>(g_seg + blk * SEG)[i] = reinterpret_cast<const uint4*>(sorted)[i];
        __syncthreads();
        if (tid < NB) {
            uint32_t w = 0x80000000u | ((uint32_t)mi[MI_CNT + tid] << 12) | (uint32_t)mi[MI_OFF + tid];
            asm volatile("st.release.gpu.global.u32 [%0], %1;" ::"l"(g_flag + tid * 160 + blk), "r"(w) : "memory");
        }
        STAMP(2);
    }
    if (!(PHASES & 2)) return;

    for (int it = tid; it < 1024; it += NTHR) {
        int c = it >> 3, b = it & 7;
        const uint4* p = reinterpret_cast<const uint4*>(w_mix + c * 128 + b * 16);
        uint4 u = __ldg(p), v = __ldg(p + 1);
        int f = (c & 3) | (((c >> 4) & 1) << 2);
        uint32_t a = sb + SM_W + c * 256;
        sts128(a + (((2 * b) ^ f) << 4), __byte_perm(u.x, u.y, 0x5410), __byte_perm(u.z, u.w, 0x5410),
               __byte_perm(v.x, v.y, 0x5410), __byte_perm(v.z, v.w, 0x5410));
        sts128(a + (((2 * b + 1) ^ f) << 4), __byte_perm(u.x, u.y, 0x7632), __byte_perm(u.z, u.w, 0x7632),
               __byte_perm(v.x, v.y, 0x7632), __byte_perm(v.z, v.w, 0x7632));
    }

    uint32_t* hist = reinterpret_cast<uint32_t*>(smem + SC_HIST);
    uint2* dense = reinterpret_cast<uint2*>(smem + SC_DENSE);
    {
        uint32_t fw = 0;
        if (lane < 11) {
            uint32_t* fp = g_flag + blk * 160 + warp * 11 + lane;
            int it = 0;
            do {
                asm volatile("ld.acquire.gpu.global.u32 %0, [%1];" : "=r"(fw) : "l"(fp) : "memory");
                if (++it > (1 << 22)) __trap();
            } while (!(fw & 0x80000000u));
            *fp = 0;
            mi[MI_INFO + warp * 11 + lane] = fw;
        }
        __syncwarp();
        STAMP(3);
        int cnt = (fw >> 12) & 0xfff, inc = cnt;
#pragma unroll
        for (int o = 1; o < 16; o <<= 1) { int v = __shfl_up_sync(~0u, inc, o); if (lane >= o) inc += v; }
        int wbase = 0;
        if (lane == 10) wbase = atomicAdd(&mi[MI_DTOT], inc);
        wbase = __shfl_sync(~0u, wbase, 10);
        int mybase = wbase + inc - cnt;
        int maxc = __reduce_max_sync(~0u, cnt);
        for (int r0 = 0; r0 < maxc; r0 += 32) {
            uint32_t en[11];
#pragma unroll
            for (int j = 0; j < 11; j++) {
                uint32_t fj = __shfl_sync(~0u, fw, j);
                int cj = (fj >> 12) & 0xfff, oj = fj & 0xfff;
                en[j] = 0xffffffffu;
                if (r0 + lane < cj) en[j] = __ldcg(g_seg + (warp * 11 + j) * SEG + oj + r0 + lane);
            }
#pragma unroll
            for (int j = 0; j < 11; j++) {
                int bj = __shfl_sync(~0u, mybase, j) + r0 + lane;
                if (en[j] != 0xffffffffu && bj < DCAP) {
                    uint32_t key = en[j] >> 12;
                    uint32_t s = key / NPB, loc = key - s * NPB;
                    uint32_t team = loc / 19, r = loc - team * 19;
                    uint32_t l = team * 5 + (r >> 2);
                    uint32_t rank = atomicAdd(&hist[l * NBK + (s >> 6)], 1u);
                    uint32_t eid = (warp * 11 + j) * EPC + (en[j] & 0xfff);
                    dense[bj] = make_uint2(eid | ((r & 3) << 20) | (l << 24), s | (rank << 16));
                }
            }
        }
    }
    __syncthreads();
    STAMP(4);
    uint16_t* cum = reinterpret_cast<uint16_t*>(smem + SC_CUM);
    uint16_t* gc = reinterpret_cast<uint16_t*>(smem + SC_GC);
    uint16_t* gpos = reinterpret_cast<uint16_t*>(smem + SC_GPOS);
    for (int l = warp; l < 20; l += 12) {
        int c[5], s = 0;
#pragma unroll
        for (int j = 0; j < 5; j++) { c[j] = hist[l * NBK + lane * 5 + j]; s += c[j]; }
        int inc = s;
#pragma unroll
        for (int o = 1; o < 32; o <<= 1) { int v = __shfl_up_sync(~0u, inc, o); if (lane >= o) inc += v; }
        int tot = __shfl_sync(~0u, inc, 31);
        int ex = inc - s;
#pragma unroll
        for (int j = 0; j < 5; j++) {
            cum[l * NBK + lane * 5 + j] = ex;
            gc[l * HS + lane * 5 + j] = (ex == tot) ? (tot + 3) >> 2 : (ex + 1) >> 2;
            ex += c[j];
        }
        if (lane == 0) { gc[l * HS + NBK] = (tot + 3) >> 2; mi[MI_TOT + l] = tot; }
    }
    __syncthreads();
    const int dtot = mi[MI_DTOT];
    int ngrp[4];
    bool ovf = dtot > DCAP;
#pragma unroll
    for (int t = 0; t < 4; t++) {
        int s = 0;
#pragma unroll
        for (int l = 0; l < 5; l++) s += gc[(t * 5 + l) * HS + NBK];
        ngrp[t] = s;
        ovf |= s > TCAP / 4;
    }
    if (!ovf) {
        uint2 de[K2];
        int pp[K2];
        uint16_t* skey = reinterpret_cast<uint16_t*>(smem + SM_KEY);
        uint8_t* slid = smem + SM_LID;
#pragma unroll
        for (int k = 0; k < K2; k++) {
            int i = tid + k * NTHR;
            pp[k] = -1;
            if (i < dtot) {
                de[k] = dense[i];
                int l = de[k].x >> 24, s = de[k].y & 0xffff, b = s >> 6;
                int p = cum[l * NBK + b] + (de[k].y >> 16);
                pp[k] = p;
                if ((p & 3) == 2 || ((p & 3) < 2 && p == mi[MI_TOT + l] - 1)) {
                    int team = l / 5, ll = l - team * 5, g = p >> 2;
#pragma unroll
                    for (int q = 0; q < 5; q++)
                        if (q != ll) g += gc[(team * 5 + q) * HS + b + (q < ll ? 1 : 0)];
                    gpos[l * (TCAP / 4) + (p >> 2)] = g;
                    skey[team * (TCAP / 4) + g] = s;
                    slid[team * (TCAP / 4) + g] = ll;
                }
            }
        }
        __syncthreads();
        uint32_t* sem = reinterpret_cast<uint32_t*>(smem + SM_EM);
        uint16_t* ssrc = reinterpret_cast<uint16_t*>(smem + SM_SRC);
#pragma unroll
        for (int k = 0; k < K2; k++) {
            if (pp[k] >= 0) {
                int l = de[k].x >> 24, team = l / 5;
                int g = gpos[l * (TCAP / 4) + (pp[k] >> 2)], j = pp[k] & 3;
                int ub = team * TCAP + (g >> 1) * 8;
                ssrc[ub + (g & 1) * 4 + j] = de[k].y & 0xffff;
                sem[ub + j * 2 + (g & 1)] = de[k].x & 0xffffff;
            }
        }
    } else {
        __syncthreads();
        float* sagg = reinterpret_cast<float*>(smem);
        for (int i = tid; i < NPB * 512; i += NTHR) sagg[i] = 0.f;
        __syncthreads();
        const int c = tid & 127, q = tid >> 7;
        for (int i = 0; i < NB; i++) {
            uint32_t fw = mi[MI_INFO + i];
            int cnt = (fw >> 12) & 0xfff, off = fw & 0xfff;
            for (int r = q; r < cnt; r += 3) {
                uint32_t en = __ldcg(g_seg + i * SEG + off + r);
                uint32_t key = en >> 12, s = key / NPB, loc = key - s * NPB;
                int e = i * EPC + (en & 0xfff);
                float pre = 0.f;
                for (int k = 0; k < 16; k++)
                    pre += __bfloat162float(ef[e * 16 + k]) * __bfloat162float(w_rad[k * 128 + c]);
                float R = pre / (1.f + __expf(-pre));
                for (int o = 0; o < 4; o++) {
                    float v = 0.f;
                    for (int ii = 0; ii < 4; ii++) {
                        float a = 0.f;
                        for (int f = 0; f < 4; f++)
                            a += __bfloat162float(Y[e * 4 + f]) * __bfloat162float(cg[ii * 16 + f * 4 + o]);
                        v += __bfloat162float(x[(size_t)s * 512 + c * 4 + ii]) * a;
                    }
                    atomicAdd(&sagg[loc * 512 + c * 4 + o], R * v);
                }
            }
        }
        ngrp[0] = ngrp[1] = ngrp[2] = ngrp[3] = 0;
    }
    __syncthreads();
    STAMP(5);

    const int g = lane >> 2, t = lane & 3;
    if (warp >= 8) {
        asm volatile("setmaxnreg.dec.sync.aligned.u32 40;");
        const int team = warp - 8;
        const int nun = ((team == 0 ? ngrp[0] : team == 1 ? ngrp[1] : team == 2 ? ngrp[2] : ngrp[3]) + 1) >> 1;
        const uint32_t t0 = clock();
        const uint32_t ring = sb + SM_RING + team * NG * STAGE;
        const uint32_t barf = sb + SM_BAR + team * NG * 8, bare = barf + 4 * NG * 8;
        const char* xl = reinterpret_cast<const char*>(x) + lane * 16;
        const char* efl = reinterpret_cast<const char*>(ef) + t * 8;
        const char* yl = reinterpret_cast<const char*>(Y) + (t & 1) * 4;
        int st = 0;
        uint32_t ph = 1;
        for (int u = 0; u < nun; u++) {
            uint4 sv = lds128(sb + SM_SRC + (team * TCAP + u * 8) * 2);
            uint32_t em, key;
            asm volatile("ld.shared.u32 %0, [%1];" : "=r"(em) : "r"(sb + SM_EM + (team * TCAP + u * 8 + g) * 4));
            asm volatile("ld.shared.u16 %0, [%1];" : "=r"(key) : "r"(sb + SM_KEY + (team * (TCAP / 4) + u * 2) * 2));
            int due = (((int)key - PACE_LEAD) * PACE_Q8) >> 8;
            mbar_wait(bare + st * 8, ph);
            while ((int)(clock() - t0) < due) {}
            const uint32_t sa = ring + st * STAGE;
            const uint32_t ss[4] = {sv.x, sv.y, sv.z, sv.w};
#pragma unroll
            for (int j = 0; j < 8; j++) {
                uint32_t s = (j & 1) ? (ss[j >> 1] >> 16) : (ss[j >> 1] & 0xffff);
                const char* p = xl + (size_t)s * 1024;
                uint32_t d = sa + j * 1024 + ((lane ^ ((j & 3) << 1)) << 4);
                asm volatile("cp.async.cg.shared.global [%0], [%1], 16;" ::"r"(d), "l"(p) : "memory");
                asm volatile("cp.async.cg.shared.global [%0], [%1], 16;" ::"r"(d + 512), "l"(p + 512) : "memory");
            }
            const uint32_t eid = em & 0xfffff, nd = em >> 20;
            const uint32_t md = sa + 8192 + lane * 16;
            asm volatile("{\n.reg .pred p;\nsetp.gt.u32 p, %2, 3;\ncp.async.ca.shared.global [%0], [%1], 8, p;\n}"
                         ::"r"(md), "l"(efl + (size_t)eid * 32), "r"(nd) : "memory");
            asm volatile("{\n.reg .pred p;\nsetp.ne.u32 p, %2, %3;\ncp.async.ca.shared.global [%0], [%1], 4, p;\n}"
                         ::"r"(md + 8), "l"(yl + (size_t)eid * 8), "r"(nd), "r"(t >> 1) : "memory");
            asm volatile("{\n.reg .pred p;\nsetp.ne.u32 p, %2, %3;\ncp.async.ca.shared.global [%0], [%1], 4, p;\n}"
                         ::"r"(md + 12), "l"(yl + (size_t)eid * 8), "r"(nd), "r"(2 + (t >> 1)) : "memory");
            asm volatile("cp.async.mbarrier.arrive.noinc.shared.b64 [%0];" ::"r"(barf + st * 8) : "memory");
            if (++st == NG) { st = 0; ph ^= 1; }
        }
        STAMPT(6, 256);
    } else {
        asm volatile("setmaxnreg.inc.sync.aligned.u32 232;");
        const int team = warp >> 1, h = warp & 1;
        const int nun = ((team == 0 ? ngrp[0] : team == 1 ? ngrp[1] : team == 2 ? ngrp[2] : ngrp[3]) + 1) >> 1;
        float acc[5][4][2][4];
        if (!ovf) {
#pragma unroll
            for (int l = 0; l < 5; l++)
#pragma unroll
                for (int m = 0; m < 4; m++)
#pragma unroll
                    for (int p = 0; p < 2; p++)
#pragma unroll
                        for (int r = 0; r < 4; r++) acc[l][m][p][r] = 0.f;
        } else {
            const float* sagg = reinterpret_cast<const float*>(smem);
#pragma unroll
            for (int l = 0; l < 5; l++)
#pragma unroll
                for (int m = 0; m < 4; m++)
#pragma unroll
                    for (int p = 0; p < 2; p++)
#pragma unroll
                        for (int r = 0; r < 4; r++) {
                            int nd = l * 4 + (g >> 2) + (r >> 1) * 2;
                            int ch = h * 64 + m * 16 + 4 * t + (r & 1) * 2 + p;
                            acc[l][m][p][r] = nd < 19 ? sagg[(team * 19 + nd) * 512 + ch * 4 + (g & 3)] : 0.f;
                        }
        }
        uint32_t wf[4][4], cgf[4];
#pragma unroll
        for (int m = 0; m < 4; m++) {
            const int c0 = h * 64 + m * 16 + 2 * g;
            uint32_t w[4];
#pragma unroll
            for (int j = 0; j < 4; j++) {
                uint32_t v = __ldg(reinterpret_cast<const uint32_t*>(w_rad + (4 * t + j) * 128 + c0));
                w[j] = mul_lo(v, 0x3f003f00u);
            }
            wf[m][0] = __byte_perm(w[0], w[1], 0x5410);
            wf[m][1] = __byte_perm(w[0], w[1], 0x7632);
            wf[m][2] = __byte_perm(w[2], w[3], 0x5410);
            wf[m][3] = __byte_perm(w[2], w[3], 0x7632);
        }
#pragma unroll
        for (int i = 0; i < 4; i++) {
            const uint16_t* cgp = reinterpret_cast<const uint16_t*>(cg) + i * 16 + (t & 1) * 8 + (g & 3);
            uint32_t v = (uint32_t)__ldg(cgp) | ((uint32_t)__ldg(cgp + 4) << 16);
            cgf[i] = ((t >> 1) == (g >> 2)) ? v : 0u;
        }
        const uint32_t ring = sb + SM_RING + team * NG * STAGE;
        const uint32_t barf = sb + SM_BAR + team * NG * 8, bare = barf + 4 * NG * 8;
        const uint32_t xoff = t * 1024 + h * 512 + ((g ^ (t << 1)) << 4);
        int st = 0;
        uint32_t ph = 0;
        for (int u = 0; u < nun; u++) {
            uint32_t lid;
            asm volatile("ld.shared.u16 %0, [%1];" : "=r"(lid) : "r"(sb + SM_LID + team * (TCAP / 4) + u * 2));
            const uint32_t sa = ring + st * STAGE;
            mbar_wait(barf + st * 8, ph);
            const uint4 md = lds128(sa + 8192 + lane * 16);
            uint4 z[4];
#pragma unroll
            for (int m = 0; m < 4; m++) z[m] = lds128(sa + xoff + m * 128);
            uint32_t aA[4], aB[4], rA[4], rB[4];
            {
                float d0[4], d1_[4], d2[4], d3[4];
                mma0(d0, cgf[0], 0u, 0u, cgf[0], md.z, md.w);
                mma0(d1_, cgf[1], 0u, 0u, cgf[1], md.z, md.w);
                mma0(d2, cgf[2], 0u, 0u, cgf[2], md.z, md.w);
                mma0(d3, cgf[3], 0u, 0u, cgf[3], md.z, md.w);
                aA[0] = pack_bf16(d0[0], d1_[0]); aA[1] = pack_bf16(d0[2], d1_[2]);
                aA[2] = pack_bf16(d2[0], d3[0]);  aA[3] = pack_bf16(d2[2], d3[2]);
                aB[0] = pack_bf16(d0[1], d1_[1]); aB[1] = pack_bf16(d0[3], d1_[3]);
                aB[2] = pack_bf16(d2[1], d3[1]);  aB[3] = pack_bf16(d2[3], d3[3]);
            }
#pragma unroll
            for (int m = 0; m < 4; m++) {
                float d[4];
                mma0(d, wf[m][0], wf[m][1], wf[m][2], wf[m][3], md.x, md.y);
#pragma unroll
                for (int r = 0; r < 4; r++) d[r] = fmaf(d[r], tanh_fast(d[r]), d[r]);
                rA[m] = pack_bf16(d[0], d[2]);
                rB[m] = pack_bf16(d[1], d[3]);
            }
#pragma unroll
            for (int m = 0; m < 4; m++) {
                z[m].x = mul_lo(z[m].x, rA[m]); z[m].y = mul_lo(z[m].y, rA[m]);
                z[m].z = mul_hi(z[m].z, rA[m]); z[m].w = mul_hi(z[m].w, rA[m]);
            }
            switch (lid & 0xff) {
                case 0: group_mma(acc[0], aA, z); break;
                case 1: group_mma(acc[1], aA, z); break;
                case 2: group_mma(acc[2], aA, z); break;
                case 3: group_mma(acc[3], aA, z); break;
                default: group_mma(acc[4], aA, z); break;
            }
#pragma unroll
            for (int m = 0; m < 4; m++) z[m] = lds128(sa + xoff + 4096 + m * 128);
#pragma unroll
            for (int m = 0; m < 4; m++) {
                z[m].x = mul_lo(z[m].x, rB[m]); z[m].y = mul_lo(z[m].y, rB[m]);
                z[m].z = mul_hi(z[m].z, rB[m]); z[m].w = mul_hi(z[m].w, rB[m]);
            }
            __syncwarp();
            if (lane == 0) mbar_arrive(bare + st * 8);
            switch (lid >> 8) {
                case 0: group_mma(acc[0], aB, z); break;
                case 1: group_mma(acc[1], aB, z); break;
                case 2: group_mma(acc[2], aB, z); break;
                case 3: group_mma(acc[3], aB, z); break;
                default: group_mma(acc[4], aB, z); break;
            }
            if (++st == NG) { st = 0; ph ^= 1; }
        }
        STAMP(7);
        asm volatile("bar.sync 1, 256;" ::: "memory");
        {
            const int rr = ((g & 3) >> 1) * 8 + (g >> 2) * 2 + (g & 1);
#pragma unroll
            for (int l = 0; l < 5; l++)
#pragma unroll
                for (int hi = 0; hi < 2; hi++) {
                    const int R = team * 80 + l * 16 + rr + hi * 4;
                    const uint32_t a = sb + h * 40960 + R * 128;
#pragma unroll
                    for (int c = 0; c < 2; c++) {
                        const int m = 2 * c;
                        sts128(a + (((2 * t + c) ^ (R & 7)) << 4),
                               pack_bf16(acc[l][m][0][2 * hi], acc[l][m][1][2 * hi]),
                               pack_bf16(acc[l][m][0][2 * hi + 1], acc[l][m][1][2 * hi + 1]),
                               pack_bf16(acc[l][m + 1][0][2 * hi], acc[l][m + 1][1][2 * hi]),
                               pack_bf16(acc[l][m + 1][0][2 * hi + 1], acc[l][m + 1][1][2 * hi + 1]));
                    }
                }
        }
        asm volatile("fence.proxy.async.shared::cta;" ::: "memory");
        uint32_t wa[8][4];
        {
            const int r = lane & 7, k = (lane >> 4) * 8 + r;
            const int chunk = (2 * warp + ((lane >> 3) & 1)) ^ r;
#pragma unroll
            for (int ks = 0; ks < 8; ks++) {
                const int c = (ks >> 2) * 64 + 16 * (k >> 2) + 4 * (ks & 3) + (k & 3);
                asm volatile("ldmatrix.sync.aligned.m8n8.x4.trans.shared.b16 {%0,%1,%2,%3}, [%4];"
                             : "=r"(wa[ks][0]), "=r"(wa[ks][1]), "=r"(wa[ks][2]), "=r"(wa[ks][3])
                             : "r"(sb + SM_W + c * 256 + (chunk << 4)));
            }
        }
        asm volatile("bar.sync 1, 256;" ::: "memory");
        STAMP(8);
        float o[4][40];
        asm volatile("wgmma.fence.sync.aligned;" ::: "memory");
#pragma unroll
        for (int tm = 0; tm < 4; tm++) {
#pragma unroll
            for (int ks = 0; ks < 8; ks++) {
                const uint32_t a = sb + (ks >> 2) * 40960 + tm * 80 * 128 + (ks & 3) * 32;
                const uint64_t desc = (uint64_t)((a & 0x3ffff) >> 4) | (1ull << 16) | (64ull << 32) | (1ull << 62);
                wgmma_n80(o[tm], wa[ks], desc, ks);
            }
            asm volatile("wgmma.commit_group.sync.aligned;" ::: "memory");
        }
#pragma unroll
        for (int tm = 0; tm < 4; tm++) {
            if (tm == 0) asm volatile("wgmma.wait_group.sync.aligned 3;" ::: "memory");
            if (tm == 1) asm volatile("wgmma.wait_group.sync.aligned 2;" ::: "memory");
            if (tm == 2) asm volatile("wgmma.wait_group.sync.aligned 1;" ::: "memory");
            if (tm == 3) asm volatile("wgmma.wait_group.sync.aligned 0;" ::: "memory");
#pragma unroll
            for (int i = 0; i < 40; i++) asm volatile("" : "+f"(o[tm][i])::"memory");
#pragma unroll
            for (int l = 0; l < 5; l++) {
                const int nl = l * 4 + t, node = blk * NPB + tm * 19 + nl;
                if (nl < 19 && node < N_NODES) {
                    uint4 v;
                    v.x = pack_bf16(o[tm][8 * l + 0], o[tm][8 * l + 1]);
                    v.y = pack_bf16(o[tm][8 * l + 4], o[tm][8 * l + 5]);
                    v.z = pack_bf16(o[tm][8 * l + 2], o[tm][8 * l + 3]);
                    v.w = pack_bf16(o[tm][8 * l + 6], o[tm][8 * l + 7]);
                    *reinterpret_cast<uint4*>(out + (size_t)node * 512 + (warp * 16 + 2 * g) * 4) = v;
                }
            }
        }
        STAMP(9);
    }
}

}

extern "C" void kernel_launch(void* const* d_in, const int* in_sizes, int n_in, void* d_out, int out_size) {
    (void)in_sizes; (void)n_in; (void)out_size;
    const __nv_bfloat16* x = (const __nv_bfloat16*)d_in[0];
    const int* src = (const int*)d_in[1];
    const int* dst = (const int*)d_in[2];
    const __nv_bfloat16* Y = (const __nv_bfloat16*)d_in[3];
    const __nv_bfloat16* ef = (const __nv_bfloat16*)d_in[4];
    const __nv_bfloat16* w_rad = (const __nv_bfloat16*)d_in[5];
    const __nv_bfloat16* cg = (const __nv_bfloat16*)d_in[6];
    const __nv_bfloat16* w_mix = (const __nv_bfloat16*)d_in[7];
    __nv_bfloat16* out = (__nv_bfloat16*)d_out;

    static int sms = 0;
    if (sms == 0) {
        int dev = 0;
        cudaGetDevice(&dev);
        cudaDeviceGetAttribute(&sms, cudaDevAttrMultiProcessorCount, dev);
        cudaFuncSetAttribute(tfn_kernel<3>, cudaFuncAttributeMaxDynamicSharedMemorySize, SM_TOTAL);
        cudaFuncSetAttribute(tfn_kernel<1>, cudaFuncAttributeMaxDynamicSharedMemorySize, SM_TOTAL);
        cudaFuncSetAttribute(tfn_kernel<2>, cudaFuncAttributeMaxDynamicSharedMemorySize, SM_TOTAL);
    }
    if (sms >= NB) {
        tfn_kernel<3><<<NB, NTHR, SM_TOTAL>>>(x, src, dst, Y, ef, w_rad, cg, w_mix, out);
    } else {
        tfn_kernel<1><<<NB, NTHR, SM_TOTAL>>>(x, src, dst, Y, ef, w_rad, cg, w_mix, out);
        tfn_kernel<2><<<NB, NTHR, SM_TOTAL>>>(x, src, dst, Y, ef, w_rad, cg, w_mix, out);
    }
}
```

```cpp
#include <cuda_runtime.h>
#include <cuda_bf16.h>
#include <stdint.h>

namespace {

constexpr int N_NODES = 10000;
constexpr int N_EDGES = 320000;
constexpr int NB      = 132;
constexpr int NPB     = 76;
constexpr int NSRC    = 128;
constexpr int EPC     = N_EDGES / NSRC;
constexpr int NTHR    = 512;
#define NGS 5
constexpr int NG      = NGS;
constexpr int ROWP    = 2176;
constexpr int STAGE   = 4 * ROWP + 128;
constexpr int UCAP    = 104;
constexpr int REC     = 52;
constexpr int NBK     = 80;
constexpr int HS      = 81;

#define PACE_Q8 685
#define PACE_LEAD 150
#define POLL_DELAY 1350
#define LEAD_CLK 700
#define START_NS 4000

constexpr int SM_RING  = 0;
constexpr int SM_W     = 4 * NG * STAGE;
constexpr int SM_REC   = SM_W + 32768;
constexpr int SM_MISC  = SM_REC + 4 * UCAP * REC;
constexpr int SM_TOTAL = SM_MISC + 192;
constexpr int SC_MAIL  = 1 * STAGE;
constexpr int SC_CNT   = 3 * STAGE;
constexpr int SC_DUMP  = 3 * STAGE + 1024;
constexpr int SC_XTRA  = 3 * STAGE + 2048;
constexpr int SC_HIST  = 4 * STAGE;
constexpr int SC_GPOS  = 6 * STAGE;
constexpr int SC_WR    = 7 * STAGE;
constexpr int GDUMMY   = 1100;
static_assert(NPB * 512 * 4 <= 4 * NG * STAGE, "slow tile");
static_assert(SM_TOTAL <= 232448, "smem");
static_assert(SM_REC % 16 == 0 && (4 * UCAP * REC) % 16 == 0 && SM_MISC % 16 == 0, "align");
constexpr int MI_XN = 0;
constexpr int MI_ALLOC = 1;
constexpr int MI_TMAX = 2;
constexpr int MI_SHIFT = 7;
constexpr int MI_NU = 8;
constexpr int MI_T0 = 3;

__device__ uint4 g_mail[NB * NSRC * 8];
__device__ uint32_t g_mail2[NB * NSRC * 32];
__device__ __align__(128) int g_lag[32];
#define STAMP(k)

__device__ __forceinline__ uint32_t smem_u32(const void* p) { return (uint32_t)__cvta_generic_to_shared(p); }
__device__ __forceinline__ uint32_t atoms_inc(uint32_t a) {
    uint32_t r;
    asm volatile("atom.shared.add.u32 %0, [%1], 1;" : "=r"(r) : "r"(a) : "memory");
    return r;
}
__device__ __forceinline__ void sts32(uint32_t a, uint32_t v) { asm volatile("st.shared.u32 [%0], %1;" ::"r"(a), "r"(v) : "memory"); }
__device__ __forceinline__ void sts16(uint32_t a, uint32_t v) { asm volatile("st.shared.u16 [%0], %1;" ::"r"(a), "h"((uint16_t)v) : "memory"); }
__device__ __forceinline__ void sts8(uint32_t a, uint32_t v) { asm volatile("st.shared.u8 [%0], %1;" ::"r"(a), "r"(v) : "memory"); }
__device__ __forceinline__ uint32_t lds32(uint32_t a) { uint32_t v; asm volatile("ld.shared.u32 %0, [%1];" : "=r"(v) : "r"(a)); return v; }
__device__ __forceinline__ uint32_t lds16(uint32_t a) { uint32_t v; asm volatile("ld.shared.u16 %0, [%1];" : "=r"(v) : "r"(a)); return v; }
__device__ __forceinline__ void cp16(uint32_t d, const void* p) {
    asm volatile("cp.async.cg.shared.global [%0], [%1], 16;" ::"r"(d), "l"(p) : "memory");
}
__device__ __forceinline__ uint32_t gtime() {
    uint32_t t;
    asm volatile("mov.u32 %0, %%globaltimer_lo;" : "=r"(t));
    return t;
}
__device__ __forceinline__ void mbar_init(uint32_t bar, int cnt) {
    asm volatile("mbarrier.init.shared.b64 [%0], %1;" ::"r"(bar), "r"(cnt) : "memory");
}
__device__ __forceinline__ void mbar_wait(uint32_t bar, uint32_t parity) {
    asm volatile("{\n.reg .pred p;\n.reg .u32 n;\nmov.u32 n, 0;\n"
                 "WAIT_%=:\nmbarrier.try_wait.parity.shared.b64 p, [%0], %1;\n@p bra DONE_%=;\n"
                 "add.u32 n, n, 1;\nsetp.lt.u32 p, n, 4194304;\n@p bra WAIT_%=;\ntrap;\nDONE_%=:\n}"
                 ::"r"(bar), "r"(parity) : "memory");
}
__device__ __forceinline__ void mbar_arrive_elect(uint32_t bar) {
    asm volatile("{\n.reg .pred p;\nelect.sync _|p, 0xffffffff;\n@p mbarrier.arrive.shared.b64 _, [%0];\n}" ::"r"(bar) : "memory");
}
__device__ __forceinline__ uint4 lds128(uint32_t a) {
    uint4 v;
    asm volatile("ld.shared.v4.u32 {%0,%1,%2,%3}, [%4];" : "=r"(v.x), "=r"(v.y), "=r"(v.z), "=r"(v.w) : "r"(a));
    return v;
}
__device__ __forceinline__ void sts128(uint32_t a, uint32_t x, uint32_t y, uint32_t z, uint32_t w) {
    asm volatile("st.shared.v4.u32 [%0], {%1,%2,%3,%4};" ::"r"(a), "r"(x), "r"(y), "r"(z), "r"(w) : "memory");
}
__device__ __forceinline__ uint32_t pack_bf16(float lo, float hi) {
    uint32_t r;
    asm("cvt.rn.bf16x2.f32 %0, %1, %2;" : "=r"(r) : "f"(hi), "f"(lo));
    return r;
}
__device__ __forceinline__ float tanh_fast(float x) {
    float r;
    asm("tanh.approx.f32 %0, %1;" : "=f"(r) : "f"(x));
    return r;
}
__device__ __forceinline__ uint32_t mul_lo(uint32_t v, uint32_t r) {
    __nv_bfloat162 a = *reinterpret_cast<__nv_bfloat162*>(&v), b = *reinterpret_cast<__nv_bfloat162*>(&r);
    __nv_bfloat162 c = __hmul2(a, __low2bfloat162(b));
    return *reinterpret_cast<uint32_t*>(&c);
}
__device__ __forceinline__ uint32_t mul_hi(uint32_t v, uint32_t r) {
    __nv_bfloat162 a = *reinterpret_cast<__nv_bfloat162*>(&v), b = *reinterpret_cast<__nv_bfloat162*>(&r);
    __nv_bfloat162 c = __hmul2(a, __high2bfloat162(b));
    return *reinterpret_cast<uint32_t*>(&c);
}
__device__ __forceinline__ void mma0(float (&d)[4], uint32_t a0, uint32_t a1, uint32_t a2, uint32_t a3,
                                     uint32_t b0, uint32_t b1) {
    asm("mma.sync.aligned.m16n8k16.row.col.f32.bf16.bf16.f32 {%0,%1,%2,%3}, {%4,%5,%6,%7}, {%8,%9}, {%10,%10,%10,%10};"
        : "=f"(d[0]), "=f"(d[1]), "=f"(d[2]), "=f"(d[3])
        : "r"(a0), "r"(a1), "r"(a2), "r"(a3), "r"(b0), "r"(b1), "f"(0.f));
}
__device__ __forceinline__ void mma0_k8(float (&d)[4], uint32_t a0, uint32_t a1, uint32_t b0) {
    asm("mma.sync.aligned.m16n8k8.row.col.f32.bf16.bf16.f32 {%0,%1,%2,%3}, {%4,%5}, {%6}, {%7,%7,%7,%7};"
        : "=f"(d[0]), "=f"(d[1]), "=f"(d[2]), "=f"(d[3])
        : "r"(a0), "r"(a1), "r"(b0), "f"(0.f));
}
__device__ __forceinline__ void mma_acc(float (&d)[4], const uint32_t (&a)[4], uint32_t b0, uint32_t b1) {
    asm volatile("mma.sync.aligned.m16n8k16.row.col.f32.bf16.bf16.f32 {%0,%1,%2,%3}, {%4,%5,%6,%7}, {%8,%9}, {%0,%1,%2,%3};"
        : "+f"(d[0]), "+f"(d[1]), "+f"(d[2]), "+f"(d[3])
        : "r"(a[0]), "r"(a[1]), "r"(a[2]), "r"(a[3]), "r"(b0), "r"(b1));
}
__device__ __forceinline__ void wgmma_n80(float (&d)[40], const uint32_t (&a)[4], uint64_t desc, int scale_d) {
    asm volatile("{\n.reg .pred p;\nsetp.ne.b32 p, %45, 0;\n"
        "wgmma.mma_async.sync.aligned.m64n80k16.f32.bf16.bf16 "
        "{%0,%1,%2,%3,%4,%5,%6,%7,%8,%9,%10,%11,%12,%13,%14,%15,%16,%17,%18,%19,"
        "%20,%21,%22,%23,%24,%25,%26,%27,%28,%29,%30,%31,%32,%33,%34,%35,%36,%37,%38,%39}, "
        "{%40,%41,%42,%43}, %44, p, 1, 1, 0;\n}"
        : "+f"(d[0]), "+f"(d[1]), "+f"(d[2]), "+f"(d[3]), "+f"(d[4]), "+f"(d[5]), "+f"(d[6]), "+f"(d[7]),
          "+f"(d[8]), "+f"(d[9]), "+f"(d[10]), "+f"(d[11]), "+f"(d[12]), "+f"(d[13]), "+f"(d[14]), "+f"(d[15]),
          "+f"(d[16]), "+f"(d[17]), "+f"(d[18]), "+f"(d[19]), "+f"(d[20]), "+f"(d[21]), "+f"(d[22]), "+f"(d[23]),
          "+f"(d[24]), "+f"(d[25]), "+f"(d[26]), "+f"(d[27]), "+f"(d[28]), "+f"(d[29]), "+f"(d[30]), "+f"(d[31]),
          "+f"(d[32]), "+f"(d[33]), "+f"(d[34]), "+f"(d[35]), "+f"(d[36]), "+f"(d[37]), "+f"(d[38]), "+f"(d[39])
        : "r"(a[0]), "r"(a[1]), "r"(a[2]), "r"(a[3]), "l"(desc), "r"(scale_d));
}

__device__ __forceinline__ void producer_loop(const void* xl, const void* efl, const void* Y, uint32_t xd, uint32_t oef,
                                              uint32_t ysel, uint32_t ring, uint32_t rec, uint32_t rlast, uint32_t odd,
                                              uint32_t lead, uint32_t lag) {
    asm volatile(
        "{\n"
        ".reg .b32 w, em, ey, cu, d, t, u, n, sa, ph, rp, rend, rlast, dy, sv, lag, lv;\n"
        ".reg .b16 tg;\n"
        ".reg .b64 pa, pb, pc, pd;\n"
        ".reg .pred lo, z, q, e, zb;\n"
        "redux.sync.or.b32 sa, %6, 0xffffffff;\n"
        "redux.sync.or.b32 rp, %7, 0xffffffff;\n"
        "redux.sync.or.b32 rlast, %8, 0xffffffff;\n"
        "add.u32 rend, sa, 44160;\n"
        "and.b32 t, %5, 1;\n"
        "setp.eq.u32 lo, t, 0;\n"
        "mov.u32 ph, 1;\n"
        "setp.ne.u32 q, %9, 0;\n"
        "@q bra.uni PODD_%=;\n"
        "add.u32 t, rp, %4;\n"
        "ld.shared.u32 em, [t+16];\n"
        "ld.shared.u32 cu, [rp+48];\n"
        "and.b32 t, em, 0xfffffff8;\n"
        "mad.wide.u32 pa, t, 4, %1;\n"
        "add.u32 d, sa, %3;\n"
        "cvt.u16.u32 tg, cu;\n"
        "st.shared.u16 [sa+8720], tg;\n"
        "elect.sync _|z, 0xffffffff;\n"
        "@z mbarrier.arrive.shared.b64 _, [sa+8704];\n"
        "@lo cp.async.cg.shared.global [d+2048], [pa], 16;\n"
        "cp.async.mbarrier.arrive.noinc.shared.b64 [sa+8704];\n"
        "add.u32 rp, rp, 52;\n"
        "add.u32 sa, sa, 8832;\n"
        "PODD_%=:\n"
        "add.u32 rp, rp, 52;\n"
        "add.u32 sa, sa, 8832;\n"
        "and.b32 t, %4, 12;\n"
        "add.u32 t, t, rp;\n"
        "ld.shared.u32 w, [t];\n"
        "add.u32 t, rp, %4;\n"
        "ld.shared.u32 em, [t+16];\n"
        "ld.shared.u32 ey, [t+-36];\n"
        "ld.shared.u32 cu, [rp+48];\n"
        "setp.eq.u32 e, sa, sa;\n"
        "setp.lt.u32 q, rp, rlast;\n"
        "@!q bra.uni PF_%=;\n"
        "PL_%=:\n"
        "and.b32 t, em, 0xfffffff8;\n"
        "mad.wide.u32 pa, t, 4, %1;\n"
        "and.b32 t, w, 0xffff;\n"
        "mad.wide.u32 pc, t, 1024, %0;\n"
        "shr.u32 t, w, 16;\n"
        "mad.wide.u32 pd, t, 1024, %0;\n"
        "mov.u32 u, %%clock;\n"
        "shl.b32 u, u, 14;\n"
        "sub.u32 u, u, cu;\n"
        "setp.ge.and.s32 q, u, 0, e;\n"
        "@q bra.uni PGO_%=;\n"
        "mov.u32 n, 0;\n"
        "PW1_%=:\n"
        "@e bra.uni PW2_%=;\n"
        "mbarrier.try_wait.parity.shared.b64 e, [sa+8712], ph;\n"
        "add.u32 n, n, 1;\n"
        "setp.lt.u32 q, n, 4194304;\n"
        "@q bra.uni PW1_%=;\n"
        "trap;\n"
        "PW2_%=:\n"
        "mov.u32 u, %%clock;\n"
        "shl.b32 u, u, 14;\n"
        "sub.u32 u, u, cu;\n"
        "setp.lt.s32 q, u, 0;\n"
        "@q bra.uni PW2_%=;\n"
        "PGO_%=:\n"
        "add.u32 d, sa, %3;\n"
        "cvt.u16.u32 tg, cu;\n"
        "st.shared.u16 [sa+8720], tg;\n"
        "elect.sync _|z, 0xffffffff;\n"
        "@z mbarrier.arrive.shared.b64 _, [sa+8704];\n"
        "@lo cp.async.cg.shared.global [d+2048], [pa], 16;\n"
        "xor.b32 t, ey, %5;\n"
        "and.b32 t, t, 7;\n"
        "setp.ne.u32 zb, t, 0;\n"
        "and.b32 t, ey, 0xfffffff8;\n"
        "cvt.u64.u32 pb, t;\n"
        "add.u64 pb, pb, %2;\n"
        "selp.u32 dy, 64, 8, lo;\n"
        "xor.b32 dy, dy, d;\n"
        "cp.async.ca.shared.global [dy+2048], [pb], 8, zb;\n"
        "cp.async.cg.shared.global [d+0], [pc+0], 16;\n"
        "cp.async.cg.shared.global [d+128], [pc+128], 16;\n"
        "cp.async.cg.shared.global [d+256], [pc+256], 16;\n"
        "cp.async.cg.shared.global [d+384], [pc+384], 16;\n"
        "cp.async.cg.shared.global [d+512], [pc+512], 16;\n"
        "cp.async.cg.shared.global [d+640], [pc+640], 16;\n"
        "cp.async.cg.shared.global [d+768], [pc+768], 16;\n"
        "cp.async.cg.shared.global [d+896], [pc+896], 16;\n"
        "cp.async.cg.shared.global [d+1024], [pd+0], 16;\n"
        "cp.async.cg.shared.global [d+1152], [pd+128], 16;\n"
        "cp.async.cg.shared.global [d+1280], [pd+256], 16;\n"
        "cp.async.cg.shared.global [d+1408], [pd+384], 16;\n"
        "cp.async.cg.shared.global [d+1536], [pd+512], 16;\n"
        "cp.async.cg.shared.global [d+1664], [pd+640], 16;\n"
        "cp.async.cg.shared.global [d+1792], [pd+768], 16;\n"
        "cp.async.cg.shared.global [d+1920], [pd+896], 16;\n"
        "add.u32 rp, rp, 104;\n"
        "and.b32 t, %4, 12;\n"
        "add.u32 t, t, rp;\n"
        "ld.shared.u32 w, [t];\n"
        "add.u32 t, rp, %4;\n"
        "ld.shared.u32 em, [t+16];\n"
        "ld.shared.u32 ey, [t+-36];\n"
        "ld.shared.u32 cu, [rp+48];\n"
        "cp.async.mbarrier.arrive.noinc.shared.b64 [sa+8704];\n"
        "add.u32 sa, sa, 17664;\n"
        "sub.u32 t, sa, 44160;\n"
        "setp.ge.u32 q, sa, rend;\n"
        "selp.u32 sa, t, sa, q;\n"
        "selp.u32 t, 1, 0, q;\n"
        "xor.b32 ph, ph, t;\n"
        "mbarrier.try_wait.parity.shared.b64 e, [sa+8712], ph;\n"
        "setp.lt.u32 q, rp, rlast;\n"
        "@q bra.uni PL_%=;\n"
        "PF_%=:\n"
        "setp.ne.u32 q, rp, rlast;\n"
        "@q bra.uni PX_%=;\n"
        "mov.u32 n, 0;\n"
        "PE1_%=:\n"
        "@e bra.uni PE2_%=;\n"
        "mbarrier.try_wait.parity.shared.b64 e, [sa+8712], ph;\n"
        "add.u32 n, n, 1;\n"
        "setp.lt.u32 q, n, 4194304;\n"
        "@q bra.uni PE1_%=;\n"
        "trap;\n"
        "PE2_%=:\n"
        "cp.async.mbarrier.arrive.noinc.shared.b64 [sa+8704];\n"
        "elect.sync _|z, 0xffffffff;\n"
        "@z mbarrier.arrive.shared.b64 _, [sa+8704];\n"
        "PX_%=:\n"
        "}\n"
        ::"l"(xl), "l"(efl), "l"(Y), "r"(xd), "r"(oef), "r"(ysel), "r"(ring), "r"(rec), "r"(rlast), "r"(odd),
          "l"(g_lag), "r"(lead), "r"(lag) : "memory");
}

__device__ __forceinline__ void consumer_loop(float (&acc)[5][4][2][4], const uint32_t (&wf)[4][4], const uint32_t (&cgf)[4],
                                              uint32_t xoff, uint32_t& ring, uint32_t moff) {
    asm volatile(
        "{\n"
        ".reg .b32 x<16>, a<4>, b<4>, r<4>, m<4>, rl, rh, tag, la, lb, sa, last, ph, tq, xa, ma, n, ring, sn, ln, yb, zz, k<4>;\n"
        ".reg .b16 lo, hi;\n"
        ".reg .f32 p<16>, d<4>, t0, t1, fz;\n"
        ".reg .pred q, w, el, c<5>;\n"
        "TA_%=: .branchtargets A0_%=, A1_%=, A2_%=, A3_%=, A4_%=, EXIT_%=;\n"
        "TB_%=: .branchtargets B0_%=, B1_%=, B2_%=, B3_%=, B4_%=, SPIN_%=;\n"
        "mov.f32 fz, 0f00000000;\n"
        "redux.sync.or.b32 ring, %160, 0xffffffff;\n"
        "mov.u32 sa, ring;\n"
        "add.u32 last, ring, 35328;\n"
        "mov.u32 ph, 0;\n"
        "redux.sync.xor.b32 zz, %160, 0xffffffff;\n"
        "mov.u32 k0, sa;\n"
        "mov.u32 k1, sa;\n"
        "mov.u32 k2, sa;\n"
        "mov.u32 k3, sa;\n"
        "mov.b32 x0, 0;\n"
        "mov.b32 x1, 0;\n"
        "mov.b32 x2, 0;\n"
        "mov.b32 x3, 0;\n"
        "mov.b32 x4, 0;\n"
        "mov.b32 x5, 0;\n"
        "mov.b32 x6, 0;\n"
        "mov.b32 x7, 0;\n"
        "mov.b32 x8, 0;\n"
        "mov.b32 x9, 0;\n"
        "mov.b32 x10, 0;\n"
        "mov.b32 x11, 0;\n"
        "mov.b32 x12, 0;\n"
        "mov.b32 x13, 0;\n"
        "mov.b32 x14, 0;\n"
        "mov.b32 x15, 0;\n"
        "mov.b32 b0, 0;\n"
        "mov.b32 r0, 0;\n"
        "mov.b32 b1, 0;\n"
        "mov.b32 r1, 0;\n"
        "mov.b32 b2, 0;\n"
        "mov.b32 r2, 0;\n"
        "mov.b32 b3, 0;\n"
        "mov.b32 r3, 0;\n"
        "mov.u32 lb, 0;\n"
        "mov.u32 n, 0;\n"
        "W0_%=:\n"
        "mbarrier.try_wait.parity.shared.b64 w, [sa+8704], 0;\n"
        "@w bra.uni W0D_%=;\n"
        "add.u32 n, n, 1;\n"
        "setp.lt.u32 q, n, 4194304;\n"
        "@q bra.uni W0_%=;\n"
        "trap;\n"
        "W0D_%=:\n"
        "add.u32 ma, sa, %182;\n"
        "ldmatrix.sync.aligned.m8n8.x4.shared.b16 {m0,m1,m2,m3}, [ma];\n"
        "ld.shared.u16 tag, [k0+8720];\n"
        "add.u32 sn, sa, 8832;\n"
        "setp.eq.u32 q, sa, last;\n"
        "selp.u32 sn, ring, sn, q;\n"
        "selp.u32 tq, 1, 0, q;\n"
        "xor.b32 ph, ph, tq;\n"
        "mbarrier.test_wait.parity.shared.b64 w, [sn+8704], ph;\n"
        "mma.sync.aligned.m16n8k16.row.col.f32.bf16.bf16.f32 {p0,p1,p2,p3}, {%161,%162,%163,%164}, {m2,m3}, {fz,fz,fz,fz};\n"
        "mma.sync.aligned.m16n8k16.row.col.f32.bf16.bf16.f32 {p4,p5,p6,p7}, {%165,%166,%167,%168}, {m2,m3}, {fz,fz,fz,fz};\n"
        "mma.sync.aligned.m16n8k16.row.col.f32.bf16.bf16.f32 {p8,p9,p10,p11}, {%169,%170,%171,%172}, {m2,m3}, {fz,fz,fz,fz};\n"
        "mma.sync.aligned.m16n8k16.row.col.f32.bf16.bf16.f32 {p12,p13,p14,p15}, {%173,%174,%175,%176}, {m2,m3}, {fz,fz,fz,fz};\n"
        "elect.sync _|el, 0xffffffff;\n"
        "@el mbarrier.arrive.shared.b64 _, [k1+8712];\n"
        "redux.sync.or.b32 ln, tag, 0xffffffff;\n"
        "mov.u32 sa, sn;\n"
        "add.u32 k0, sn, zz;\n"
        "or.b32 k1, sn, zz;\n"
        "SPIN_%=:\n"
        "mov.u32 n, 0;\n"
        "SP1_%=:\n"
        "mbarrier.try_wait.parity.shared.b64 w, [sa+8704], ph;\n"
        "@w bra.uni SP2_%=;\n"
        "add.u32 n, n, 1;\n"
        "setp.lt.u32 q, n, 4194304;\n"
        "@q bra.uni SP1_%=;\n"
        "trap;\n"
        "SP2_%=:\n"
        "brx.idx.uni lb, TB_%=;\n"
        "A0_%=:\n"
        "add.u32 xa, sa, %181;\n"
        "add.u32 ma, sa, %182;\n"
        "ldmatrix.sync.aligned.m8n8.x4.shared.b16 {m0,m1,m2,m3}, [ma];\n"
        "ld.shared.u16 tag, [k0+8720];\n"
        "add.u32 sn, sa, 8832;\n"
        "setp.eq.u32 q, sa, last;\n"
        "selp.u32 sn, ring, sn, q;\n"
        "selp.u32 tq, 1, 0, q;\n"
        "xor.b32 ph, ph, tq;\n"
        "mbarrier.test_wait.parity.shared.b64 w, [sn+8704], ph;\n"
        "mma.sync.aligned.m16n8k16.row.col.f32.bf16.bf16.f32 {%0,%1,%2,%3}, {a0,a1,a2,a3}, {x0,x1}, {%0,%1,%2,%3};\n"
        "mma.sync.aligned.m16n8k16.row.col.f32.bf16.bf16.f32 {%4,%5,%6,%7}, {a0,a1,a2,a3}, {x2,x3}, {%4,%5,%6,%7};\n"
        "ld.shared.v4.u32 {x0,x1,x2,x3}, [xa+1024];\n"
        "tanh.approx.f32 t0, p1;\n"
        "tanh.approx.f32 t1, p3;\n"
        "fma.rn.f32 t0, p1, t0, p1;\n"
        "fma.rn.f32 t1, p3, t1, p3;\n"
        "cvt.rn.bf16x2.f32 r0, t1, t0;\n"
        "mma.sync.aligned.m16n8k16.row.col.f32.bf16.bf16.f32 {p0,p1,p2,p3}, {%161,%162,%163,%164}, {m2,m3}, {fz,fz,fz,fz};\n"
        "mma.sync.aligned.m16n8k16.row.col.f32.bf16.bf16.f32 {%8,%9,%10,%11}, {a0,a1,a2,a3}, {x4,x5}, {%8,%9,%10,%11};\n"
        "mma.sync.aligned.m16n8k16.row.col.f32.bf16.bf16.f32 {%12,%13,%14,%15}, {a0,a1,a2,a3}, {x6,x7}, {%12,%13,%14,%15};\n"
        "ld.shared.v4.u32 {x4,x5,x6,x7}, [xa+1152];\n"
        "mma.sync.aligned.m16n8k8.row.col.f32.bf16.bf16.f32 {d0,d1,d2,d3}, {%177,%178}, {m1}, {fz,fz,fz,fz};\n"
        "cvt.rn.bf16x2.f32 b0, d2, d0;\n"
        "cvt.rn.bf16x2.f32 b1, d3, d1;\n"
        "tanh.approx.f32 t0, p5;\n"
        "tanh.approx.f32 t1, p7;\n"
        "fma.rn.f32 t0, p5, t0, p5;\n"
        "fma.rn.f32 t1, p7, t1, p7;\n"
        "cvt.rn.bf16x2.f32 r1, t1, t0;\n"
        "mma.sync.aligned.m16n8k16.row.col.f32.bf16.bf16.f32 {p4,p5,p6,p7}, {%165,%166,%167,%168}, {m2,m3}, {fz,fz,fz,fz};\n"
        "mov.b32 {lo,hi}, r2;\n"
        "mov.b32 rl, {lo,lo};\n"
        "mov.b32 rh, {hi,hi};\n"
        "mul.bf16x2 x8, x8, rl;\n"
        "mul.bf16x2 x9, x9, rl;\n"
        "mul.bf16x2 x10, x10, rh;\n"
        "mul.bf16x2 x11, x11, rh;\n"
        "mma.sync.aligned.m16n8k16.row.col.f32.bf16.bf16.f32 {%16,%17,%18,%19}, {a0,a1,a2,a3}, {x8,x9}, {%16,%17,%18,%19};\n"
        "mma.sync.aligned.m16n8k16.row.col.f32.bf16.bf16.f32 {%20,%21,%22,%23}, {a0,a1,a2,a3}, {x10,x11}, {%20,%21,%22,%23};\n"
        "ld.shared.v4.u32 {x8,x9,x10,x11}, [xa+1280];\n"
        "mma.sync.aligned.m16n8k8.row.col.f32.bf16.bf16.f32 {d0,d1,d2,d3}, {%179,%180}, {m1}, {fz,fz,fz,fz};\n"
        "cvt.rn.bf16x2.f32 b2, d2, d0;\n"
        "cvt.rn.bf16x2.f32 b3, d3, d1;\n"
        "tanh.approx.f32 t0, p9;\n"
        "tanh.approx.f32 t1, p11;\n"
        "fma.rn.f32 t0, p9, t0, p9;\n"
        "fma.rn.f32 t1, p11, t1, p11;\n"
        "cvt.rn.bf16x2.f32 r2, t1, t0;\n"
        "mma.sync.aligned.m16n8k16.row.col.f32.bf16.bf16.f32 {p8,p9,p10,p11}, {%169,%170,%171,%172}, {m2,m3}, {fz,fz,fz,fz};\n"
        "selp.u32 tq, lb, 5, w;\n"
        "mov.b32 {lo,hi}, r3;\n"
        "mov.b32 rl, {lo,lo};\n"
        "mov.b32 rh, {hi,hi};\n"
        "mul.bf16x2 x12, x12, rl;\n"
        "mul.bf16x2 x13, x13, rl;\n"
        "mul.bf16x2 x14, x14, rh;\n"
        "mul.bf16x2 x15, x15, rh;\n"
        "mma.sync.aligned.m16n8k16.row.col.f32.bf16.bf16.f32 {%24,%25,%26,%27}, {a0,a1,a2,a3}, {x12,x13}, {%24,%25,%26,%27};\n"
        "mma.sync.aligned.m16n8k16.row.col.f32.bf16.bf16.f32 {%28,%29,%30,%31}, {a0,a1,a2,a3}, {x14,x15}, {%28,%29,%30,%31};\n"
        "ld.shared.v4.u32 {x12,x13,x14,x15}, [xa+1408];\n"
        "elect.sync _|el, 0xffffffff;\n"
        "@el mbarrier.arrive.shared.b64 _, [k1+8712];\n"
        "redux.sync.or.b32 ln, tag, 0xffffffff;\n"
        "mov.u32 sa, sn;\n"
        "add.u32 k0, sn, zz;\n"
        "or.b32 k1, sn, zz;\n"
        "tanh.approx.f32 t0, p13;\n"
        "tanh.approx.f32 t1, p15;\n"
        "fma.rn.f32 t0, p13, t0, p13;\n"
        "fma.rn.f32 t1, p15, t1, p15;\n"
        "cvt.rn.bf16x2.f32 r3, t1, t0;\n"
        "mma.sync.aligned.m16n8k16.row.col.f32.bf16.bf16.f32 {p12,p13,p14,p15}, {%173,%174,%175,%176}, {m2,m3}, {fz,fz,fz,fz};\n"
        "mov.b32 {lo,hi}, r0;\n"
        "mov.b32 rl, {lo,lo};\n"
        "mov.b32 rh, {hi,hi};\n"
        "mul.bf16x2 x0, x0, rl;\n"
        "mul.bf16x2 x1, x1, rl;\n"
        "mul.bf16x2 x2, x2, rh;\n"
        "mul.bf16x2 x3, x3, rh;\n"
        "mov.b32 {lo,hi}, r1;\n"
        "mov.b32 rl, {lo,lo};\n"
        "mov.b32 rh, {hi,hi};\n"
        "mul.bf16x2 x4, x4, rl;\n"
        "mul.bf16x2 x5, x5, rl;\n"
        "mul.bf16x2 x6, x6, rh;\n"
        "mul.bf16x2 x7, x7, rh;\n"
        "brx.idx.uni tq, TB_%=;\n"
        "A1_%=:\n"
        "add.u32 xa, sa, %181;\n"
        "add.u32 ma, sa, %182;\n"
        "ldmatrix.sync.aligned.m8n8.x4.shared.b16 {m0,m1,m2,m3}, [ma];\n"
        "ld.shared.u16 tag, [k0+8720];\n"
        "add.u32 sn, sa, 8832;\n"
        "setp.eq.u32 q, sa, last;\n"
        "selp.u32 sn, ring, sn, q;\n"
        "selp.u32 tq, 1, 0, q;\n"
        "xor.b32 ph, ph, tq;\n"
        "mbarrier.test_wait.parity.shared.b64 w, [sn+8704], ph;\n"
        "mma.sync.aligned.m16n8k16.row.col.f32.bf16.bf16.f32 {%32,%33,%34,%35}, {a0,a1,a2,a3}, {x0,x1}, {%32,%33,%34,%35};\n"
        "mma.sync.aligned.m16n8k16.row.col.f32.bf16.bf16.f32 {%36,%37,%38,%39}, {a0,a1,a2,a3}, {x2,x3}, {%36,%37,%38,%39};\n"
        "ld.shared.v4.u32 {x0,x1,x2,x3}, [xa+1024];\n"
        "tanh.approx.f32 t0, p1;\n"
        "tanh.approx.f32 t1, p3;\n"
        "fma.rn.f32 t0, p1, t0, p1;\n"
        "fma.rn.f32 t1, p3, t1, p3;\n"
        "cvt.rn.bf16x2.f32 r0, t1, t0;\n"
        "mma.sync.aligned.m16n8k16.row.col.f32.bf16.bf16.f32 {p0,p1,p2,p3}, {%161,%162,%163,%164}, {m2,m3}, {fz,fz,fz,fz};\n"
        "mma.sync.aligned.m16n8k16.row.col.f32.bf16.bf16.f32 {%40,%41,%42,%43}, {a0,a1,a2,a3}, {x4,x5}, {%40,%41,%42,%43};\n"
        "mma.sync.aligned.m16n8k16.row.col.f32.bf16.bf16.f32 {%44,%45,%46,%47}, {a0,a1,a2,a3}, {x6,x7}, {%44,%45,%46,%47};\n"
        "ld.shared.v4.u32 {x4,x5,x6,x7}, [xa+1152];\n"
        "mma.sync.aligned.m16n8k8.row.col.f32.bf16.bf16.f32 {d0,d1,d2,d3}, {%177,%178}, {m1}, {fz,fz,fz,fz};\n"
        "cvt.rn.bf16x2.f32 b0, d2, d0;\n"
        "cvt.rn.bf16x2.f32 b1, d3, d1;\n"
        "tanh.approx.f32 t0, p5;\n"
        "tanh.approx.f32 t1, p7;\n"
        "fma.rn.f32 t0, p5, t0, p5;\n"
        "fma.rn.f32 t1, p7, t1, p7;\n"
        "cvt.rn.bf16x2.f32 r1, t1, t0;\n"
        "mma.sync.aligned.m16n8k16.row.col.f32.bf16.bf16.f32 {p4,p5,p6,p7}, {%165,%166,%167,%168}, {m2,m3}, {fz,fz,fz,fz};\n"
        "mov.b32 {lo,hi}, r2;\n"
        "mov.b32 rl, {lo,lo};\n"
        "mov.b32 rh, {hi,hi};\n"
        "mul.bf16x2 x8, x8, rl;\n"
        "mul.bf16x2 x9, x9, rl;\n"
        "mul.bf16x2 x10, x10, rh;\n"
        "mul.bf16x2 x11, x11, rh;\n"
        "mma.sync.aligned.m16n8k16.row.col.f32.bf16.bf16.f32 {%48,%49,%50,%51}, {a0,a1,a2,a3}, {x8,x9}, {%48,%49,%50,%51};\n"
        "mma.sync.aligned.m16n8k16.row.col.f32.bf16.bf16.f32 {%52,%53,%54,%55}, {a0,a1,a2,a3}, {x10,x11}, {%52,%53,%54,%55};\n"
        "ld.shared.v4.u32 {x8,x9,x10,x11}, [xa+1280];\n"
        "mma.sync.aligned.m16n8k8.row.col.f32.bf16.bf16.f32 {d0,d1,d2,d3}, {%179,%180}, {m1}, {fz,fz,fz,fz};\n"
        "cvt.rn.bf16x2.f32 b2, d2, d0;\n"
        "cvt.rn.bf16x2.f32 b3, d3, d1;\n"
        "tanh.approx.f32 t0, p9;\n"
        "tanh.approx.f32 t1, p11;\n"
        "fma.rn.f32 t0, p9, t0, p9;\n"
        "fma.rn.f32 t1, p11, t1, p11;\n"
        "cvt.rn.bf16x2.f32 r2, t1, t0;\n"
        "mma.sync.aligned.m16n8k16.row.col.f32.bf16.bf16.f32 {p8,p9,p10,p11}, {%169,%170,%171,%172}, {m2,m3}, {fz,fz,fz,fz};\n"
        "selp.u32 tq, lb, 5, w;\n"
        "mov.b32 {lo,hi}, r3;\n"
        "mov.b32 rl, {lo,lo};\n"
        "mov.b32 rh, {hi,hi};\n"
        "mul.bf16x2 x12, x12, rl;\n"
        "mul.bf16x2 x13, x13, rl;\n"
        "mul.bf16x2 x14, x14, rh;\n"
        "mul.bf16x2 x15, x15, rh;\n"
        "mma.sync.aligned.m16n8k16.row.col.f32.bf16.bf16.f32 {%56,%57,%58,%59}, {a0,a1,a2,a3}, {x12,x13}, {%56,%57,%58,%59};\n"
        "mma.sync.aligned.m16n8k16.row.col.f32.bf16.bf16.f32 {%60,%61,%62,%63}, {a0,a1,a2,a3}, {x14,x15}, {%60,%61,%62,%63};\n"
        "ld.shared.v4.u32 {x12,x13,x14,x15}, [xa+1408];\n"
        "elect.sync _|el, 0xffffffff;\n"
        "@el mbarrier.arrive.shared.b64 _, [k1+8712];\n"
        "redux.sync.or.b32 ln, tag, 0xffffffff;\n"
        "mov.u32 sa, sn;\n"
        "add.u32 k0, sn, zz;\n"
        "or.b32 k1, sn, zz;\n"
        "tanh.approx.f32 t0, p13;\n"
        "tanh.approx.f32 t1, p15;\n"
        "fma.rn.f32 t0, p13, t0, p13;\n"
        "fma.rn.f32 t1, p15, t1, p15;\n"
        "cvt.rn.bf16x2.f32 r3, t1, t0;\n"
        "mma.sync.aligned.m16n8k16.row.col.f32.bf16.bf16.f32 {p12,p13,p14,p15}, {%173,%174,%175,%176}, {m2,m3}, {fz,fz,fz,fz};\n"
        "mov.b32 {lo,hi}, r0;\n"
        "mov.b32 rl, {lo,lo};\n"
        "mov.b32 rh, {hi,hi};\n"
        "mul.bf16x2 x0, x0, rl;\n"
        "mul.bf16x2 x1, x1, rl;\n"
        "mul.bf16x2 x2, x2, rh;\n"
        "mul.bf16x2 x3, x3, rh;\n"
        "mov.b32 {lo,hi}, r1;\n"
        "mov.b32 rl, {lo,lo};\n"
        "mov.b32 rh, {hi,hi};\n"
        "mul.bf16x2 x4, x4, rl;\n"
        "mul.bf16x2 x5, x5, rl;\n"
        "mul.bf16x2 x6, x6, rh;\n"
        "mul.bf16x2 x7, x7, rh;\n"
        "brx.idx.uni tq, TB_%=;\n"
        "A2_%=:\n"
        "add.u32 xa, sa, %181;\n"
        "add.u32 ma, sa, %182;\n"
        "ldmatrix.sync.aligned.m8n8.x4.shared.b16 {m0,m1,m2,m3}, [ma];\n"
        "ld.shared.u16 tag, [k0+8720];\n"
        "add.u32 sn, sa, 8832;\n"
        "setp.eq.u32 q, sa, last;\n"
        "selp.u32 sn, ring, sn, q;\n"
        "selp.u32 tq, 1, 0, q;\n"
        "xor.b32 ph, ph, tq;\n"
        "mbarrier.test_wait.parity.shared.b64 w, [sn+8704], ph;\n"
        "mma.sync.aligned.m16n8k16.row.col.f32.bf16.bf16.f32 {%64,%65,%66,%67}, {a0,a1,a2,a3}, {x0,x1}, {%64,%65,%66,%67};\n"
        "mma.sync.aligned.m16n8k16.row.col.f32.bf16.bf16.f32 {%68,%69,%70,%71}, {a0,a1,a2,a3}, {x2,x3}, {%68,%69,%70,%71};\n"
        "ld.shared.v4.u32 {x0,x1,x2,x3}, [xa+1024];\n"
        "tanh.approx.f32 t0, p1;\n"
        "tanh.approx.f32 t1, p3;\n"
        "fma.rn.f32 t0, p1, t0, p1;\n"
        "fma.rn.f32 t1, p3, t1, p3;\n"
        "cvt.rn.bf16x2.f32 r0, t1, t0;\n"
        "mma.sync.aligned.m16n8k16.row.col.f32.bf16.bf16.f32 {p0,p1,p2,p3}, {%161,%162,%163,%164}, {m2,m3}, {fz,fz,fz,fz};\n"
        "mma.sync.aligned.m16n8k16.row.col.f32.bf16.bf16.f32 {%72,%73,%74,%75}, {a0,a1,a2,a3}, {x4,x5}, {%72,%73,%74,%75};\n"
        "mma.sync.aligned.m16n8k16.row.col.f32.bf16.bf16.f32 {%76,%77,%78,%79}, {a0,a1,a2,a3}, {x6,x7}, {%76,%77,%78,%79};\n"
        "ld.shared.v4.u32 {x4,x5,x6,x7}, [xa+1152];\n"
        "mma.sync.aligned.m16n8k8.row.col.f32.bf16.bf16.f32 {d0,d1,d2,d3}, {%177,%178}, {m1}, {fz,fz,fz,fz};\n"
        "cvt.rn.bf16x2.f32 b0, d2, d0;\n"
        "cvt.rn.bf16x2.f32 b1, d3, d1;\n"
        "tanh.approx.f32 t0, p5;\n"
        "tanh.approx.f32 t1, p7;\n"
        "fma.rn.f32 t0, p5, t0, p5;\n"
        "fma.rn.f32 t1, p7, t1, p7;\n"
        "cvt.rn.bf16x2.f32 r1, t1, t0;\n"
        "mma.sync.aligned.m16n8k16.row.col.f32.bf16.bf16.f32 {p4,p5,p6,p7}, {%165,%166,%167,%168}, {m2,m3}, {fz,fz,fz,fz};\n"
        "mov.b32 {lo,hi}, r2;\n"
        "mov.b32 rl, {lo,lo};\n"
        "mov.b32 rh, {hi,hi};\n"
        "mul.bf16x2 x8, x8, rl;\n"
        "mul.bf16x2 x9, x9, rl;\n"
        "mul.bf16x2 x10, x10, rh;\n"
        "mul.bf16x2 x11, x11, rh;\n"
        "mma.sync.aligned.m16n8k16.row.col.f32.bf16.bf16.f32 {%80,%81,%82,%83}, {a0,a1,a2,a3}, {x8,x9}, {%80,%81,%82,%83};\n"
        "mma.sync.aligned.m16n8k16.row.col.f32.bf16.bf16.f32 {%84,%85,%86,%87}, {a0,a1,a2,a3}, {x10,x11}, {%84,%85,%86,%87};\n"
        "ld.shared.v4.u32 {x8,x9,x10,x11}, [xa+1280];\n"
        "mma.sync.aligned.m16n8k8.row.col.f32.bf16.bf16.f32 {d0,d1,d2,d3}, {%179,%180}, {m1}, {fz,fz,fz,fz};\n"
        "cvt.rn.bf16x2.f32 b2, d2, d0;\n"
        "cvt.rn.bf16x2.f32 b3, d3, d1;\n"
        "tanh.approx.f32 t0, p9;\n"
        "tanh.approx.f32 t1, p11;\n"
        "fma.rn.f32 t0, p9, t0, p9;\n"
        "fma.rn.f32 t1, p11, t1, p11;\n"
        "cvt.rn.bf16x2.f32 r2, t1, t0;\n"
        "mma.sync.aligned.m16n8k16.row.col.f32.bf16.bf16.f32 {p8,p9,p10,p11}, {%169,%170,%171,%172}, {m2,m3}, {fz,fz,fz,fz};\n"
        "selp.u32 tq, lb, 5, w;\n"
        "mov.b32 {lo,hi}, r3;\n"
        "mov.b32 rl, {lo,lo};\n"
        "mov.b32 rh, {hi,hi};\n"
        "mul.bf16x2 x12, x12, rl;\n"
        "mul.bf16x2 x13, x13, rl;\n"
        "mul.bf16x2 x14, x14, rh;\n"
        "mul.bf16x2 x15, x15, rh;\n"
        "mma.sync.aligned.m16n8k16.row.col.f32.bf16.bf16.f32 {%88,%89,%90,%91}, {a0,a1,a2,a3}, {x12,x13}, {%88,%89,%90,%91};\n"
        "mma.sync.aligned.m16n8k16.row.col.f32.bf16.bf16.f32 {%92,%93,%94,%95}, {a0,a1,a2,a3}, {x14,x15}, {%92,%93,%94,%95};\n"
        "ld.shared.v4.u32 {x12,x13,x14,x15}, [xa+1408];\n"
        "elect.sync _|el, 0xffffffff;\n"
        "@el mbarrier.arrive.shared.b64 _, [k1+8712];\n"
        "redux.sync.or.b32 ln, tag, 0xffffffff;\n"
        "mov.u32 sa, sn;\n"
        "add.u32 k0, sn, zz;\n"
        "or.b32 k1, sn, zz;\n"
        "tanh.approx.f32 t0, p13;\n"
        "tanh.approx.f32 t1, p15;\n"
        "fma.rn.f32 t0, p13, t0, p13;\n"
        "fma.rn.f32 t1, p15, t1, p15;\n"
        "cvt.rn.bf16x2.f32 r3, t1, t0;\n"
        "mma.sync.aligned.m16n8k16.row.col.f32.bf16.bf16.f32 {p12,p13,p14,p15}, {%173,%174,%175,%176}, {m2,m3}, {fz,fz,fz,fz};\n"
        "mov.b32 {lo,hi}, r0;\n"
        "mov.b32 rl, {lo,lo};\n"
        "mov.b32 rh, {hi,hi};\n"
        "mul.bf16x2 x0, x0, rl;\n"
        "mul.bf16x2 x1, x1, rl;\n"
        "mul.bf16x2 x2, x2, rh;\n"
        "mul.bf16x2 x3, x3, rh;\n"
        "mov.b32 {lo,hi}, r1;\n"
        "mov.b32 rl, {lo,lo};\n"
        "mov.b32 rh, {hi,hi};\n"
        "mul.bf16x2 x4, x4, rl;\n"
        "mul.bf16x2 x5, x5, rl;\n"
        "mul.bf16x2 x6, x6, rh;\n"
        "mul.bf16x2 x7, x7, rh;\n"
        "brx.idx.uni tq, TB_%=;\n"
        "A3_%=:\n"
        "add.u32 xa, sa, %181;\n"
        "add.u32 ma, sa, %182;\n"
        "ldmatrix.sync.aligned.m8n8.x4.shared.b16 {m0,m1,m2,m3}, [ma];\n"
        "ld.shared.u16 tag, [k0+8720];\n"
        "add.u32 sn, sa, 8832;\n"
        "setp.eq.u32 q, sa, last;\n"
        "selp.u32 sn, ring, sn, q;\n"
        "selp.u32 tq, 1, 0, q;\n"
        "xor.b32 ph, ph, tq;\n"
        "mbarrier.test_wait.parity.shared.b64 w, [sn+8704], ph;\n"
        "mma.sync.aligned.m16n8k16.row.col.f32.bf16.bf16.f32 {%96,%97,%98,%99}, {a0,a1,a2,a3}, {x0,x1}, {%96,%97,%98,%99};\n"
        "mma.sync.aligned.m16n8k16.row.col.f32.bf16.bf16.f32 {%100,%101,%102,%103}, {a0,a1,a2,a3}, {x2,x3}, {%100,%101,%102,%103};\n"
        "ld.shared.v4.u32 {x0,x1,x2,x3}, [xa+1024];\n"
        "tanh.approx.f32 t0, p1;\n"
        "tanh.approx.f32 t1, p3;\n"
        "fma.rn.f32 t0, p1, t0, p1;\n"
        "fma.rn.f32 t1, p3, t1, p3;\n"
        "cvt.rn.bf16x2.f32 r0, t1, t0;\n"
        "mma.sync.aligned.m16n8k16.row.col.f32.bf16.bf16.f32 {p0,p1,p2,p3}, {%161,%162,%163,%164}, {m2,m3}, {fz,fz,fz,fz};\n"
        "mma.sync.aligned.m16n8k16.row.col.f32.bf16.bf16.f32 {%104,%105,%106,%107}, {a0,a1,a2,a3}, {x4,x5}, {%104,%105,%106,%107};\n"
        "mma.sync.aligned.m16n8k16.row.col.f32.bf16.bf16.f32 {%108,%109,%110,%111}, {a0,a1,a2,a3}, {x6,x7}, {%108,%109,%110,%111};\n"
        "ld.shared.v4.u32 {x4,x5,x6,x7}, [xa+1152];\n"
        "mma.sync.aligned.m16n8k8.row.col.f32.bf16.bf16.f32 {d0,d1,d2,d3}, {%177,%178}, {m1}, {fz,fz,fz,fz};\n"
        "cvt.rn.bf16x2.f32 b0, d2, d0;\n"
        "cvt.rn.bf16x2.f32 b1, d3, d1;\n"
        "tanh.approx.f32 t0, p5;\n"
        "tanh.approx.f32 t1, p7;\n"
        "fma.rn.f32 t0, p5, t0, p5;\n"
        "fma.rn.f32 t1, p7, t1, p7;\n"
        "cvt.rn.bf16x2.f32 r1, t1, t0;\n"
        "mma.sync.aligned.m16n8k16.row.col.f32.bf16.bf16.f32 {p4,p5,p6,p7}, {%165,%166,%167,%168}, {m2,m3}, {fz,fz,fz,fz};\n"
        "mov.b32 {lo,hi}, r2;\n"
        "mov.b32 rl, {lo,lo};\n"
        "mov.b32 rh, {hi,hi};\n"
        "mul.bf16x2 x8, x8, rl;\n"
        "mul.bf16x2 x9, x9, rl;\n"
        "mul.bf16x2 x10, x10, rh;\n"
        "mul.bf16x2 x11, x11, rh;\n"
        "mma.sync.aligned.m16n8k16.row.col.f32.bf16.bf16.f32 {%112,%113,%114,%115}, {a0,a1,a2,a3}, {x8,x9}, {%112,%113,%114,%115};\n"
        "mma.sync.aligned.m16n8k16.row.col.f32.bf16.bf16.f32 {%116,%117,%118,%119}, {a0,a1,a2,a3}, {x10,x11}, {%116,%117,%118,%119};\n"
        "ld.shared.v4.u32 {x8,x9,x10,x11}, [xa+1280];\n"
        "mma.sync.aligned.m16n8k8.row.col.f32.bf16.bf16.f32 {d0,d1,d2,d3}, {%179,%180}, {m1}, {fz,fz,fz,fz};\n"
        "cvt.rn.bf16x2.f32 b2, d2, d0;\n"
        "cvt.rn.bf16x2.f32 b3, d3, d1;\n"
        "tanh.approx.f32 t0, p9;\n"
        "tanh.approx.f32 t1, p11;\n"
        "fma.rn.f32 t0, p9, t0, p9;\n"
        "fma.rn.f32 t1, p11, t1, p11;\n"
        "cvt.rn.bf16x2.f32 r2, t1, t0;\n"
        "mma.sync.aligned.m16n8k16.row.col.f32.bf16.bf16.f32 {p8,p9,p10,p11}, {%169,%170,%171,%172}, {m2,m3}, {fz,fz,fz,fz};\n"
        "selp.u32 tq, lb, 5, w;\n"
        "mov.b32 {lo,hi}, r3;\n"
        "mov.b32 rl, {lo,lo};\n"
        "mov.b32 rh, {hi,hi};\n"
        "mul.bf16x2 x12, x12, rl;\n"
        "mul.bf16x2 x13, x13, rl;\n"
        "mul.bf16x2 x14, x14, rh;\n"
        "mul.bf16x2 x15, x15, rh;\n"
        "mma.sync.aligned.m16n8k16.row.col.f32.bf16.bf16.f32 {%120,%121,%122,%123}, {a0,a1,a2,a3}, {x12,x13}, {%120,%121,%122,%123};\n"
        "mma.sync.aligned.m16n8k16.row.col.f32.bf16.bf16.f32 {%124,%125,%126,%127}, {a0,a1,a2,a3}, {x14,x15}, {%124,%125,%126,%127};\n"
        "ld.shared.v4.u32 {x12,x13,x14,x15}, [xa+1408];\n"
        "elect.sync _|el, 0xffffffff;\n"
        "@el mbarrier.arrive.shared.b64 _, [k1+8712];\n"
        "redux.sync.or.b32 ln, tag, 0xffffffff;\n"
        "mov.u32 sa, sn;\n"
        "add.u32 k0, sn, zz;\n"
        "or.b32 k1, sn, zz;\n"
        "tanh.approx.f32 t0, p13;\n"
        "tanh.approx.f32 t1, p15;\n"
        "fma.rn.f32 t0, p13, t0, p13;\n"
        "fma.rn.f32 t1, p15, t1, p15;\n"
        "cvt.rn.bf16x2.f32 r3, t1, t0;\n"
        "mma.sync.aligned.m16n8k16.row.col.f32.bf16.bf16.f32 {p12,p13,p14,p15}, {%173,%174,%175,%176}, {m2,m3}, {fz,fz,fz,fz};\n"
        "mov.b32 {lo,hi}, r0;\n"
        "mov.b32 rl, {lo,lo};\n"
        "mov.b32 rh, {hi,hi};\n"
        "mul.bf16x2 x0, x0, rl;\n"
        "mul.bf16x2 x1, x1, rl;\n"
        "mul.bf16x2 x2, x2, rh;\n"
        "mul.bf16x2 x3, x3, rh;\n"
        "mov.b32 {lo,hi}, r1;\n"
        "mov.b32 rl, {lo,lo};\n"
        "mov.b32 rh, {hi,hi};\n"
        "mul.bf16x2 x4, x4, rl;\n"
        "mul.bf16x2 x5, x5, rl;\n"
        "mul.bf16x2 x6, x6, rh;\n"
        "mul.bf16x2 x7, x7, rh;\n"
        "brx.idx.uni tq, TB_%=;\n"
        "A4_%=:\n"
        "add.u32 xa, sa, %181;\n"
        "add.u32 ma, sa, %182;\n"
        "ldmatrix.sync.aligned.m8n8.x4.shared.b16 {m0,m1,m2,m3}, [ma];\n"
        "ld.shared.u16 tag, [k0+8720];\n"
        "add.u32 sn, sa, 8832;\n"
        "setp.eq.u32 q, sa, last;\n"
        "selp.u32 sn, ring, sn, q;\n"
        "selp.u32 tq, 1, 0, q;\n"
        "xor.b32 ph, ph, tq;\n"
        "mbarrier.test_wait.parity.shared.b64 w, [sn+8704], ph;\n"
        "mma.sync.aligned.m16n8k16.row.col.f32.bf16.bf16.f32 {%128,%129,%130,%131}, {a0,a1,a2,a3}, {x0,x1}, {%128,%129,%130,%131};\n"
        "mma.sync.aligned.m16n8k16.row.col.f32.bf16.bf16.f32 {%132,%133,%134,%135}, {a0,a1,a2,a3}, {x2,x3}, {%132,%133,%134,%135};\n"
        "ld.shared.v4.u32 {x0,x1,x2,x3}, [xa+1024];\n"
        "tanh.approx.f32 t0, p1;\n"
        "tanh.approx.f32 t1, p3;\n"
        "fma.rn.f32 t0, p1, t0, p1;\n"
        "fma.rn.f32 t1, p3, t1, p3;\n"
        "cvt.rn.bf16x2.f32 r0, t1, t0;\n"
        "mma.sync.aligned.m16n8k16.row.col.f32.bf16.bf16.f32 {p0,p1,p2,p3}, {%161,%162,%163,%164}, {m2,m3}, {fz,fz,fz,fz};\n"
        "mma.sync.aligned.m16n8k16.row.col.f32.bf16.bf16.f32 {%136,%137,%138,%139}, {a0,a1,a2,a3}, {x4,x5}, {%136,%137,%138,%139};\n"
        "mma.sync.aligned.m16n8k16.row.col.f32.bf16.bf16.f32 {%140,%141,%142,%143}, {a0,a1,a2,a3}, {x6,x7}, {%140,%141,%142,%143};\n"
        "ld.shared.v4.u32 {x4,x5,x6,x7}, [xa+1152];\n"
        "mma.sync.aligned.m16n8k8.row.col.f32.bf16.bf16.f32 {d0,d1,d2,d3}, {%177,%178}, {m1}, {fz,fz,fz,fz};\n"
        "cvt.rn.bf16x2.f32 b0, d2, d0;\n"
        "cvt.rn.bf16x2.f32 b1, d3, d1;\n"
        "tanh.approx.f32 t0, p5;\n"
        "tanh.approx.f32 t1, p7;\n"
        "fma.rn.f32 t0, p5, t0, p5;\n"
        "fma.rn.f32 t1, p7, t1, p7;\n"
        "cvt.rn.bf16x2.f32 r1, t1, t0;\n"
        "mma.sync.aligned.m16n8k16.row.col.f32.bf16.bf16.f32 {p4,p5,p6,p7}, {%165,%166,%167,%168}, {m2,m3}, {fz,fz,fz,fz};\n"
        "mov.b32 {lo,hi}, r2;\n"
        "mov.b32 rl, {lo,lo};\n"
        "mov.b32 rh, {hi,hi};\n"
        "mul.bf16x2 x8, x8, rl;\n"
        "mul.bf16x2 x9, x9, rl;\n"
        "mul.bf16x2 x10, x10, rh;\n"
        "mul.bf16x2 x11, x11, rh;\n"
        "mma.sync.aligned.m16n8k16.row.col.f32.bf16.bf16.f32 {%144,%145,%146,%147}, {a0,a1,a2,a3}, {x8,x9}, {%144,%145,%146,%147};\n"
        "mma.sync.aligned.m16n8k16.row.col.f32.bf16.bf16.f32 {%148,%149,%150,%151}, {a0,a1,a2,a3}, {x10,x11}, {%148,%149,%150,%151};\n"
        "ld.shared.v4.u32 {x8,x9,x10,x11}, [xa+1280];\n"
        "mma.sync.aligned.m16n8k8.row.col.f32.bf16.bf16.f32 {d0,d1,d2,d3}, {%179,%180}, {m1}, {fz,fz,fz,fz};\n"
        "cvt.rn.bf16x2.f32 b2, d2, d0;\n"
        "cvt.rn.bf16x2.f32 b3, d3, d1;\n"
        "tanh.approx.f32 t0, p9;\n"
        "tanh.approx.f32 t1, p11;\n"
        "fma.rn.f32 t0, p9, t0, p9;\n"
        "fma.rn.f32 t1, p11, t1, p11;\n"
        "cvt.rn.bf16x2.f32 r2, t1, t0;\n"
        "mma.sync.aligned.m16n8k16.row.col.f32.bf16.bf16.f32 {p8,p9,p10,p11}, {%169,%170,%171,%172}, {m2,m3}, {fz,fz,fz,fz};\n"
        "selp.u32 tq, lb, 5, w;\n"
        "mov.b32 {lo,hi}, r3;\n"
        "mov.b32 rl, {lo,lo};\n"
        "mov.b32 rh, {hi,hi};\n"
        "mul.bf16x2 x12, x12, rl;\n"
        "mul.bf16x2 x13, x13, rl;\n"
        "mul.bf16x2 x14, x14, rh;\n"
        "mul.bf16x2 x15, x15, rh;\n"
        "mma.sync.aligned.m16n8k16.row.col.f32.bf16.bf16.f32 {%152,%153,%154,%155}, {a0,a1,a2,a3}, {x12,x13}, {%152,%153,%154,%155};\n"
        "mma.sync.aligned.m16n8k16.row.col.f32.bf16.bf16.f32 {%156,%157,%158,%159}, {a0,a1,a2,a3}, {x14,x15}, {%156,%157,%158,%159};\n"
        "ld.shared.v4.u32 {x12,x13,x14,x15}, [xa+1408];\n"
        "elect.sync _|el, 0xffffffff;\n"
        "@el mbarrier.arrive.shared.b64 _, [k1+8712];\n"
        "redux.sync.or.b32 ln, tag, 0xffffffff;\n"
        "mov.u32 sa, sn;\n"
        "add.u32 k0, sn, zz;\n"
        "or.b32 k1, sn, zz;\n"
        "tanh.approx.f32 t0, p13;\n"
        "tanh.approx.f32 t1, p15;\n"
        "fma.rn.f32 t0, p13, t0, p13;\n"
        "fma.rn.f32 t1, p15, t1, p15;\n"
        "cvt.rn.bf16x2.f32 r3, t1, t0;\n"
        "mma.sync.aligned.m16n8k16.row.col.f32.bf16.bf16.f32 {p12,p13,p14,p15}, {%173,%174,%175,%176}, {m2,m3}, {fz,fz,fz,fz};\n"
        "mov.b32 {lo,hi}, r0;\n"
        "mov.b32 rl, {lo,lo};\n"
        "mov.b32 rh, {hi,hi};\n"
        "mul.bf16x2 x0, x0, rl;\n"
        "mul.bf16x2 x1, x1, rl;\n"
        "mul.bf16x2 x2, x2, rh;\n"
        "mul.bf16x2 x3, x3, rh;\n"
        "mov.b32 {lo,hi}, r1;\n"
        "mov.b32 rl, {lo,lo};\n"
        "mov.b32 rh, {hi,hi};\n"
        "mul.bf16x2 x4, x4, rl;\n"
        "mul.bf16x2 x5, x5, rl;\n"
        "mul.bf16x2 x6, x6, rh;\n"
        "mul.bf16x2 x7, x7, rh;\n"
        "brx.idx.uni tq, TB_%=;\n"
        "B0_%=:\n"
        "and.b32 la, ln, 255;\n"
        "shr.u32 lb, ln, 8;\n"
        "add.u32 ma, sa, %182;\n"
        "ldmatrix.sync.aligned.m8n8.x1.shared.b16 {yb}, [ma];\n"
        "add.u32 xa, sa, %181;\n"
        "mma.sync.aligned.m16n8k16.row.col.f32.bf16.bf16.f32 {%0,%1,%2,%3}, {b0,b1,b2,b3}, {x0,x1}, {%0,%1,%2,%3};\n"
        "mma.sync.aligned.m16n8k16.row.col.f32.bf16.bf16.f32 {%4,%5,%6,%7}, {b0,b1,b2,b3}, {x2,x3}, {%4,%5,%6,%7};\n"
        "ld.shared.v4.u32 {x0,x1,x2,x3}, [xa+0];\n"
        "tanh.approx.f32 t0, p0;\n"
        "tanh.approx.f32 t1, p2;\n"
        "fma.rn.f32 t0, p0, t0, p0;\n"
        "fma.rn.f32 t1, p2, t1, p2;\n"
        "cvt.rn.bf16x2.f32 r0, t1, t0;\n"
        "mma.sync.aligned.m16n8k16.row.col.f32.bf16.bf16.f32 {%8,%9,%10,%11}, {b0,b1,b2,b3}, {x4,x5}, {%8,%9,%10,%11};\n"
        "mma.sync.aligned.m16n8k16.row.col.f32.bf16.bf16.f32 {%12,%13,%14,%15}, {b0,b1,b2,b3}, {x6,x7}, {%12,%13,%14,%15};\n"
        "ld.shared.v4.u32 {x4,x5,x6,x7}, [xa+128];\n"
        "tanh.approx.f32 t0, p4;\n"
        "tanh.approx.f32 t1, p6;\n"
        "fma.rn.f32 t0, p4, t0, p4;\n"
        "fma.rn.f32 t1, p6, t1, p6;\n"
        "cvt.rn.bf16x2.f32 r1, t1, t0;\n"
        "mma.sync.aligned.m16n8k8.row.col.f32.bf16.bf16.f32 {d0,d1,d2,d3}, {%177,%178}, {yb}, {fz,fz,fz,fz};\n"
        "cvt.rn.bf16x2.f32 a0, d2, d0;\n"
        "cvt.rn.bf16x2.f32 a1, d3, d1;\n"
        "mov.b32 {lo,hi}, r2;\n"
        "mov.b32 rl, {lo,lo};\n"
        "mov.b32 rh, {hi,hi};\n"
        "mul.bf16x2 x8, x8, rl;\n"
        "mul.bf16x2 x9, x9, rl;\n"
        "mul.bf16x2 x10, x10, rh;\n"
        "mul.bf16x2 x11, x11, rh;\n"
        "mma.sync.aligned.m16n8k16.row.col.f32.bf16.bf16.f32 {%16,%17,%18,%19}, {b0,b1,b2,b3}, {x8,x9}, {%16,%17,%18,%19};\n"
        "mma.sync.aligned.m16n8k16.row.col.f32.bf16.bf16.f32 {%20,%21,%22,%23}, {b0,b1,b2,b3}, {x10,x11}, {%20,%21,%22,%23};\n"
        "ld.shared.v4.u32 {x8,x9,x10,x11}, [xa+256];\n"
        "tanh.approx.f32 t0, p8;\n"
        "tanh.approx.f32 t1, p10;\n"
        "fma.rn.f32 t0, p8, t0, p8;\n"
        "fma.rn.f32 t1, p10, t1, p10;\n"
        "cvt.rn.bf16x2.f32 r2, t1, t0;\n"
        "mma.sync.aligned.m16n8k8.row.col.f32.bf16.bf16.f32 {d0,d1,d2,d3}, {%179,%180}, {yb}, {fz,fz,fz,fz};\n"
        "cvt.rn.bf16x2.f32 a2, d2, d0;\n"
        "cvt.rn.bf16x2.f32 a3, d3, d1;\n"
        "mov.b32 {lo,hi}, r3;\n"
        "mov.b32 rl, {lo,lo};\n"
        "mov.b32 rh, {hi,hi};\n"
        "mul.bf16x2 x12, x12, rl;\n"
        "mul.bf16x2 x13, x13, rl;\n"
        "mul.bf16x2 x14, x14, rh;\n"
        "mul.bf16x2 x15, x15, rh;\n"
        "mma.sync.aligned.m16n8k16.row.col.f32.bf16.bf16.f32 {%24,%25,%26,%27}, {b0,b1,b2,b3}, {x12,x13}, {%24,%25,%26,%27};\n"
        "mma.sync.aligned.m16n8k16.row.col.f32.bf16.bf16.f32 {%28,%29,%30,%31}, {b0,b1,b2,b3}, {x14,x15}, {%28,%29,%30,%31};\n"
        "ld.shared.v4.u32 {x12,x13,x14,x15}, [xa+384];\n"
        "tanh.approx.f32 t0, p12;\n"
        "tanh.approx.f32 t1, p14;\n"
        "fma.rn.f32 t0, p12, t0, p12;\n"
        "fma.rn.f32 t1, p14, t1, p14;\n"
        "cvt.rn.bf16x2.f32 r3, t1, t0;\n"
        "mov.b32 {lo,hi}, r0;\n"
        "mov.b32 rl, {lo,lo};\n"
        "mov.b32 rh, {hi,hi};\n"
        "mul.bf16x2 x0, x0, rl;\n"
        "mul.bf16x2 x1, x1, rl;\n"
        "mul.bf16x2 x2, x2, rh;\n"
        "mul.bf16x2 x3, x3, rh;\n"
        "mov.b32 {lo,hi}, r1;\n"
        "mov.b32 rl, {lo,lo};\n"
        "mov.b32 rh, {hi,hi};\n"
        "mul.bf16x2 x4, x4, rl;\n"
        "mul.bf16x2 x5, x5, rl;\n"
        "mul.bf16x2 x6, x6, rh;\n"
        "mul.bf16x2 x7, x7, rh;\n"
        "brx.idx.uni la, TA_%=;\n"
        "B1_%=:\n"
        "and.b32 la, ln, 255;\n"
        "shr.u32 lb, ln, 8;\n"
        "add.u32 ma, sa, %182;\n"
        "ldmatrix.sync.aligned.m8n8.x1.shared.b16 {yb}, [ma];\n"
        "add.u32 xa, sa, %181;\n"
        "mma.sync.aligned.m16n8k16.row.col.f32.bf16.bf16.f32 {%32,%33,%34,%35}, {b0,b1,b2,b3}, {x0,x1}, {%32,%33,%34,%35};\n"
        "mma.sync.aligned.m16n8k16.row.col.f32.bf16.bf16.f32 {%36,%37,%38,%39}, {b0,b1,b2,b3}, {x2,x3}, {%36,%37,%38,%39};\n"
        "ld.shared.v4.u32 {x0,x1,x2,x3}, [xa+0];\n"
        "tanh.approx.f32 t0, p0;\n"
        "tanh.approx.f32 t1, p2;\n"
        "fma.rn.f32 t0, p0, t0, p0;\n"
        "fma.rn.f32 t1, p2, t1, p2;\n"
        "cvt.rn.bf16x2.f32 r0, t1, t0;\n"
        "mma.sync.aligned.m16n8k16.row.col.f32.bf16.bf16.f32 {%40,%41,%42,%43}, {b0,b1,b2,b3}, {x4,x5}, {%40,%41,%42,%43};\n"
        "mma.sync.aligned.m16n8k16.row.col.f32.bf16.bf16.f32 {%44,%45,%46,%47}, {b0,b1,b2,b3}, {x6,x7}, {%44,%45,%46,%47};\n"
        "ld.shared.v4.u32 {x4,x5,x6,x7}, [xa+128];\n"
        "tanh.approx.f32 t0, p4;\n"
        "tanh.approx.f32 t1, p6;\n"
        "fma.rn.f32 t0, p4, t0, p4;\n"
        "fma.rn.f32 t1, p6, t1, p6;\n"
        "cvt.rn.bf16x2.f32 r1, t1, t0;\n"
        "mma.sync.aligned.m16n8k8.row.col.f32.bf16.bf16.f32 {d0,d1,d2,d3}, {%177,%178}, {yb}, {fz,fz,fz,fz};\n"
        "cvt.rn.bf16x2.f32 a0, d2, d0;\n"
        "cvt.rn.bf16x2.f32 a1, d3, d1;\n"
        "mov.b32 {lo,hi}, r2;\n"
        "mov.b32 rl, {lo,lo};\n"
        "mov.b32 rh, {hi,hi};\n"
        "mul.bf16x2 x8, x8, rl;\n"
        "mul.bf16x2 x9, x9, rl;\n"
        "mul.bf16x2 x10, x10, rh;\n"
        "mul.bf16x2 x11, x11, rh;\n"
        "mma.sync.aligned.m16n8k16.row.col.f32.bf16.bf16.f32 {%48,%49,%50,%51}, {b0,b1,b2,b3}, {x8,x9}, {%48,%49,%50,%51};\n"
        "mma.sync.aligned.m16n8k16.row.col.f32.bf16.bf16.f32 {%52,%53,%54,%55}, {b0,b1,b2,b3}, {x10,x11}, {%52,%53,%54,%55};\n"
        "ld.shared.v4.u32 {x8,x9,x10,x11}, [xa+256];\n"
        "tanh.approx.f32 t0, p8;\n"
        "tanh.approx.f32 t1, p10;\n"
        "fma.rn.f32 t0, p8, t0, p8;\n"
        "fma.rn.f32 t1, p10, t1, p10;\n"
        "cvt.rn.bf16x2.f32 r2, t1, t0;\n"
        "mma.sync.aligned.m16n8k8.row.col.f32.bf16.bf16.f32 {d0,d1,d2,d3}, {%179,%180}, {yb}, {fz,fz,fz,fz};\n"
        "cvt.rn.bf16x2.f32 a2, d2, d0;\n"
        "cvt.rn.bf16x2.f32 a3, d3, d1;\n"
        "mov.b32 {lo,hi}, r3;\n"
        "mov.b32 rl, {lo,lo};\n"
        "mov.b32 rh, {hi,hi};\n"
        "mul.bf16x2 x12, x12, rl;\n"
        "mul.bf16x2 x13, x13, rl;\n"
        "mul.bf16x2 x14, x14, rh;\n"
        "mul.bf16x2 x15, x15, rh;\n"
        "mma.sync.aligned.m16n8k16.row.col.f32.bf16.bf16.f32 {%56,%57,%58,%59}, {b0,b1,b2,b3}, {x12,x13}, {%56,%57,%58,%59};\n"
        "mma.sync.aligned.m16n8k16.row.col.f32.bf16.bf16.f32 {%60,%61,%62,%63}, {b0,b1,b2,b3}, {x14,x15}, {%60,%61,%62,%63};\n"
        "ld.shared.v4.u32 {x12,x13,x14,x15}, [xa+384];\n"
        "tanh.approx.f32 t0, p12;\n"
        "tanh.approx.f32 t1, p14;\n"
        "fma.rn.f32 t0, p12, t0, p12;\n"
        "fma.rn.f32 t1, p14, t1, p14;\n"
        "cvt.rn.bf16x2.f32 r3, t1, t0;\n"
        "mov.b32 {lo,hi}, r0;\n"
        "mov.b32 rl, {lo,lo};\n"
        "mov.b32 rh, {hi,hi};\n"
        "mul.bf16x2 x0, x0, rl;\n"
        "mul.bf16x2 x1, x1, rl;\n"
        "mul.bf16x2 x2, x2, rh;\n"
        "mul.bf16x2 x3, x3, rh;\n"
        "mov.b32 {lo,hi}, r1;\n"
        "mov.b32 rl, {lo,lo};\n"
        "mov.b32 rh, {hi,hi};\n"
        "mul.bf16x2 x4, x4, rl;\n"
        "mul.bf16x2 x5, x5, rl;\n"
        "mul.bf16x2 x6, x6, rh;\n"
        "mul.bf16x2 x7, x7, rh;\n"
        "brx.idx.uni la, TA_%=;\n"
        "B2_%=:\n"
        "and.b32 la, ln, 255;\n"
        "shr.u32 lb, ln, 8;\n"
        "add.u32 ma, sa, %182;\n"
        "ldmatrix.sync.aligned.m8n8.x1.shared.b16 {yb}, [ma];\n"
        "add.u32 xa, sa, %181;\n"
        "mma.sync.aligned.m16n8k16.row.col.f32.bf16.bf16.f32 {%64,%65,%66,%67}, {b0,b1,b2,b3}, {x0,x1}, {%64,%65,%66,%67};\n"
        "mma.sync.aligned.m16n8k16.row.col.f32.bf16.bf16.f32 {%68,%69,%70,%71}, {b0,b1,b2,b3}, {x2,x3}, {%68,%69,%70,%71};\n"
        "ld.shared.v4.u32 {x0,x1,x2,x3}, [xa+0];\n"
        "tanh.approx.f32 t0, p0;\n"
        "tanh.approx.f32 t1, p2;\n"
        "fma.rn.f32 t0, p0, t0, p0;\n"
        "fma.rn.f32 t1, p2, t1, p2;\n"
        "cvt.rn.bf16x2.f32 r0, t1, t0;\n"
        "mma.sync.aligned.m16n8k16.row.col.f32.bf16.bf16.f32 {%72,%73,%74,%75}, {b0,b1,b2,b3}, {x4,x5}, {%72,%73,%74,%75};\n"
        "mma.sync.aligned.m16n8k16.row.col.f32.bf16.bf16.f32 {%76,%77,%78,%79}, {b0,b1,b2,b3}, {x6,x7}, {%76,%77,%78,%79};\n"
        "ld.shared.v4.u32 {x4,x5,x6,x7}, [xa+128];\n"
        "tanh.approx.f32 t0, p4;\n"
        "tanh.approx.f32 t1, p6;\n"
        "fma.rn.f32 t0, p4, t0, p4;\n"
        "fma.rn.f32 t1, p6, t1, p6;\n"
        "cvt.rn.bf16x2.f32 r1, t1, t0;\n"
        "mma.sync.aligned.m16n8k8.row.col.f32.bf16.bf16.f32 {d0,d1,d2,d3}, {%177,%178}, {yb}, {fz,fz,fz,fz};\n"
        "cvt.rn.bf16x2.f32 a0, d2, d0;\n"
        "cvt.rn.bf16x2.f32 a1, d3, d1;\n"
        "mov.b32 {lo,hi}, r2;\n"
        "mov.b32 rl, {lo,lo};\n"
        "mov.b32 rh, {hi,hi};\n"
        "mul.bf16x2 x8, x8, rl;\n"
        "mul.bf16x2 x9, x9, rl;\n"
        "mul.bf16x2 x10, x10, rh;\n"
        "mul.bf16x2 x11, x11, rh;\n"
        "mma.sync.aligned.m16n8k16.row.col.f32.bf16.bf16.f32 {%80,%81,%82,%83}, {b0,b1,b2,b3}, {x8,x9}, {%80,%81,%82,%83};\n"
        "mma.sync.aligned.m16n8k16.row.col.f32.bf16.bf16.f32 {%84,%85,%86,%87}, {b0,b1,b2,b3}, {x10,x11}, {%84,%85,%86,%87};\n"
        "ld.shared.v4.u32 {x8,x9,x10,x11}, [xa+256];\n"
        "tanh.approx.f32 t0, p8;\n"
        "tanh.approx.f32 t1, p10;\n"
        "fma.rn.f32 t0, p8, t0, p8;\n"
        "fma.rn.f32 t1, p10, t1, p10;\n"
        "cvt.rn.bf16x2.f32 r2, t1, t0;\n"
        "mma.sync.aligned.m16n8k8.row.col.f32.bf16.bf16.f32 {d0,d1,d2,d3}, {%179,%180}, {yb}, {fz,fz,fz,fz};\n"
        "cvt.rn.bf16x2.f32 a2, d2, d0;\n"
        "cvt.rn.bf16x2.f32 a3, d3, d1;\n"
        "mov.b32 {lo,hi}, r3;\n"
        "mov.b32 rl, {lo,lo};\n"
        "mov.b32 rh, {hi,hi};\n"
        "mul.bf16x2 x12, x12, rl;\n"
        "mul.bf16x2 x13, x13, rl;\n"
        "mul.bf16x2 x14, x14, rh;\n"
        "mul.bf16x2 x15, x15, rh;\n"
        "mma.sync.aligned.m16n8k16.row.col.f32.bf16.bf16.f32 {%88,%89,%90,%91}, {b0,b1,b2,b3}, {x12,x13}, {%88,%89,%90,%91};\n"
        "mma.sync.aligned.m16n8k16.row.col.f32.bf16.bf16.f32 {%92,%93,%94,%95}, {b0,b1,b2,b3}, {x14,x15}, {%92,%93,%94,%95};\n"
        "ld.shared.v4.u32 {x12,x13,x14,x15}, [xa+384];\n"
        "tanh.approx.f32 t0, p12;\n"
        "tanh.approx.f32 t1, p14;\n"
        "fma.rn.f32 t0, p12, t0, p12;\n"
        "fma.rn.f32 t1, p14, t1, p14;\n"
        "cvt.rn.bf16x2.f32 r3, t1, t0;\n"
        "mov.b32 {lo,hi}, r0;\n"
        "mov.b32 rl, {lo,lo};\n"
        "mov.b32 rh, {hi,hi};\n"
        "mul.bf16x2 x0, x0, rl;\n"
        "mul.bf16x2 x1, x1, rl;\n"
        "mul.bf16x2 x2, x2, rh;\n"
        "mul.bf16x2 x3, x3, rh;\n"
        "mov.b32 {lo,hi}, r1;\n"
        "mov.b32 rl, {lo,lo};\n"
        "mov.b32 rh, {hi,hi};\n"
        "mul.bf16x2 x4, x4, rl;\n"
        "mul.bf16x2 x5, x5, rl;\n"
        "mul.bf16x2 x6, x6, rh;\n"
        "mul.bf16x2 x7, x7, rh;\n"
        "brx.idx.uni la, TA_%=;\n"
        "B3_%=:\n"
        "and.b32 la, ln, 255;\n"
        "shr.u32 lb, ln, 8;\n"
        "add.u32 ma, sa, %182;\n"
        "ldmatrix.sync.aligned.m8n8.x1.shared.b16 {yb}, [ma];\n"
        "add.u32 xa, sa, %181;\n"
        "mma.sync.aligned.m16n8k16.row.col.f32.bf16.bf16.f32 {%96,%97,%98,%99}, {b0,b1,b2,b3}, {x0,x1}, {%96,%97,%98,%99};\n"
        "mma.sync.aligned.m16n8k16.row.col.f32.bf16.bf16.f32 {%100,%101,%102,%103}, {b0,b1,b2,b3}, {x2,x3}, {%100,%101,%102,%103};\n"
        "ld.shared.v4.u32 {x0,x1,x2,x3}, [xa+0];\n"
        "tanh.approx.f32 t0, p0;\n"
        "tanh.approx.f32 t1, p2;\n"
        "fma.rn.f32 t0, p0, t0, p0;\n"
        "fma.rn.f32 t1, p2, t1, p2;\n"
        "cvt.rn.bf16x2.f32 r0, t1, t0;\n"
        "mma.sync.aligned.m16n8k16.row.col.f32.bf16.bf16.f32 {%104,%105,%106,%107}, {b0,b1,b2,b3}, {x4,x5}, {%104,%105,%106,%107};\n"
        "mma.sync.aligned.m16n8k16.row.col.f32.bf16.bf16.f32 {%108,%109,%110,%111}, {b0,b1,b2,b3}, {x6,x7}, {%108,%109,%110,%111};\n"
        "ld.shared.v4.u32 {x4,x5,x6,x7}, [xa+128];\n"
        "tanh.approx.f32 t0, p4;\n"
        "tanh.approx.f32 t1, p6;\n"
        "fma.rn.f32 t0, p4, t0, p4;\n"
        "fma.rn.f32 t1, p6, t1, p6;\n"
        "cvt.rn.bf16x2.f32 r1, t1, t0;\n"
        "mma.sync.aligned.m16n8k8.row.col.f32.bf16.bf16.f32 {d0,d1,d2,d3}, {%177,%178}, {yb}, {fz,fz,fz,fz};\n"
        "cvt.rn.bf16x2.f32 a0, d2, d0;\n"
        "cvt.rn.bf16x2.f32 a1, d3, d1;\n"
        "mov.b32 {lo,hi}, r2;\n"
        "mov.b32 rl, {lo,lo};\n"
        "mov.b32 rh, {hi,hi};\n"
        "mul.bf16x2 x8, x8, rl;\n"
        "mul.bf16x2 x9, x9, rl;\n"
        "mul.bf16x2 x10, x10, rh;\n"
        "mul.bf16x2 x11, x11, rh;\n"
        "mma.sync.aligned.m16n8k16.row.col.f32.bf16.bf16.f32 {%112,%113,%114,%115}, {b0,b1,b2,b3}, {x8,x9}, {%112,%113,%114,%115};\n"
        "mma.sync.aligned.m16n8k16.row.col.f32.bf16.bf16.f32 {%116,%117,%118,%119}, {b0,b1,b2,b3}, {x10,x11}, {%116,%117,%118,%119};\n"
        "ld.shared.v4.u32 {x8,x9,x10,x11}, [xa+256];\n"
        "tanh.approx.f32 t0, p8;\n"
        "tanh.approx.f32 t1, p10;\n"
        "fma.rn.f32 t0, p8, t0, p8;\n"
        "fma.rn.f32 t1, p10, t1, p10;\n"
        "cvt.rn.bf16x2.f32 r2, t1, t0;\n"
        "mma.sync.aligned.m16n8k8.row.col.f32.bf16.bf16.f32 {d0,d1,d2,d3}, {%179,%180}, {yb}, {fz,fz,fz,fz};\n"
        "cvt.rn.bf16x2.f32 a2, d2, d0;\n"
        "cvt.rn.bf16x2.f32 a3, d3, d1;\n"
        "mov.b32 {lo,hi}, r3;\n"
        "mov.b32 rl, {lo,lo};\n"
        "mov.b32 rh, {hi,hi};\n"
        "mul.bf16x2 x12, x12, rl;\n"
        "mul.bf16x2 x13, x13, rl;\n"
        "mul.bf16x2 x14, x14, rh;\n"
        "mul.bf16x2 x15, x15, rh;\n"
        "mma.sync.aligned.m16n8k16.row.col.f32.bf16.bf16.f32 {%120,%121,%122,%123}, {b0,b1,b2,b3}, {x12,x13}, {%120,%121,%122,%123};\n"
        "mma.sync.aligned.m16n8k16.row.col.f32.bf16.bf16.f32 {%124,%125,%126,%127}, {b0,b1,b2,b3}, {x14,x15}, {%124,%125,%126,%127};\n"
        "ld.shared.v4.u32 {x12,x13,x14,x15}, [xa+384];\n"
        "tanh.approx.f32 t0, p12;\n"
        "tanh.approx.f32 t1, p14;\n"
        "fma.rn.f32 t0, p12, t0, p12;\n"
        "fma.rn.f32 t1, p14, t1, p14;\n"
        "cvt.rn.bf16x2.f32 r3, t1, t0;\n"
        "mov.b32 {lo,hi}, r0;\n"
        "mov.b32 rl, {lo,lo};\n"
        "mov.b32 rh, {hi,hi};\n"
        "mul.bf16x2 x0, x0, rl;\n"
        "mul.bf16x2 x1, x1, rl;\n"
        "mul.bf16x2 x2, x2, rh;\n"
        "mul.bf16x2 x3, x3, rh;\n"
        "mov.b32 {lo,hi}, r1;\n"
        "mov.b32 rl, {lo,lo};\n"
        "mov.b32 rh, {hi,hi};\n"
        "mul.bf16x2 x4, x4, rl;\n"
        "mul.bf16x2 x5, x5, rl;\n"
        "mul.bf16x2 x6, x6, rh;\n"
        "mul.bf16x2 x7, x7, rh;\n"
        "brx.idx.uni la, TA_%=;\n"
        "B4_%=:\n"
        "and.b32 la, ln, 255;\n"
        "shr.u32 lb, ln, 8;\n"
        "add.u32 ma, sa, %182;\n"
        "ldmatrix.sync.aligned.m8n8.x1.shared.b16 {yb}, [ma];\n"
        "add.u32 xa, sa, %181;\n"
        "mma.sync.aligned.m16n8k16.row.col.f32.bf16.bf16.f32 {%128,%129,%130,%131}, {b0,b1,b2,b3}, {x0,x1}, {%128,%129,%130,%131};\n"
        "mma.sync.aligned.m16n8k16.row.col.f32.bf16.bf16.f32 {%132,%133,%134,%135}, {b0,b1,b2,b3}, {x2,x3}, {%132,%133,%134,%135};\n"
        "ld.shared.v4.u32 {x0,x1,x2,x3}, [xa+0];\n"
        "tanh.approx.f32 t0, p0;\n"
        "tanh.approx.f32 t1, p2;\n"
        "fma.rn.f32 t0, p0, t0, p0;\n"
        "fma.rn.f32 t1, p2, t1, p2;\n"
        "cvt.rn.bf16x2.f32 r0, t1, t0;\n"
        "mma.sync.aligned.m16n8k16.row.col.f32.bf16.bf16.f32 {%136,%137,%138,%139}, {b0,b1,b2,b3}, {x4,x5}, {%136,%137,%138,%139};\n"
        "mma.sync.aligned.m16n8k16.row.col.f32.bf16.bf16.f32 {%140,%141,%142,%143}, {b0,b1,b2,b3}, {x6,x7}, {%140,%141,%142,%143};\n"
        "ld.shared.v4.u32 {x4,x5,x6,x7}, [xa+128];\n"
        "tanh.approx.f32 t0, p4;\n"
        "tanh.approx.f32 t1, p6;\n"
        "fma.rn.f32 t0, p4, t0, p4;\n"
        "fma.rn.f32 t1, p6, t1, p6;\n"
        "cvt.rn.bf16x2.f32 r1, t1, t0;\n"
        "mma.sync.aligned.m16n8k8.row.col.f32.bf16.bf16.f32 {d0,d1,d2,d3}, {%177,%178}, {yb}, {fz,fz,fz,fz};\n"
        "cvt.rn.bf16x2.f32 a0, d2, d0;\n"
        "cvt.rn.bf16x2.f32 a1, d3, d1;\n"
        "mov.b32 {lo,hi}, r2;\n"
        "mov.b32 rl, {lo,lo};\n"
        "mov.b32 rh, {hi,hi};\n"
        "mul.bf16x2 x8, x8, rl;\n"
        "mul.bf16x2 x9, x9, rl;\n"
        "mul.bf16x2 x10, x10, rh;\n"
        "mul.bf16x2 x11, x11, rh;\n"
        "mma.sync.aligned.m16n8k16.row.col.f32.bf16.bf16.f32 {%144,%145,%146,%147}, {b0,b1,b2,b3}, {x8,x9}, {%144,%145,%146,%147};\n"
        "mma.sync.aligned.m16n8k16.row.col.f32.bf16.bf16.f32 {%148,%149,%150,%151}, {b0,b1,b2,b3}, {x10,x11}, {%148,%149,%150,%151};\n"
        "ld.shared.v4.u32 {x8,x9,x10,x11}, [xa+256];\n"
        "tanh.approx.f32 t0, p8;\n"
        "tanh.approx.f32 t1, p10;\n"
        "fma.rn.f32 t0, p8, t0, p8;\n"
        "fma.rn.f32 t1, p10, t1, p10;\n"
        "cvt.rn.bf16x2.f32 r2, t1, t0;\n"
        "mma.sync.aligned.m16n8k8.row.col.f32.bf16.bf16.f32 {d0,d1,d2,d3}, {%179,%180}, {yb}, {fz,fz,fz,fz};\n"
        "cvt.rn.bf16x2.f32 a2, d2, d0;\n"
        "cvt.rn.bf16x2.f32 a3, d3, d1;\n"
        "mov.b32 {lo,hi}, r3;\n"
        "mov.b32 rl, {lo,lo};\n"
        "mov.b32 rh, {hi,hi};\n"
        "mul.bf16x2 x12, x12, rl;\n"
        "mul.bf16x2 x13, x13, rl;\n"
        "mul.bf16x2 x14, x14, rh;\n"
        "mul.bf16x2 x15, x15, rh;\n"
        "mma.sync.aligned.m16n8k16.row.col.f32.bf16.bf16.f32 {%152,%153,%154,%155}, {b0,b1,b2,b3}, {x12,x13}, {%152,%153,%154,%155};\n"
        "mma.sync.aligned.m16n8k16.row.col.f32.bf16.bf16.f32 {%156,%157,%158,%159}, {b0,b1,b2,b3}, {x14,x15}, {%156,%157,%158,%159};\n"
        "ld.shared.v4.u32 {x12,x13,x14,x15}, [xa+384];\n"
        "tanh.approx.f32 t0, p12;\n"
        "tanh.approx.f32 t1, p14;\n"
        "fma.rn.f32 t0, p12, t0, p12;\n"
        "fma.rn.f32 t1, p14, t1, p14;\n"
        "cvt.rn.bf16x2.f32 r3, t1, t0;\n"
        "mov.b32 {lo,hi}, r0;\n"
        "mov.b32 rl, {lo,lo};\n"
        "mov.b32 rh, {hi,hi};\n"
        "mul.bf16x2 x0, x0, rl;\n"
        "mul.bf16x2 x1, x1, rl;\n"
        "mul.bf16x2 x2, x2, rh;\n"
        "mul.bf16x2 x3, x3, rh;\n"
        "mov.b32 {lo,hi}, r1;\n"
        "mov.b32 rl, {lo,lo};\n"
        "mov.b32 rh, {hi,hi};\n"
        "mul.bf16x2 x4, x4, rl;\n"
        "mul.bf16x2 x5, x5, rl;\n"
        "mul.bf16x2 x6, x6, rh;\n"
        "mul.bf16x2 x7, x7, rh;\n"
        "brx.idx.uni la, TA_%=;\n"
        "EXIT_%=:\n"
        "mov.u32 %160, ring;\n"
        "}\n"
        : "+f"(acc[0][0][0][0]), "+f"(acc[0][0][0][1]), "+f"(acc[0][0][0][2]), "+f"(acc[0][0][0][3]), "+f"(acc[0][0][1][0]),
          "+f"(acc[0][0][1][1]), "+f"(acc[0][0][1][2]), "+f"(acc[0][0][1][3]), "+f"(acc[0][1][0][0]), "+f"(acc[0][1][0][1]),
          "+f"(acc[0][1][0][2]), "+f"(acc[0][1][0][3]), "+f"(acc[0][1][1][0]), "+f"(acc[0][1][1][1]), "+f"(acc[0][1][1][2]),
          "+f"(acc[0][1][1][3]), "+f"(acc[0][2][0][0]), "+f"(acc[0][2][0][1]), "+f"(acc[0][2][0][2]), "+f"(acc[0][2][0][3]),
          "+f"(acc[0][2][1][0]), "+f"(acc[0][2][1][1]), "+f"(acc[0][2][1][2]), "+f"(acc[0][2][1][3]), "+f"(acc[0][3][0][0]),
          "+f"(acc[0][3][0][1]), "+f"(acc[0][3][0][2]), "+f"(acc[0][3][0][3]), "+f"(acc[0][3][1][0]), "+f"(acc[0][3][1][1]),
          "+f"(acc[0][3][1][2]), "+f"(acc[0][3][1][3]), "+f"(acc[1][0][0][0]), "+f"(acc[1][0][0][1]), "+f"(acc[1][0][0][2]),
          "+f"(acc[1][0][0][3]), "+f"(acc[1][0][1][0]), "+f"(acc[1][0][1][1]), "+f"(acc[1][0][1][2]), "+f"(acc[1][0][1][3]),
          "+f"(acc[1][1][0][0]), "+f"(acc[1][1][0][1]), "+f"(acc[1][1][0][2]), "+f"(acc[1][1][0][3]), "+f"(acc[1][1][1][0]),
          "+f"(acc[1][1][1][1]), "+f"(acc[1][1][1][2]), "+f"(acc[1][1][1][3]), "+f"(acc[1][2][0][0]), "+f"(acc[1][2][0][1]),
          "+f"(acc[1][2][0][2]), "+f"(acc[1][2][0][3]), "+f"(acc[1][2][1][0]), "+f"(acc[1][2][1][1]), "+f"(acc[1][2][1][2]),
          "+f"(acc[1][2][1][3]), "+f"(acc[1][3][0][0]), "+f"(acc[1][3][0][1]), "+f"(acc[1][3][0][2]), "+f"(acc[1][3][0][3]),
          "+f"(acc[1][3][1][0]), "+f"(acc[1][3][1][1]), "+f"(acc[1][3][1][2]), "+f"(acc[1][3][1][3]), "+f"(acc[2][0][0][0]),
          "+f"(acc[2][0][0][1]), "+f"(acc[2][0][0][2]), "+f"(acc[2][0][0][3]), "+f"(acc[2][0][1][0]), "+f"(acc[2][0][1][1]),
          "+f"(acc[2][0][1][2]), "+f"(acc[2][0][1][3]), "+f"(acc[2][1][0][0]), "+f"(acc[2][1][0][1]), "+f"(acc[2][1][0][2]),
          "+f"(acc[2][1][0][3]), "+f"(acc[2][1][1][0]), "+f"(acc[2][1][1][1]), "+f"(acc[2][1][1][2]), "+f"(acc[2][1][1][3]),
          "+f"(acc[2][2][0][0]), "+f"(acc[2][2][0][1]), "+f"(acc[2][2][0][2]), "+f"(acc[2][2][0][3]), "+f"(acc[2][2][1][0]),
          "+f"(acc[2][2][1][1]), "+f"(acc[2][2][1][2]), "+f"(acc[2][2][1][3]), "+f"(acc[2][3][0][0]), "+f"(acc[2][3][0][1]),
          "+f"(acc[2][3][0][2]), "+f"(acc[2][3][0][3]), "+f"(acc[2][3][1][0]), "+f"(acc[2][3][1][1]), "+f"(acc[2][3][1][2]),
          "+f"(acc[2][3][1][3]), "+f"(acc[3][0][0][0]), "+f"(acc[3][0][0][1]), "+f"(acc[3][0][0][2]), "+f"(acc[3][0][0][3]),
          "+f"(acc[3][0][1][0]), "+f"(acc[3][0][1][1]), "+f"(acc[3][0][1][2]), "+f"(acc[3][0][1][3]), "+f"(acc[3][1][0][0]),
          "+f"(acc[3][1][0][1]), "+f"(acc[3][1][0][2]), "+f"(acc[3][1][0][3]), "+f"(acc[3][1][1][0]), "+f"(acc[3][1][1][1]),
          "+f"(acc[3][1][1][2]), "+f"(acc[3][1][1][3]), "+f"(acc[3][2][0][0]), "+f"(acc[3][2][0][1]), "+f"(acc[3][2][0][2]),
          "+f"(acc[3][2][0][3]), "+f"(acc[3][2][1][0]), "+f"(acc[3][2][1][1]), "+f"(acc[3][2][1][2]), "+f"(acc[3][2][1][3]),
          "+f"(acc[3][3][0][0]), "+f"(acc[3][3][0][1]), "+f"(acc[3][3][0][2]), "+f"(acc[3][3][0][3]), "+f"(acc[3][3][1][0]),
          "+f"(acc[3][3][1][1]), "+f"(acc[3][3][1][2]), "+f"(acc[3][3][1][3]), "+f"(acc[4][0][0][0]), "+f"(acc[4][0][0][1]),
          "+f"(acc[4][0][0][2]), "+f"(acc[4][0][0][3]), "+f"(acc[4][0][1][0]), "+f"(acc[4][0][1][1]), "+f"(acc[4][0][1][2]),
          "+f"(acc[4][0][1][3]), "+f"(acc[4][1][0][0]), "+f"(acc[4][1][0][1]), "+f"(acc[4][1][0][2]), "+f"(acc[4][1][0][3]),
          "+f"(acc[4][1][1][0]), "+f"(acc[4][1][1][1]), "+f"(acc[4][1][1][2]), "+f"(acc[4][1][1][3]), "+f"(acc[4][2][0][0]),
          "+f"(acc[4][2][0][1]), "+f"(acc[4][2][0][2]), "+f"(acc[4][2][0][3]), "+f"(acc[4][2][1][0]), "+f"(acc[4][2][1][1]),
          "+f"(acc[4][2][1][2]), "+f"(acc[4][2][1][3]), "+f"(acc[4][3][0][0]), "+f"(acc[4][3][0][1]), "+f"(acc[4][3][0][2]),
          "+f"(acc[4][3][0][3]), "+f"(acc[4][3][1][0]), "+f"(acc[4][3][1][1]), "+f"(acc[4][3][1][2]), "+f"(acc[4][3][1][3]),
          "+r"(ring)
        : "r"(wf[0][0]), "r"(wf[0][1]), "r"(wf[0][2]), "r"(wf[0][3]), "r"(wf[1][0]), "r"(wf[1][1]), "r"(wf[1][2]), "r"(wf[1][3]),
          "r"(wf[2][0]), "r"(wf[2][1]), "r"(wf[2][2]), "r"(wf[2][3]), "r"(wf[3][0]), "r"(wf[3][1]), "r"(wf[3][2]), "r"(wf[3][3]),
          "r"(cgf[0]), "r"(cgf[1]), "r"(cgf[2]), "r"(cgf[3]), "r"(xoff), "r"(moff)
        : "memory");
}

#define PF_A 0x00000
#define PF_B 0x00000
#define PF_C 0x00000
__device__ __forceinline__ void l2_warm(uint32_t mask, int blk, int lane, const void* x, const void* Y, const void* ef) {
    if ((mask >> lane) & 1) {
        constexpr int EFP = (N_EDGES * 32 / (NB * 8) / 16 + 1) * 16, YP = (N_EDGES * 8 / (NB * 2) / 16 + 1) * 16;
        const char* base = lane < 8 ? (const char*)ef : lane < 10 ? (const char*)Y : (const char*)x;
        int o = lane < 8 ? (blk * 8 + lane) * EFP : lane < 10 ? (blk * 2 + lane - 8) * YP : ((lane - 10) * NB + blk) * 8192;
        int n = lane < 8 ? min(EFP, N_EDGES * 32 - o) : lane < 10 ? min(YP, N_EDGES * 8 - o) : min(8192, N_NODES * 1024 - o);
        if (n > 0) asm volatile("cp.async.bulk.prefetch.L2.global [%0], %1;" ::"l"(base + o), "r"(n));
    }
}

__device__ __noinline__ void generic_path(float* sagg, const __nv_bfloat16* x, const int* src, const int* dst,
                                          const __nv_bfloat16* Y, const __nv_bfloat16* ef, const __nv_bfloat16* w_rad,
                                          const __nv_bfloat16* cg, int x0, int x1) {
    const int tid = threadIdx.x, lane = tid & 31, blk = blockIdx.x;
    for (int k = 0; k < 2; k++)
        for (int r = 0; r < min(k == 0 ? x0 : x1, 32); r++) {
            uint32_t* p2 = g_mail2 + (blk * NSRC + ((tid + k * NTHR) >> 3)) * 32 + r;
            uint32_t v;
            int it = 0;
            do {
                asm volatile("ld.relaxed.gpu.global.u32 %0, [%1];" : "=r"(v) : "l"(p2) : "memory");
                if (++it > (1 << 20)) __trap();
            } while (v == 0);
            *p2 = 0;
        }
    __syncthreads();
    for (int i = tid; i < NPB * 512; i += NTHR) sagg[i] = 0.f;
    __syncthreads();
    for (int e0 = tid & ~31; e0 < N_EDGES; e0 += NTHR) {
        uint32_t bm = __ballot_sync(~0u, dst[e0 + lane] / NPB == blk);
        while (bm) {
            const int e = e0 + __ffs(bm) - 1, s = src[e], loc = dst[e] - blk * NPB;
            bm &= bm - 1;
            float a[4][4];
            for (int i = 0; i < 4; i++)
                for (int o = 0; o < 4; o++) {
                    a[i][o] = 0.f;
                    for (int f = 0; f < 4; f++)
                        a[i][o] += __bfloat162float(Y[e * 4 + f]) * __bfloat162float(cg[i * 16 + f * 4 + o]);
                }
#pragma unroll 1
            for (int c = lane; c < 128; c += 32) {
                float pre = 0.f;
                for (int k = 0; k < 16; k++)
                    pre += __bfloat162float(ef[e * 16 + k]) * __bfloat162float(w_rad[k * 128 + c]);
                const float R = pre / (1.f + __expf(-pre));
                for (int o = 0; o < 4; o++) {
                    float acc = 0.f;
                    for (int i = 0; i < 4; i++) acc += __bfloat162float(x[(size_t)s * 512 + c * 4 + i]) * a[i][o];
                    atomicAdd(&sagg[loc * 512 + c * 4 + o], R * acc);
                }
            }
        }
    }
    __syncthreads();
}

__device__ __forceinline__ void init_barriers() {
    extern __shared__ __align__(1024) uint8_t smem[];
    const uint32_t sb = smem_u32(smem);
#pragma unroll
    for (int i = 0; i < 4 * NG; i++) {
        mbar_init(sb + i * STAGE + 4 * ROWP, 33);
        mbar_init(sb + i * STAGE + 4 * ROWP + 8, 2);
    }
}

template <int PHASES>
__global__ void __launch_bounds__(NTHR, 1)
tfn_kernel(const __nv_bfloat16* __restrict__ x, const int* __restrict__ src, const int* __restrict__ dst,
           const __nv_bfloat16* __restrict__ Y, const __nv_bfloat16* __restrict__ ef,
           const __nv_bfloat16* __restrict__ w_rad, const __nv_bfloat16* __restrict__ cg,
           const __nv_bfloat16* __restrict__ w_mix, __nv_bfloat16* __restrict__ out) {
    extern __shared__ __align__(1024) uint8_t smem[];
    const int tid = threadIdx.x, lane = tid & 31;
    const int warp = __shfl_sync(~0u, tid >> 5, 0);
    const int blk = blockIdx.x;
    uint32_t sb = smem_u32(smem);
    asm volatile("" : "+r"(sb));
    int* mi = reinterpret_cast<int*>(smem + SM_MISC);

    const int g = lane >> 2, t = lane & 3;
    const uint32_t dump = sb + SC_DUMP + lane * 4;
    int4 d1[2], s1[2];
    constexpr int nq = EPC / 4;
    const bool binner = (PHASES & 1) && blk < NSRC;
    if (binner) {
#pragma unroll
        for (int k = 0; k < 2; k++) {
            const int q = tid + k * NTHR;
            if (q < nq) {
                d1[k] = __ldg(reinterpret_cast<const int4*>(dst + blk * EPC) + q);
                s1[k] = __ldg(reinterpret_cast<const int4*>(src + blk * EPC) + q);
            }
        }
    }
    if (binner) {
#pragma unroll
        for (int k = 0; k < 3; k++)
            if (k < 2 || warp < 1) sts128(sb + SC_MAIL + (tid + k * NTHR) * 16, ~0u, ~0u, ~0u, ~0u);
        if (tid <= NB / 4) sts128(sb + SC_CNT + tid * 16, 0, 0, 0, 0);
    }
    if (PHASES & 2) {
        if (tid == 160) sts128(sb + SM_MISC, 0, 0, 0, 0);
        constexpr int lead = LEAD_CLK >> 2;
        if (tid == 161) mi[MI_SHIFT] = 0;
        if (tid == 162 && !(blk & 3) && blk < 128) g_lag[blk >> 2] = lead;
        if (tid < 20 * HS / 4) sts128(sb + SC_HIST + tid * 16, 0, 0, 0, 0);
        const uint32_t pad = (uint32_t)(lane * 0x10008 + 7);
#pragma unroll
        for (int k = 0; k < 3; k++)
            if (tid + k * NTHR < 4 * UCAP * REC / 16) sts128(sb + SM_REC + (tid + k * NTHR) * 16, pad, pad, pad, pad);
    }
    __syncthreads();
    if (PHASES & 2) {
#pragma unroll
        for (int k = 0; k < 4; k++) {
            const int i = tid + k * NTHR, c = i >> 4;
            cp16(sb + SM_W + c * 256 + (((i & 15) ^ ((c & 2) | (((c >> 4) & 1) << 2))) << 4), w_mix + i * 8);
        }
        if (warp >= 8) cp16(sb + SC_WR + ((tid - 256) ^ ((tid >> 4) & 6)) * 16, w_rad + (tid - 256) * 8);
        if (tid < 8) cp16(sb + SC_WR + 4096 + tid * 16, cg + tid * 8);
        if (PF_A && warp == 11) l2_warm(PF_A, blk, lane, x, Y, ef);
    }
    if (binner) {
#pragma unroll
        for (int k = 0; k < 2; k++) {
            if (tid + k * NTHR < nq) {
                const uint32_t dd[4] = {(uint32_t)d1[k].x, (uint32_t)d1[k].y, (uint32_t)d1[k].z, (uint32_t)d1[k].w};
                const uint32_t ss[4] = {(uint32_t)s1[k].x, (uint32_t)s1[k].y, (uint32_t)s1[k].z, (uint32_t)s1[k].w};
                uint32_t own[4], rk[4], v[4];
#pragma unroll
                for (int j = 0; j < 4; j++) { own[j] = dd[j] / NPB; rk[j] = atoms_inc(sb + SC_CNT + own[j] * 4); }
#pragma unroll
                for (int j = 0; j < 4; j++) {
                    const uint32_t loc = dd[j] - own[j] * NPB, code = loc + ((loc * 216) >> 12);
                    v[j] = (ss[j] << 18) + code * 2560 + (tid + k * NTHR) * 4 + j + 1;
                    sts32(sb + SC_MAIL + own[j] * 128 + ((min(rk[j], 31u) * 4) ^ ((own[j] & 7) << 4)), v[j]);
                }
                if (max(max(rk[0], rk[1]), max(rk[2], rk[3])) >= 31) {
#pragma unroll
                    for (int j = 0; j < 4; j++)
                        if (rk[j] - 31 < 32)
                            asm volatile("st.relaxed.gpu.global.u32 [%0], %1;" ::"l"(g_mail2 + (own[j] * NSRC + blk) * 32 + rk[j] - 31), "r"(v[j]) : "memory");
                }
            }
        }
        __syncwarp();
        asm volatile("red.shared.max.u32 [%0], %1;" ::"r"(lane == 0 ? sb + SC_CNT + NB * 4 : dump), "r"(gtime()) : "memory");
        STAMP(1);
        __syncthreads();
        const uint32_t hdr = 0xc0000000u | ((lds32(sb + SC_CNT + NB * 4) << 7) & 0x3ffff000u);
        uint4 mv[3];
        uint32_t mc[3];
#pragma unroll
        for (int k = 0; k < 3; k++)
            if (k < 2 || warp < 1) {
                const int j = tid + k * NTHR, own = j >> 3;
                mv[k] = lds128(sb + SC_MAIL + own * 128 + (((j ^ own) & 7) << 4));
                mc[k] = lds32(sb + SC_CNT + own * 4);
            }
#pragma unroll
        for (int k = 0; k < 3; k++)
            if (k < 2 || warp < 1) {
                const int j = tid + k * NTHR;
                asm volatile("st.relaxed.gpu.global.v4.u32 [%0], {%1,%2,%3,%4};" ::"l"(g_mail + ((j >> 3) * NSRC + blk) * 8 + (j & 7)),
                             "r"(mv[k].x), "r"(mv[k].y), "r"(mv[k].z), "r"((j & 7) == 7 ? hdr | mc[k] : mv[k].w) : "memory");
            }
        STAMP(2);
    }
    if (!(PHASES & 2)) return;
    const uint32_t tpub = (uint32_t)clock() + (blk < NSRC ? 0 : 3000);

    uint32_t en[8], hr[8], rk[8], em[8];
    int xc[2];
    const uint32_t tref = __shfl_sync(~0u, gtime() >> 5, 0);
    {
        uint4* mp = g_mail + blk * NSRC * 8 + tid;
        int it = 0;
        bool ok;
        while ((int)((uint32_t)clock() - tpub) < POLL_DELAY) {}
        do {
#pragma unroll
            for (int k = 0; k < 2; k++)
                    asm volatile("ld.relaxed.gpu.global.v4.u32 {%0,%1,%2,%3}, [%4];"
                                 : "=r"(en[4 * k]), "=r"(en[4 * k + 1]), "=r"(en[4 * k + 2]), "=r"(en[4 * k + 3])
                                 : "l"(mp + k * NTHR) : "memory");
            uint32_t m = ~0u;
#pragma unroll
            for (int i = 0; i < 8; i++) m = min(m, en[i]);
            ok = __all_sync(~0u, m != 0);
            if (++it > (1 << 20)) __trap();
        } while (!ok);
        STAMP(3);
#pragma unroll
        for (int i = 0; i < 8; i++) {
            const uint32_t w = en[i] & 0x3ffff, code = ((w >> 9) * 13108) >> 16;
            hr[i] = en[i] < 0xc0000000u ? sb + SC_HIST + ((code >> 2) * HS + (en[i] >> 25)) * 4 : dump;
            rk[i] = atoms_inc(hr[i]);
            em[i] = ((((tid + (i >> 2) * NTHR) >> 3) * EPC + w - code * 2560 - 1) * 8) | (code & 3);
        }
        int dt = -(1 << 20);
#pragma unroll
        for (int k = 0; k < 2; k++) {
            const bool hd = (lane & 7) == 7;
            dt = max(dt, hd ? (int)(((en[4 * k + 3] >> 12) - tref) << 14) >> 14 : -(1 << 20));
            xc[k] = hd ? max((int)(en[4 * k + 3] & 0xfff) - 31, 0) : 0;
        }
        dt = __reduce_max_sync(~0u, dt);
        asm volatile("red.shared.max.u32 [%0], %1;" ::"r"(lane == 0 ? sb + SM_MISC + MI_TMAX * 4 : dump + 128), "r"(tref + dt + (1u << 27)) : "memory");
        if (xc[0] | xc[1]) {
#pragma unroll
            for (int k = 0; k < 2; k++) {
                const int slot = atomicAdd(&mi[MI_XN], xc[k]);
                for (int r = 0; r < xc[k] && slot + r < 32; r++)
                    reinterpret_cast<uint32_t*>(smem + SC_XTRA)[slot + r] = ((tid + k * NTHR) >> 3) * 32 + r;
            }
        }
#pragma unroll
        for (int k = 0; k < 2; k++)
            mp[k * NTHR] = make_uint4(0, 0, 0, 0);
    }
    __syncthreads();
    STAMP(4);
    uint32_t* hist = reinterpret_cast<uint32_t*>(smem + SC_HIST);
    const int xn = mi[MI_XN];
    uint32_t xi = 0, xv = 1;
    if (warp < 10) {
        uint32_t* hp = hist + (warp * 2 + (lane >> 4)) * HS + (lane & 15) * 5;
        int c[5], s = 0;
#pragma unroll
        for (int j = 0; j < 5; j++) { c[j] = hp[j]; s += c[j]; }
        int inc = s;
#pragma unroll
        for (int o = 1; o < 16; o <<= 1) { int v = __shfl_up_sync(~0u, inc, o, 16); if ((lane & 15) >= o) inc += v; }
        int base = 0;
        if ((lane & 15) == 15) { base = atomicAdd(&mi[MI_ALLOC], (inc + 3) >> 2); hp[5] = (base + ((inc + 3) >> 2)) << 16; }
        const int tot = __shfl_sync(~0u, inc, 15, 16);
        base = __shfl_sync(~0u, base, 15, 16);
        int ex = inc - s;
#pragma unroll
        for (int j = 0; j < 5; j++) {
            hp[j] = (base * 4 + ex) | ((base + ((ex == tot ? ex + 3 : ex + 1) >> 2)) << 16);
            ex += c[j];
        }
    } else if (warp == 10) {
        if (PF_B) l2_warm(PF_B, blk, lane, x, Y, ef);
        if (lane < xn) {
            xi = reinterpret_cast<const uint32_t*>(smem + SC_XTRA)[lane];
            asm volatile("ld.relaxed.gpu.global.u32 %0, [%1];" : "=r"(xv) : "l"(g_mail2 + blk * NSRC * 32 + xi) : "memory");
        }
    } else if (tid == 12 * 32) {
        init_barriers();
    } else if (tid == 11 * 32) {
        sts32(sb + SC_GPOS + GDUMMY * 4, (uint32_t)(4 * UCAP * REC + 128) * 0x10001u);
        constexpr int start_ns = START_NS;
        mi[MI_T0] = (uint32_t)clock() + (((int)(((uint32_t)mi[MI_TMAX] << 5) + start_ns - gtime()) * 31) >> 4);
    }
    asm volatile("cp.async.wait_all;" ::: "memory");
    __syncthreads();
    STAMP(10);
    int myng = 0;
    if (lane < 4)
#pragma unroll
        for (int l = 0; l < 5; l++) myng += (hist[(lane * 5 + l) * HS + NBK] >> 16) - (hist[(lane * 5 + l) * HS] >> 16);
    const bool ovf = __any_sync(~0u, myng + xn > 2 * (UCAP - 4) || xn > 32);
    if (warp >= 12) {
        const uint32_t d = sb + (warp - 12) * NG * STAGE + lane * 16;
#pragma unroll
        for (int m = 0; m < 8; m++) {
            uint32_t w[4];
#pragma unroll
            for (int j = 0; j < 4; j++)
                w[j] = mul_lo(lds32(sb + SC_WR + (2 * t + (j & 1) + (j >> 1) * 8) * 256 + (((m * 8 + g) * 4) ^ (t << 5))), 0x3f003f00u);
            sts128(d + (m >> 2) * ROWP + (m & 3) * 512, __byte_perm(w[0], w[1], 0x5410), __byte_perm(w[0], w[1], 0x7632),
                   __byte_perm(w[2], w[3], 0x5410), __byte_perm(w[2], w[3], 0x7632));
        }
        uint32_t c[4];
#pragma unroll
        for (int i = 0; i < 4; i++) {
            const uint32_t ca = sb + SC_WR + 4096 + (i * 16 + (t & 1) * 8 + (g & 3)) * 2;
            c[i] = (lds16(ca) | (lds16(ca + 8) << 16)) & ((t >> 1) == (g >> 2) ? ~0u : 0u);
        }
        sts128(d + 2 * ROWP, c[0], c[1], c[2], c[3]);
    }
    if (!ovf) {
        constexpr int pace = PACE_Q8;
        if (warp < 10) {
            const int team = tid / NBK, b = tid - team * NBK;
            int lo[5], n[5], pos = team * UCAP * 2, nmax = 0, nsum = 0;
#pragma unroll
            for (int q = 0; q < 5; q++) {
                lo[q] = hist[(team * 5 + q) * HS + b] >> 16;
                n[q] = (hist[(team * 5 + q) * HS + b + 1] >> 16) - lo[q];
                pos += lo[q] - (hist[(team * 5 + q) * HS] >> 16);
                nmax = max(nmax, n[q]);
                nsum += n[q];
            }
            nmax = __reduce_max_sync(~0u, nmax);
            const int step = __float2int_rz(__fdividef((float)pace, (float)max(nsum, 1)));
            const int tb = (b * 128 - PACE_LEAD) * pace / 128 + step / 2 - pos * step;
            const uint32_t t0 = mi[MI_T0];
#pragma unroll 1
            for (int r = 0; r < nmax; r++) {
                int pq = pos + r;
#pragma unroll
                for (int q = 0; q < 5; q++) {
                    const bool on = r < n[q];
                    const uint32_t ro = (pq >> 1) * REC, par = pq & 1;
                    sts32(on ? sb + SC_GPOS + (lo[q] + r) * 4 : dump, ro * 0x10001u + par * 0x40002u + (REC | (16 << 16)));
                    sts8(on ? sb + SM_REC + 48 + ro + par : dump, q);
                    sts16(on && !par ? sb + SM_REC + REC + 50 + ro : dump, (t0 + max(tb + pq * step, 0)) >> 2);
                    pq += n[q];
                }
            }
        } else if (warp == 10) {
            for (int n = 0; __any_sync(~0u, xv == 0); n++) {
                if (xv == 0) asm volatile("ld.relaxed.gpu.global.u32 %0, [%1];" : "=r"(xv) : "l"(g_mail2 + blk * NSRC * 32 + xi) : "memory");
                if (n > (1 << 20)) __trap();
            }
            const uint32_t w = xv & 0x3ffff, code = ((w >> 9) * 13108) >> 16, xt = lane < xn ? code / 20 : 4;
            const uint32_t same = __match_any_sync(~0u, xt);
            const int pq = __shfl_sync(~0u, myng, xt & 3) + __popc(same & ((1u << lane) - 1));
#pragma unroll
            for (int q = 0; q < 4; q++) {
                const int c = __popc(__ballot_sync(~0u, xt == q));
                if (lane == q) myng += c;
            }
            if (lane < xn) {
                g_mail2[blk * NSRC * 32 + xi] = 0;
                const uint32_t a = sb + SM_REC + (xt * UCAP + (pq >> 1)) * REC;
                sts16(a + REC + (pq & 1) * 2, xv >> 18);
                sts32(a + 16 + (pq & 1) * 4, (((xi >> 5) * EPC + w - code * 2560 - 1) * 8) | (code & 3));
                sts8(a + 48 + (pq & 1), (code >> 2) - xt * 5);
                if (!(pq & 1)) sts16(a + REC + 50, ((uint32_t)mi[MI_T0] + (N_NODES - PACE_LEAD) * pace / 128) >> 2);
            }
            if (lane < 4) {
                const uint32_t a = sb + SM_REC + (lane * UCAP + (myng >> 1)) * REC + 48;
                if (myng & 1) sts8(a + 1, 0);
                sts16(a + (myng & 1) * REC, 5);
                mi[MI_NU + lane] = (myng + 1) >> 1;
            }
        }
#pragma unroll
        for (int i = 0; i < 8; i++) {
            const uint32_t p = en[i] < 0xc0000000u ? rk[i] + lds16(hr[i]) : GDUMMY * 4;
            hr[i] = sb + SC_GPOS + (p & ~3u);
            rk[i] = (p & 3) * 0x80004u;
        }
        __syncthreads();
        STAMP(11);
#pragma unroll
        for (int i = 0; i < 8; i++) rk[i] += lds32(hr[i]);
#pragma unroll
        for (int i = 0; i < 8; i++) {
            sts16(sb + SM_REC + (rk[i] & 0xffff), en[i] >> 18);
            sts32(sb + SM_REC + (rk[i] >> 16), em[i]);
        }
    } else {
        if (tid < 4) {
            sts16(sb + SM_REC + tid * UCAP * REC + 48, 5);
            mi[MI_NU + tid] = 0;
        }
        generic_path(reinterpret_cast<float*>(smem), x, src, dst, Y, ef, w_rad, cg, xc[0], xc[1]);
    }

    __syncwarp();
    if (warp >= 8) {
        asm volatile("bar.sync 3, 512;" ::: "memory");
        asm volatile("setmaxnreg.dec.sync.aligned.u32 24;");
        const int team = warp & 3;
        if (ovf) {
            asm volatile("bar.sync 2;" ::: "memory");
            if (tid == 256) init_barriers();
            asm volatile("bar.sync 2;" ::: "memory");
        }
        STAMP(5);
        const uint32_t ring = sb + SM_RING + team * NG * STAGE;
        constexpr int lead = LEAD_CLK >> 2;
        const uint32_t q = lane >> 3, c = lane & 7, rec = sb + SM_REC + team * UCAP * REC;
        __syncwarp();
        producer_loop(reinterpret_cast<const char*>(x) + c * 16, reinterpret_cast<const char*>(ef) + (c & 1) * 16, Y,
                      q * ROWP + ((c ^ (q << 1)) << 4), q * 4 + (c & 2) * 8, (c & 1) * 2 + (c >> 2), ring, rec,
                      rec + (mi[MI_NU + team] + 1) * REC, warp >= 12, lead, sb + SM_MISC + MI_SHIFT * 4);
    } else {
        const int team = warp >> 1, h = warp & 1;
        asm volatile("bar.arrive 3, 512;" ::: "memory");
        if (PF_C && warp == 0) l2_warm(PF_C, blk, lane, x, Y, ef);
        asm volatile("setmaxnreg.inc.sync.aligned.u32 232;");
        uint32_t ring = sb + SM_RING + team * NG * STAGE;
        uint32_t wf[4][4], cgf[4];
#pragma unroll
        for (int m = 0; m < 5; m++) {
            const uint4 v = lds128(ring + (m < 4 ? h * ROWP + m * 512 : 2 * ROWP) + lane * 16);
            uint32_t* f = m < 4 ? wf[m] : cgf;
            f[0] = v.x; f[1] = v.y; f[2] = v.z; f[3] = v.w;
        }
        float acc[5][4][2][4];
        if (!ovf) {
#pragma unroll
            for (int l = 0; l < 5; l++)
#pragma unroll
                for (int m = 0; m < 4; m++)
#pragma unroll
                    for (int p = 0; p < 2; p++)
#pragma unroll
                        for (int r = 0; r < 4; r++) acc[l][m][p][r] = 0.f;
        } else {
            const float* sagg = reinterpret_cast<const float*>(smem);
#pragma unroll
            for (int l = 0; l < 5; l++)
#pragma unroll
                for (int m = 0; m < 4; m++)
#pragma unroll
                    for (int p = 0; p < 2; p++)
#pragma unroll
                        for (int r = 0; r < 4; r++) {
                            int nd = l * 4 + (g >> 2) + (r >> 1) * 2;
                            int ch = h * 64 + m * 16 + 4 * t + (r & 1) * 2 + p;
                            acc[l][m][p][r] = nd < 19 ? sagg[(team * 19 + nd) * 512 + ch * 4 + (g & 3)] : 0.f;
                        }
            asm volatile("bar.sync 2;" ::: "memory");
            asm volatile("bar.sync 2;" ::: "memory");
        }
#pragma unroll
        for (int k = 0; k < 4; k++) {
            const int it = tid + k * 256, c = it >> 3, f = (c & 3) | (((c >> 4) & 1) << 2);
            const uint32_t a0 = sb + SM_W + c * 256 + (((2 * (it & 7)) ^ f) << 4), a1 = a0 ^ 16;
            const uint4 u = lds128(a0 & ~16u), v = lds128(a0 | 16u);
            sts128(a0, __byte_perm(u.x, u.y, 0x5410), __byte_perm(u.z, u.w, 0x5410), __byte_perm(v.x, v.y, 0x5410),
                   __byte_perm(v.z, v.w, 0x5410));
            sts128(a1, __byte_perm(u.x, u.y, 0x7632), __byte_perm(u.z, u.w, 0x7632), __byte_perm(v.x, v.y, 0x7632),
                   __byte_perm(v.z, v.w, 0x7632));
        }
        const uint32_t xoff = t * ROWP + h * 512 + ((g ^ (t << 1)) << 4);
        const uint32_t mat = lane >> 3, mhi = (lane >> 2) & 1;
        const bool isy = mat < 2;
        const uint32_t ml = isy ? (t & 2) + (mat & 1) : t;
        const uint32_t moff = ml * ROWP + 2048 + (((isy ? 4 + 2 * mhi + (t & 1) : 2 * mhi + mat - 2) ^ (ml << 1)) << 4);
        __syncwarp();
        consumer_loop(acc, wf, cgf, xoff, ring, moff);
        {
        int lane_;
        asm volatile("mov.u32 %0, %%laneid;" : "=r"(lane_));
        const int lane = lane_, g = lane >> 2, t = lane & 3;
        const uint32_t sb = ring - team * NG * STAGE;
        STAMP(7);
        asm volatile("bar.sync 1, 256;" ::: "memory");
        {
            const int rr = ((g & 3) >> 1) * 8 + (g >> 2) * 2 + (g & 1);
#pragma unroll
            for (int l = 0; l < 5; l++)
#pragma unroll
                for (int hi = 0; hi < 2; hi++) {
                    const int R = team * 80 + l * 16 + rr + hi * 4;
                    const uint32_t a = sb + h * 40960 + R * 128;
#pragma unroll
                    for (int c = 0; c < 2; c++) {
                        const int m = 2 * c;
                        sts128(a + (((2 * t + c) ^ (R & 7)) << 4),
                               pack_bf16(acc[l][m][0][2 * hi], acc[l][m][1][2 * hi]),
                               pack_bf16(acc[l][m][0][2 * hi + 1], acc[l][m][1][2 * hi + 1]),
                               pack_bf16(acc[l][m + 1][0][2 * hi], acc[l][m + 1][1][2 * hi]),
                               pack_bf16(acc[l][m + 1][0][2 * hi + 1], acc[l][m + 1][1][2 * hi + 1]));
                    }
                }
        }
        asm volatile("fence.proxy.async.shared::cta;" ::: "memory");
        uint32_t wa[8][4];
        {
            const int r = lane & 7, k = (lane >> 4) * 8 + r;
            const int chunk = (2 * warp + ((lane >> 3) & 1)) ^ r;
#pragma unroll
            for (int ks = 0; ks < 8; ks++) {
                const int c = (ks >> 2) * 64 + 16 * (k >> 2) + 4 * (ks & 3) + (k & 3);
                asm volatile("ldmatrix.sync.aligned.m8n8.x4.trans.shared.b16 {%0,%1,%2,%3}, [%4];"
                             : "=r"(wa[ks][0]), "=r"(wa[ks][1]), "=r"(wa[ks][2]), "=r"(wa[ks][3])
                             : "r"(sb + SM_W + c * 256 + (chunk << 4)));
            }
        }
        asm volatile("bar.sync 1, 256;" ::: "memory");
        STAMP(8);
        float o[4][40];
        asm volatile("wgmma.fence.sync.aligned;" ::: "memory");
#pragma unroll
        for (int tm = 0; tm < 4; tm++) {
#pragma unroll
            for (int ks = 0; ks < 8; ks++) {
                const uint32_t a = sb + (ks >> 2) * 40960 + tm * 80 * 128 + (ks & 3) * 32;
                const uint64_t desc = (uint64_t)((a & 0x3ffff) >> 4) | (1ull << 16) | (64ull << 32) | (1ull << 62);
                wgmma_n80(o[tm], wa[ks], desc, ks);
            }
            asm volatile("wgmma.commit_group.sync.aligned;" ::: "memory");
        }
#pragma unroll
        for (int tm = 0; tm < 4; tm++) {
            if (tm == 0) asm volatile("wgmma.wait_group.sync.aligned 3;" ::: "memory");
            if (tm == 1) asm volatile("wgmma.wait_group.sync.aligned 2;" ::: "memory");
            if (tm == 2) asm volatile("wgmma.wait_group.sync.aligned 1;" ::: "memory");
            if (tm == 3) asm volatile("wgmma.wait_group.sync.aligned 0;" ::: "memory");
#pragma unroll
            for (int i = 0; i < 40; i++) asm volatile("" : "+f"(o[tm][i])::"memory");
#pragma unroll
            for (int l = 0; l < 5; l++) {
                const int sl = (lane & 7) * 4 + (lane >> 3);
                uint4 v;
                v.x = __shfl_sync(~0u, pack_bf16(o[tm][8 * l + 0], o[tm][8 * l + 1]), sl);
                v.y = __shfl_sync(~0u, pack_bf16(o[tm][8 * l + 4], o[tm][8 * l + 5]), sl);
                v.z = __shfl_sync(~0u, pack_bf16(o[tm][8 * l + 2], o[tm][8 * l + 3]), sl);
                v.w = __shfl_sync(~0u, pack_bf16(o[tm][8 * l + 6], o[tm][8 * l + 7]), sl);
                const int nl = l * 4 + (lane >> 3), node = blk * NPB + tm * 19 + nl;
                if (nl < 19 && node < N_NODES)
                    *reinterpret_cast<uint4*>(out + (size_t)node * 512 + warp * 64 + (lane & 7) * 8) = v;
            }
        }
        STAMP(9);
        }
    }
}

}

extern "C" void kernel_launch(void* const* d_in, const int* in_sizes, int n_in, void* d_out, int out_size) {
    (void)in_sizes; (void)n_in; (void)out_size;
    const __nv_bfloat16* x = (const __nv_bfloat16*)d_in[0];
    const int* src = (const int*)d_in[1];
    const int* dst = (const int*)d_in[2];
    const __nv_bfloat16* Y = (const __nv_bfloat16*)d_in[3];
    const __nv_bfloat16* ef = (const __nv_bfloat16*)d_in[4];
    const __nv_bfloat16* w_rad = (const __nv_bfloat16*)d_in[5];
    const __nv_bfloat16* cg = (const __nv_bfloat16*)d_in[6];
    const __nv_bfloat16* w_mix = (const __nv_bfloat16*)d_in[7];
    __nv_bfloat16* out = (__nv_bfloat16*)d_out;

    static int sms = 0;
    if (sms == 0) {
        int dev = 0;
        cudaGetDevice(&dev);
        cudaDeviceGetAttribute(&sms, cudaDevAttrMultiProcessorCount, dev);
        cudaFuncSetAttribute(tfn_kernel<3>, cudaFuncAttributeMaxDynamicSharedMemorySize, SM_TOTAL);
        cudaFuncSetAttribute(tfn_kernel<1>, cudaFuncAttributeMaxDynamicSharedMemorySize, SM_TOTAL);
        cudaFuncSetAttribute(tfn_kernel<2>, cudaFuncAttributeMaxDynamicSharedMemorySize, SM_TOTAL);
    }
    if (sms >= NB) {
        tfn_kernel<3><<<NB, NTHR, SM_TOTAL>>>(x, src, dst, Y, ef, w_rad, cg, w_mix, out);
    } else {
        tfn_kernel<1><<<NB, NTHR, SM_TOTAL>>>(x, src, dst, Y, ef, w_rad, cg, w_mix, out);
        tfn_kernel<2><<<NB, NTHR, SM_TOTAL>>>(x, src, dst, Y, ef, w_rad, cg, w_mix, out);
    }
}
```

```cpp
#include <cuda_runtime.h>
#include <cuda_bf16.h>
#include <stdint.h>

namespace {

constexpr int N_NODES = 10000;
constexpr int N_EDGES = 320000;
constexpr int NB      = 132;
constexpr int NPB     = 76;
constexpr int NSRC    = 128;
constexpr int EPC     = N_EDGES / NSRC;
constexpr int NTHR    = 512;
#define NGS 5
constexpr int NG      = NGS;
constexpr int ROWP    = 2176;
constexpr int STAGE   = 4 * ROWP + 128;
constexpr int UCAP    = 104;
constexpr int REC     = 52;
constexpr int NBK     = 80;
constexpr int HS      = 81;

#define PACE_Q8 660
#define PACE_LEAD 300
#define PACE_HEAD 730
#define HEAD_BK 10
#define PACE_TAIL PACE_Q8
#define TAIL_BK 80
#define POLL_DELAY 1350
#define LEAD_CLK 700
#define START_NS 3200

constexpr int SM_RING  = 0;
constexpr int SM_W     = 4 * NG * STAGE;
constexpr int SM_REC   = SM_W + 32768;
constexpr int SM_MISC  = SM_REC + 4 * UCAP * REC;
constexpr int SM_TOTAL = SM_MISC + 192;
constexpr int SC_MAIL  = 1 * STAGE;
constexpr int SC_CNT   = 3 * STAGE;
constexpr int SC_DUMP  = 3 * STAGE + 1024;
constexpr int SC_XTRA  = 3 * STAGE + 2048;
constexpr int SC_HIST  = 4 * STAGE;
constexpr int SC_GPOS  = 6 * STAGE;
constexpr int SC_WR    = 7 * STAGE;
constexpr int GDUMMY   = 1024;
constexpr int AGGT     = (NG * STAGE + 1023) / 1024 * 1024;
static_assert(3 * AGGT + 20480 <= 4 * NG * STAGE, "agg tile inside the team's ring");
static_assert(NPB * 512 * 4 <= 4 * NG * STAGE, "slow tile");
static_assert(SM_TOTAL <= 232448, "smem");
static_assert(SM_REC % 16 == 0 && (4 * UCAP * REC) % 16 == 0 && SM_MISC % 16 == 0, "align");
constexpr int MI_XN = 0;
constexpr int MI_TMAX = 2;
constexpr int MI_SHIFT = 7;
constexpr int MI_NU = 8;
constexpr int MI_END = 28;
constexpr int MI_T0 = 3;

__device__ uint4 g_mail[NB * NSRC * 8];
__device__ uint32_t g_mail2[NB * NSRC * 32];
__device__ __align__(128) int g_lag[32];
#define STAMP(k)

__device__ __forceinline__ uint32_t smem_u32(const void* p) { return (uint32_t)__cvta_generic_to_shared(p); }
__device__ __forceinline__ uint32_t atoms_inc(uint32_t a) {
    uint32_t r;
    asm volatile("atom.shared.add.u32 %0, [%1], 1;" : "=r"(r) : "r"(a) : "memory");
    return r;
}
__device__ __forceinline__ void sts32(uint32_t a, uint32_t v) { asm volatile("st.shared.u32 [%0], %1;" ::"r"(a), "r"(v) : "memory"); }
__device__ __forceinline__ void sts16(uint32_t a, uint32_t v) { asm volatile("st.shared.u16 [%0], %1;" ::"r"(a), "h"((uint16_t)v) : "memory"); }
__device__ __forceinline__ void sts8(uint32_t a, uint32_t v) { asm volatile("st.shared.u8 [%0], %1;" ::"r"(a), "r"(v) : "memory"); }
__device__ __forceinline__ uint32_t lds32(uint32_t a) { uint32_t v; asm volatile("ld.shared.u32 %0, [%1];" : "=r"(v) : "r"(a)); return v; }
__device__ __forceinline__ uint32_t lds16(uint32_t a) { uint32_t v; asm volatile("ld.shared.u16 %0, [%1];" : "=r"(v) : "r"(a)); return v; }
__device__ __forceinline__ void cp16(uint32_t d, const void* p) {
    asm volatile("cp.async.cg.shared.global [%0], [%1], 16;" ::"r"(d), "l"(p) : "memory");
}
__device__ __forceinline__ uint32_t gtime() {
    uint32_t t;
    asm volatile("mov.u32 %0, %%globaltimer_lo;" : "=r"(t));
    return t;
}
__device__ __forceinline__ void mbar_init(uint32_t bar, int cnt) {
    asm volatile("mbarrier.init.shared.b64 [%0], %1;" ::"r"(bar), "r"(cnt) : "memory");
}
__device__ __forceinline__ void mbar_wait(uint32_t bar, uint32_t parity) {
    asm volatile("{\n.reg .pred p;\n.reg .u32 n;\nmov.u32 n, 0;\n"
                 "WAIT_%=:\nmbarrier.try_wait.parity.shared.b64 p, [%0], %1;\n@p bra DONE_%=;\n"
                 "add.u32 n, n, 1;\nsetp.lt.u32 p, n, 4194304;\n@p bra WAIT_%=;\ntrap;\nDONE_%=:\n}"
                 ::"r"(bar), "r"(parity) : "memory");
}
__device__ __forceinline__ void mbar_arrive_elect(uint32_t bar) {
    asm volatile("{\n.reg .pred p;\nelect.sync _|p, 0xffffffff;\n@p mbarrier.arrive.shared.b64 _, [%0];\n}" ::"r"(bar) : "memory");
}
__device__ __forceinline__ uint4 lds128(uint32_t a) {
    uint4 v;
    asm volatile("ld.shared.v4.u32 {%0,%1,%2,%3}, [%4];" : "=r"(v.x), "=r"(v.y), "=r"(v.z), "=r"(v.w) : "r"(a));
    return v;
}
__device__ __forceinline__ void sts128(uint32_t a, uint32_t x, uint32_t y, uint32_t z, uint32_t w) {
    asm volatile("st.shared.v4.u32 [%0], {%1,%2,%3,%4};" ::"r"(a), "r"(x), "r"(y), "r"(z), "r"(w) : "memory");
}
__device__ __forceinline__ uint32_t pack_bf16(float lo, float hi) {
    uint32_t r;
    asm("cvt.rn.bf16x2.f32 %0, %1, %2;" : "=r"(r) : "f"(hi), "f"(lo));
    return r;
}
__device__ __forceinline__ float tanh_fast(float x) {
    float r;
    asm("tanh.approx.f32 %0, %1;" : "=f"(r) : "f"(x));
    return r;
}
__device__ __forceinline__ uint32_t mul_lo(uint32_t v, uint32_t r) {
    __nv_bfloat162 a = *reinterpret_cast<__nv_bfloat162*>(&v), b = *reinterpret_cast<__nv_bfloat162*>(&r);
    __nv_bfloat162 c = __hmul2(a, __low2bfloat162(b));
    return *reinterpret_cast<uint32_t*>(&c);
}
__device__ __forceinline__ uint32_t mul_hi(uint32_t v, uint32_t r) {
    __nv_bfloat162 a = *reinterpret_cast<__nv_bfloat162*>(&v), b = *reinterpret_cast<__nv_bfloat162*>(&r);
    __nv_bfloat162 c = __hmul2(a, __high2bfloat162(b));
    return *reinterpret_cast<uint32_t*>(&c);
}
__device__ __forceinline__ void mma0(float (&d)[4], uint32_t a0, uint32_t a1, uint32_t a2, uint32_t a3,
                                     uint32_t b0, uint32_t b1) {
    asm("mma.sync.aligned.m16n8k16.row.col.f32.bf16.bf16.f32 {%0,%1,%2,%3}, {%4,%5,%6,%7}, {%8,%9}, {%10,%10,%10,%10};"
        : "=f"(d[0]), "=f"(d[1]), "=f"(d[2]), "=f"(d[3])
        : "r"(a0), "r"(a1), "r"(a2), "r"(a3), "r"(b0), "r"(b1), "f"(0.f));
}
__device__ __forceinline__ void mma0_k8(float (&d)[4], uint32_t a0, uint32_t a1, uint32_t b0) {
    asm("mma.sync.aligned.m16n8k8.row.col.f32.bf16.bf16.f32 {%0,%1,%2,%3}, {%4,%5}, {%6}, {%7,%7,%7,%7};"
        : "=f"(d[0]), "=f"(d[1]), "=f"(d[2]), "=f"(d[3])
        : "r"(a0), "r"(a1), "r"(b0), "f"(0.f));
}
__device__ __forceinline__ void mma_acc(float (&d)[4], const uint32_t (&a)[4], uint32_t b0, uint32_t b1) {
    asm volatile("mma.sync.aligned.m16n8k16.row.col.f32.bf16.bf16.f32 {%0,%1,%2,%3}, {%4,%5,%6,%7}, {%8,%9}, {%0,%1,%2,%3};"
        : "+f"(d[0]), "+f"(d[1]), "+f"(d[2]), "+f"(d[3])
        : "r"(a[0]), "r"(a[1]), "r"(a[2]), "r"(a[3]), "r"(b0), "r"(b1));
}
__device__ __forceinline__ void wgmma_n80(float (&d)[40], const uint32_t (&a)[4], uint64_t desc, int scale_d) {
    asm volatile("{\n.reg .pred p;\nsetp.ne.b32 p, %45, 0;\n"
        "wgmma.mma_async.sync.aligned.m64n80k16.f32.bf16.bf16 "
        "{%0,%1,%2,%3,%4,%5,%6,%7,%8,%9,%10,%11,%12,%13,%14,%15,%16,%17,%18,%19,"
        "%20,%21,%22,%23,%24,%25,%26,%27,%28,%29,%30,%31,%32,%33,%34,%35,%36,%37,%38,%39}, "
        "{%40,%41,%42,%43}, %44, p, 1, 1, 0;\n}"
        : "+f"(d[0]), "+f"(d[1]), "+f"(d[2]), "+f"(d[3]), "+f"(d[4]), "+f"(d[5]), "+f"(d[6]), "+f"(d[7]),
          "+f"(d[8]), "+f"(d[9]), "+f"(d[10]), "+f"(d[11]), "+f"(d[12]), "+f"(d[13]), "+f"(d[14]), "+f"(d[15]),
          "+f"(d[16]), "+f"(d[17]), "+f"(d[18]), "+f"(d[19]), "+f"(d[20]), "+f"(d[21]), "+f"(d[22]), "+f"(d[23]),
          "+f"(d[24]), "+f"(d[25]), "+f"(d[26]), "+f"(d[27]), "+f"(d[28]), "+f"(d[29]), "+f"(d[30]), "+f"(d[31]),
          "+f"(d[32]), "+f"(d[33]), "+f"(d[34]), "+f"(d[35]), "+f"(d[36]), "+f"(d[37]), "+f"(d[38]), "+f"(d[39])
        : "r"(a[0]), "r"(a[1]), "r"(a[2]), "r"(a[3]), "l"(desc), "r"(scale_d));
}

__device__ __forceinline__ void producer_loop(const void* xl, const void* efl, const void* Y, uint32_t xd, uint32_t oef,
                                              uint32_t ysel, uint32_t ring, uint32_t rec, uint32_t rlast, uint32_t odd,
                                              uint32_t lead, uint32_t lag) {
    asm volatile(
        "{\n"
        ".reg .b32 w, em, ey, cu, d, t, u, n, sa, ph, rp, rend, rlast, dy, sv, lag, lv;\n"
        ".reg .b16 tg;\n"
        ".reg .b64 pa, pb, pc, pd;\n"
        ".reg .pred lo, z, q, e, zb;\n"
        "redux.sync.or.b32 sa, %6, 0xffffffff;\n"
        "redux.sync.or.b32 rp, %7, 0xffffffff;\n"
        "redux.sync.or.b32 rlast, %8, 0xffffffff;\n"
        "add.u32 rend, sa, 44160;\n"
        "and.b32 t, %5, 1;\n"
        "setp.eq.u32 lo, t, 0;\n"
        "mov.u32 ph, 1;\n"
        "setp.ne.u32 q, %9, 0;\n"
        "@q bra.uni PODD_%=;\n"
        "add.u32 t, rp, %4;\n"
        "ld.shared.u32 em, [t+16];\n"
        "ld.shared.u32 cu, [rp+48];\n"
        "and.b32 t, em, 0xfffffff8;\n"
        "mad.wide.u32 pa, t, 4, %1;\n"
        "add.u32 d, sa, %3;\n"
        "cvt.u16.u32 tg, cu;\n"
        "st.shared.u16 [sa+8720], tg;\n"
        "elect.sync _|z, 0xffffffff;\n"
        "@z mbarrier.arrive.shared.b64 _, [sa+8704];\n"
        "@lo cp.async.cg.shared.global [d+2048], [pa], 16;\n"
        "cp.async.mbarrier.arrive.noinc.shared.b64 [sa+8704];\n"
        "add.u32 rp, rp, 52;\n"
        "add.u32 sa, sa, 8832;\n"
        "PODD_%=:\n"
        "add.u32 rp, rp, 52;\n"
        "add.u32 sa, sa, 8832;\n"
        "and.b32 t, %4, 12;\n"
        "add.u32 t, t, rp;\n"
        "ld.shared.u32 w, [t];\n"
        "add.u32 t, rp, %4;\n"
        "ld.shared.u32 em, [t+16];\n"
        "ld.shared.u32 ey, [t+-36];\n"
        "ld.shared.u32 cu, [rp+48];\n"
        "setp.eq.u32 e, sa, sa;\n"
        "setp.lt.u32 q, rp, rlast;\n"
        "@!q bra.uni PF_%=;\n"
        "PL_%=:\n"
        "and.b32 t, em, 0xfffffff8;\n"
        "mad.wide.u32 pa, t, 4, %1;\n"
        "and.b32 t, w, 0xffff;\n"
        "mad.wide.u32 pc, t, 1024, %0;\n"
        "shr.u32 t, w, 16;\n"
        "mad.wide.u32 pd, t, 1024, %0;\n"
        "mov.u32 u, %%clock;\n"
        "shl.b32 u, u, 14;\n"
        "sub.u32 u, u, cu;\n"
        "setp.ge.and.s32 q, u, 0, e;\n"
        "@q bra.uni PGO_%=;\n"
        "mov.u32 n, 0;\n"
        "PW1_%=:\n"
        "@e bra.uni PW2_%=;\n"
        "mbarrier.try_wait.parity.shared.b64 e, [sa+8712], ph;\n"
        "add.u32 n, n, 1;\n"
        "setp.lt.u32 q, n, 4194304;\n"
        "@q bra.uni PW1_%=;\n"
        "trap;\n"
        "PW2_%=:\n"
        "mov.u32 u, %%clock;\n"
        "shl.b32 u, u, 14;\n"
        "sub.u32 u, u, cu;\n"
        "setp.lt.s32 q, u, 0;\n"
        "@q bra.uni PW2_%=;\n"
        "PGO_%=:\n"
        "add.u32 d, sa, %3;\n"
        "cvt.u16.u32 tg, cu;\n"
        "st.shared.u16 [sa+8720], tg;\n"
        "elect.sync _|z, 0xffffffff;\n"
        "@z mbarrier.arrive.shared.b64 _, [sa+8704];\n"
        "@lo cp.async.cg.shared.global [d+2048], [pa], 16;\n"
        "xor.b32 t, ey, %5;\n"
        "and.b32 t, t, 7;\n"
        "setp.ne.u32 zb, t, 0;\n"
        "and.b32 t, ey, 0xfffffff8;\n"
        "cvt.u64.u32 pb, t;\n"
        "add.u64 pb, pb, %2;\n"
        "selp.u32 dy, 64, 8, lo;\n"
        "xor.b32 dy, dy, d;\n"
        "cp.async.ca.shared.global [dy+2048], [pb], 8, zb;\n"
        "cp.async.cg.shared.global [d+0], [pc+0], 16;\n"
        "cp.async.cg.shared.global [d+128], [pc+128], 16;\n"
        "cp.async.cg.shared.global [d+256], [pc+256], 16;\n"
        "cp.async.cg.shared.global [d+384], [pc+384], 16;\n"
        "cp.async.cg.shared.global [d+512], [pc+512], 16;\n"
        "cp.async.cg.shared.global [d+640], [pc+640], 16;\n"
        "cp.async.cg.shared.global [d+768], [pc+768], 16;\n"
        "cp.async.cg.shared.global [d+896], [pc+896], 16;\n"
        "cp.async.cg.shared.global [d+1024], [pd+0], 16;\n"
        "cp.async.cg.shared.global [d+1152], [pd+128], 16;\n"
        "cp.async.cg.shared.global [d+1280], [pd+256], 16;\n"
        "cp.async.cg.shared.global [d+1408], [pd+384], 16;\n"
        "cp.async.cg.shared.global [d+1536], [pd+512], 16;\n"
        "cp.async.cg.shared.global [d+1664], [pd+640], 16;\n"
        "cp.async.cg.shared.global [d+1792], [pd+768], 16;\n"
        "cp.async.cg.shared.global [d+1920], [pd+896], 16;\n"
        "add.u32 rp, rp, 104;\n"
        "and.b32 t, %4, 12;\n"
        "add.u32 t, t, rp;\n"
        "ld.shared.u32 w, [t];\n"
        "add.u32 t, rp, %4;\n"
        "ld.shared.u32 em, [t+16];\n"
        "ld.shared.u32 ey, [t+-36];\n"
        "ld.shared.u32 cu, [rp+48];\n"
        "cp.async.mbarrier.arrive.noinc.shared.b64 [sa+8704];\n"
        "add.u32 sa, sa, 17664;\n"
        "sub.u32 t, sa, 44160;\n"
        "setp.ge.u32 q, sa, rend;\n"
        "selp.u32 sa, t, sa, q;\n"
        "selp.u32 t, 1, 0, q;\n"
        "xor.b32 ph, ph, t;\n"
        "mbarrier.try_wait.parity.shared.b64 e, [sa+8712], ph;\n"
        "setp.lt.u32 q, rp, rlast;\n"
        "@q bra.uni PL_%=;\n"
        "PF_%=:\n"
        "setp.ne.u32 q, rp, rlast;\n"
        "@q bra.uni PX_%=;\n"
        "mov.u32 n, 0;\n"
        "PE1_%=:\n"
        "@e bra.uni PE2_%=;\n"
        "mbarrier.try_wait.parity.shared.b64 e, [sa+8712], ph;\n"
        "add.u32 n, n, 1;\n"
        "setp.lt.u32 q, n, 4194304;\n"
        "@q bra.uni PE1_%=;\n"
        "trap;\n"
        "PE2_%=:\n"
        "cp.async.mbarrier.arrive.noinc.shared.b64 [sa+8704];\n"
        "elect.sync _|z, 0xffffffff;\n"
        "@z mbarrier.arrive.shared.b64 _, [sa+8704];\n"
        "PX_%=:\n"
        "}\n"
        ::"l"(xl), "l"(efl), "l"(Y), "r"(xd), "r"(oef), "r"(ysel), "r"(ring), "r"(rec), "r"(rlast), "r"(odd),
          "l"(g_lag), "r"(lead), "r"(lag) : "memory");
}

__device__ __forceinline__ void consumer_loop(float (&acc)[5][4][2][4], const uint32_t (&wf)[4][4], const uint32_t (&cgf)[4],
                                              uint32_t xoff, uint32_t& ring, uint32_t moff) {
    asm volatile(
        "{\n"
        ".reg .b32 x<16>, a<4>, b<4>, r<4>, m<4>, rl, rh, tag, la, lb, sa, last, ph, tq, xa, ma, n, ring, sn, ln, yb, zz, k<4>;\n"
        ".reg .b16 lo, hi;\n"
        ".reg .f32 p<16>, d<4>, t0, t1, fz;\n"
        ".reg .pred q, w, el, c<5>;\n"
        "TA_%=: .branchtargets A0_%=, A1_%=, A2_%=, A3_%=, A4_%=, EXIT_%=;\n"
        "TB_%=: .branchtargets B0_%=, B1_%=, B2_%=, B3_%=, B4_%=, SPIN_%=;\n"
        "mov.f32 fz, 0f00000000;\n"
        "redux.sync.or.b32 ring, %160, 0xffffffff;\n"
        "mov.u32 sa, ring;\n"
        "add.u32 last, ring, 35328;\n"
        "mov.u32 ph, 0;\n"
        "redux.sync.xor.b32 zz, %160, 0xffffffff;\n"
        "mov.u32 k0, sa;\n"
        "mov.u32 k1, sa;\n"
        "mov.u32 k2, sa;\n"
        "mov.u32 k3, sa;\n"
        "mov.b32 x0, 0;\n"
        "mov.b32 x1, 0;\n"
        "mov.b32 x2, 0;\n"
        "mov.b32 x3, 0;\n"
        "mov.b32 x4, 0;\n"
        "mov.b32 x5, 0;\n"
        "mov.b32 x6, 0;\n"
        "mov.b32 x7, 0;\n"
        "mov.b32 x8, 0;\n"
        "mov.b32 x9, 0;\n"
        "mov.b32 x10, 0;\n"
        "mov.b32 x11, 0;\n"
        "mov.b32 x12, 0;\n"
        "mov.b32 x13, 0;\n"
        "mov.b32 x14, 0;\n"
        "mov.b32 x15, 0;\n"
        "mov.b32 b0, 0;\n"
        "mov.b32 r0, 0;\n"
        "mov.b32 b1, 0;\n"
        "mov.b32 r1, 0;\n"
        "mov.b32 b2, 0;\n"
        "mov.b32 r2, 0;\n"
        "mov.b32 b3, 0;\n"
        "mov.b32 r3, 0;\n"
        "mov.u32 lb, 0;\n"
        "mov.u32 n, 0;\n"
        "W0_%=:\n"
        "mbarrier.try_wait.parity.shared.b64 w, [sa+8704], 0;\n"
        "@w bra.uni W0D_%=;\n"
        "add.u32 n, n, 1;\n"
        "setp.lt.u32 q, n, 4194304;\n"
        "@q bra.uni W0_%=;\n"
        "trap;\n"
        "W0D_%=:\n"
        "add.u32 ma, sa, %182;\n"
        "ldmatrix.sync.aligned.m8n8.x4.shared.b16 {m0,m1,m2,m3}, [ma];\n"
        "ld.shared.u16 tag, [k0+8720];\n"
        "add.u32 sn, sa, 8832;\n"
        "setp.eq.u32 q, sa, last;\n"
        "selp.u32 sn, ring, sn, q;\n"
        "selp.u32 tq, 1, 0, q;\n"
        "xor.b32 ph, ph, tq;\n"
        "mbarrier.test_wait.parity.shared.b64 w, [sn+8704], ph;\n"
        "mma.sync.aligned.m16n8k16.row.col.f32.bf16.bf16.f32 {p0,p1,p2,p3}, {%161,%162,%163,%164}, {m2,m3}, {fz,fz,fz,fz};\n"
        "mma.sync.aligned.m16n8k16.row.col.f32.bf16.bf16.f32 {p4,p5,p6,p7}, {%165,%166,%167,%168}, {m2,m3}, {fz,fz,fz,fz};\n"
        "mma.sync.aligned.m16n8k16.row.col.f32.bf16.bf16.f32 {p8,p9,p10,p11}, {%169,%170,%171,%172}, {m2,m3}, {fz,fz,fz,fz};\n"
        "mma.sync.aligned.m16n8k16.row.col.f32.bf16.bf16.f32 {p12,p13,p14,p15}, {%173,%174,%175,%176}, {m2,m3}, {fz,fz,fz,fz};\n"
        "elect.sync _|el, 0xffffffff;\n"
        "@el mbarrier.arrive.shared.b64 _, [k1+8712];\n"
        "redux.sync.or.b32 ln, tag, 0xffffffff;\n"
        "mov.u32 sa, sn;\n"
        "add.u32 k0, sn, zz;\n"
        "or.b32 k1, sn, zz;\n"
        "SPIN_%=:\n"
        "mov.u32 n, 0;\n"
        "SP1_%=:\n"
        "mbarrier.try_wait.parity.shared.b64 w, [sa+8704], ph;\n"
        "@w bra.uni SP2_%=;\n"
        "add.u32 n, n, 1;\n"
        "setp.lt.u32 q, n, 4194304;\n"
        "@q bra.uni SP1_%=;\n"
        "trap;\n"
        "SP2_%=:\n"
        "brx.idx.uni lb, TB_%=;\n"
        "A0_%=:\n"
        "add.u32 xa, sa, %181;\n"
        "add.u32 ma, sa, %182;\n"
        "ldmatrix.sync.aligned.m8n8.x4.shared.b16 {m0,m1,m2,m3}, [ma];\n"
        "ld.shared.u16 tag, [k0+8720];\n"
        "add.u32 sn, sa, 8832;\n"
        "setp.eq.u32 q, sa, last;\n"
        "selp.u32 sn, ring, sn, q;\n"
        "selp.u32 tq, 1, 0, q;\n"
        "xor.b32 ph, ph, tq;\n"
        "mbarrier.test_wait.parity.shared.b64 w, [sn+8704], ph;\n"
        "mma.sync.aligned.m16n8k16.row.col.f32.bf16.bf16.f32 {%0,%1,%2,%3}, {a0,a1,a2,a3}, {x0,x1}, {%0,%1,%2,%3};\n"
        "mma.sync.aligned.m16n8k16.row.col.f32.bf16.bf16.f32 {%4,%5,%6,%7}, {a0,a1,a2,a3}, {x2,x3}, {%4,%5,%6,%7};\n"
        "ld.shared.v4.u32 {x0,x1,x2,x3}, [xa+1024];\n"
        "tanh.approx.f32 t0, p1;\n"
        "tanh.approx.f32 t1, p3;\n"
        "fma.rn.f32 t0, p1, t0, p1;\n"
        "fma.rn.f32 t1, p3, t1, p3;\n"
        "cvt.rn.bf16x2.f32 r0, t1, t0;\n"
        "mma.sync.aligned.m16n8k16.row.col.f32.bf16.bf16.f32 {p0,p1,p2,p3}, {%161,%162,%163,%164}, {m2,m3}, {fz,fz,fz,fz};\n"
        "mma.sync.aligned.m16n8k16.row.col.f32.bf16.bf16.f32 {%8,%9,%10,%11}, {a0,a1,a2,a3}, {x4,x5}, {%8,%9,%10,%11};\n"
        "mma.sync.aligned.m16n8k16.row.col.f32.bf16.bf16.f32 {%12,%13,%14,%15}, {a0,a1,a2,a3}, {x6,x7}, {%12,%13,%14,%15};\n"
        "ld.shared.v4.u32 {x4,x5,x6,x7}, [xa+1152];\n"
        "mma.sync.aligned.m16n8k8.row.col.f32.bf16.bf16.f32 {d0,d1,d2,d3}, {%177,%178}, {m1}, {fz,fz,fz,fz};\n"
        "cvt.rn.bf16x2.f32 b0, d2, d0;\n"
        "cvt.rn.bf16x2.f32 b1, d3, d1;\n"
        "tanh.approx.f32 t0, p5;\n"
        "tanh.approx.f32 t1, p7;\n"
        "fma.rn.f32 t0, p5, t0, p5;\n"
        "fma.rn.f32 t1, p7, t1, p7;\n"
        "cvt.rn.bf16x2.f32 r1, t1, t0;\n"
        "mma.sync.aligned.m16n8k16.row.col.f32.bf16.bf16.f32 {p4,p5,p6,p7}, {%165,%166,%167,%168}, {m2,m3}, {fz,fz,fz,fz};\n"
        "mov.b32 {lo,hi}, r2;\n"
        "mov.b32 rl, {lo,lo};\n"
        "mov.b32 rh, {hi,hi};\n"
        "mul.bf16x2 x8, x8, rl;\n"
        "mul.bf16x2 x9, x9, rl;\n"
        "mul.bf16x2 x10, x10, rh;\n"
        "mul.bf16x2 x11, x11, rh;\n"
        "mma.sync.aligned.m16n8k16.row.col.f32.bf16.bf16.f32 {%16,%17,%18,%19}, {a0,a1,a2,a3}, {x8,x9}, {%16,%17,%18,%19};\n"
        "mma.sync.aligned.m16n8k16.row.col.f32.bf16.bf16.f32 {%20,%21,%22,%23}, {a0,a1,a2,a3}, {x10,x11}, {%20,%21,%22,%23};\n"
        "ld.shared.v4.u32 {x8,x9,x10,x11}, [xa+1280];\n"
        "mma.sync.aligned.m16n8k8.row.col.f32.bf16.bf16.f32 {d0,d1,d2,d3}, {%179,%180}, {m1}, {fz,fz,fz,fz};\n"
        "cvt.rn.bf16x2.f32 b2, d2, d0;\n"
        "cvt.rn.bf16x2.f32 b3, d3, d1;\n"
        "tanh.approx.f32 t0, p9;\n"
        "tanh.approx.f32 t1, p11;\n"
        "fma.rn.f32 t0, p9, t0, p9;\n"
        "fma.rn.f32 t1, p11, t1, p11;\n"
        "cvt.rn.bf16x2.f32 r2, t1, t0;\n"
        "mma.sync.aligned.m16n8k16.row.col.f32.bf16.bf16.f32 {p8,p9,p10,p11}, {%169,%170,%171,%172}, {m2,m3}, {fz,fz,fz,fz};\n"
        "selp.u32 tq, lb, 5, w;\n"
        "mov.b32 {lo,hi}, r3;\n"
        "mov.b32 rl, {lo,lo};\n"
        "mov.b32 rh, {hi,hi};\n"
        "mul.bf16x2 x12, x12, rl;\n"
        "mul.bf16x2 x13, x13, rl;\n"
        "mul.bf16x2 x14, x14, rh;\n"
        "mul.bf16x2 x15, x15, rh;\n"
        "mma.sync.aligned.m16n8k16.row.col.f32.bf16.bf16.f32 {%24,%25,%26,%27}, {a0,a1,a2,a3}, {x12,x13}, {%24,%25,%26,%27};\n"
        "mma.sync.aligned.m16n8k16.row.col.f32.bf16.bf16.f32 {%28,%29,%30,%31}, {a0,a1,a2,a3}, {x14,x15}, {%28,%29,%30,%31};\n"
        "ld.shared.v4.u32 {x12,x13,x14,x15}, [xa+1408];\n"
        "elect.sync _|el, 0xffffffff;\n"
        "@el mbarrier.arrive.shared.b64 _, [k1+8712];\n"
        "redux.sync.or.b32 ln, tag, 0xffffffff;\n"
        "mov.u32 sa, sn;\n"
        "add.u32 k0, sn, zz;\n"
        "or.b32 k1, sn, zz;\n"
        "tanh.approx.f32 t0, p13;\n"
        "tanh.approx.f32 t1, p15;\n"
        "fma.rn.f32 t0, p13, t0, p13;\n"
        "fma.rn.f32 t1, p15, t1, p15;\n"
        "cvt.rn.bf16x2.f32 r3, t1, t0;\n"
        "mma.sync.aligned.m16n8k16.row.col.f32.bf16.bf16.f32 {p12,p13,p14,p15}, {%173,%174,%175,%176}, {m2,m3}, {fz,fz,fz,fz};\n"
        "mov.b32 {lo,hi}, r0;\n"
        "mov.b32 rl, {lo,lo};\n"
        "mov.b32 rh, {hi,hi};\n"
        "mul.bf16x2 x0, x0, rl;\n"
        "mul.bf16x2 x1, x1, rl;\n"
        "mul.bf16x2 x2, x2, rh;\n"
        "mul.bf16x2 x3, x3, rh;\n"
        "mov.b32 {lo,hi}, r1;\n"
        "mov.b32 rl, {lo,lo};\n"
        "mov.b32 rh, {hi,hi};\n"
        "mul.bf16x2 x4, x4, rl;\n"
        "mul.bf16x2 x5, x5, rl;\n"
        "mul.bf16x2 x6, x6, rh;\n"
        "mul.bf16x2 x7, x7, rh;\n"
        "brx.idx.uni tq, TB_%=;\n"
        "A1_%=:\n"
        "add.u32 xa, sa, %181;\n"
        "add.u32 ma, sa, %182;\n"
        "ldmatrix.sync.aligned.m8n8.x4.shared.b16 {m0,m1,m2,m3}, [ma];\n"
        "ld.shared.u16 tag, [k0+8720];\n"
        "add.u32 sn, sa, 8832;\n"
        "setp.eq.u32 q, sa, last;\n"
        "selp.u32 sn, ring, sn, q;\n"
        "selp.u32 tq, 1, 0, q;\n"
        "xor.b32 ph, ph, tq;\n"
        "mbarrier.test_wait.parity.shared.b64 w, [sn+8704], ph;\n"
        "mma.sync.aligned.m16n8k16.row.col.f32.bf16.bf16.f32 {%32,%33,%34,%35}, {a0,a1,a2,a3}, {x0,x1}, {%32,%33,%34,%35};\n"
        "mma.sync.aligned.m16n8k16.row.col.f32.bf16.bf16.f32 {%36,%37,%38,%39}, {a0,a1,a2,a3}, {x2,x3}, {%36,%37,%38,%39};\n"
        "ld.shared.v4.u32 {x0,x1,x2,x3}, [xa+1024];\n"
        "tanh.approx.f32 t0, p1;\n"
        "tanh.approx.f32 t1, p3;\n"
        "fma.rn.f32 t0, p1, t0, p1;\n"
        "fma.rn.f32 t1, p3, t1, p3;\n"
        "cvt.rn.bf16x2.f32 r0, t1, t0;\n"
        "mma.sync.aligned.m16n8k16.row.col.f32.bf16.bf16.f32 {p0,p1,p2,p3}, {%161,%162,%163,%164}, {m2,m3}, {fz,fz,fz,fz};\n"
        "mma.sync.aligned.m16n8k16.row.col.f32.bf16.bf16.f32 {%40,%41,%42,%43}, {a0,a1,a2,a3}, {x4,x5}, {%40,%41,%42,%43};\n"
        "mma.sync.aligned.m16n8k16.row.col.f32.bf16.bf16.f32 {%44,%45,%46,%47}, {a0,a1,a2,a3}, {x6,x7}, {%44,%45,%46,%47};\n"
        "ld.shared.v4.u32 {x4,x5,x6,x7}, [xa+1152];\n"
        "mma.sync.aligned.m16n8k8.row.col.f32.bf16.bf16.f32 {d0,d1,d2,d3}, {%177,%178}, {m1}, {fz,fz,fz,fz};\n"
        "cvt.rn.bf16x2.f32 b0, d2, d0;\n"
        "cvt.rn.bf16x2.f32 b1, d3, d1;\n"
        "tanh.approx.f32 t0, p5;\n"
        "tanh.approx.f32 t1, p7;\n"
        "fma.rn.f32 t0, p5, t0, p5;\n"
        "fma.rn.f32 t1, p7, t1, p7;\n"
        "cvt.rn.bf16x2.f32 r1, t1, t0;\n"
        "mma.sync.aligned.m16n8k16.row.col.f32.bf16.bf16.f32 {p4,p5,p6,p7}, {%165,%166,%167,%168}, {m2,m3}, {fz,fz,fz,fz};\n"
        "mov.b32 {lo,hi}, r2;\n"
        "mov.b32 rl, {lo,lo};\n"
        "mov.b32 rh, {hi,hi};\n"
        "mul.bf16x2 x8, x8, rl;\n"
        "mul.bf16x2 x9, x9, rl;\n"
        "mul.bf16x2 x10, x10, rh;\n"
        "mul.bf16x2 x11, x11, rh;\n"
        "mma.sync.aligned.m16n8k16.row.col.f32.bf16.bf16.f32 {%48,%49,%50,%51}, {a0,a1,a2,a3}, {x8,x9}, {%48,%49,%50,%51};\n"
        "mma.sync.aligned.m16n8k16.row.col.f32.bf16.bf16.f32 {%52,%53,%54,%55}, {a0,a1,a2,a3}, {x10,x11}, {%52,%53,%54,%55};\n"
        "ld.shared.v4.u32 {x8,x9,x10,x11}, [xa+1280];\n"
        "mma.sync.aligned.m16n8k8.row.col.f32.bf16.bf16.f32 {d0,d1,d2,d3}, {%179,%180}, {m1}, {fz,fz,fz,fz};\n"
        "cvt.rn.bf16x2.f32 b2, d2, d0;\n"
        "cvt.rn.bf16x2.f32 b3, d3, d1;\n"
        "tanh.approx.f32 t0, p9;\n"
        "tanh.approx.f32 t1, p11;\n"
        "fma.rn.f32 t0, p9, t0, p9;\n"
        "fma.rn.f32 t1, p11, t1, p11;\n"
        "cvt.rn.bf16x2.f32 r2, t1, t0;\n"
        "mma.sync.aligned.m16n8k16.row.col.f32.bf16.bf16.f32 {p8,p9,p10,p11}, {%169,%170,%171,%172}, {m2,m3}, {fz,fz,fz,fz};\n"
        "selp.u32 tq, lb, 5, w;\n"
        "mov.b32 {lo,hi}, r3;\n"
        "mov.b32 rl, {lo,lo};\n"
        "mov.b32 rh, {hi,hi};\n"
        "mul.bf16x2 x12, x12, rl;\n"
        "mul.bf16x2 x13, x13, rl;\n"
        "mul.bf16x2 x14, x14, rh;\n"
        "mul.bf16x2 x15, x15, rh;\n"
        "mma.sync.aligned.m16n8k16.row.col.f32.bf16.bf16.f32 {%56,%57,%58,%59}, {a0,a1,a2,a3}, {x12,x13}, {%56,%57,%58,%59};\n"
        "mma.sync.aligned.m16n8k16.row.col.f32.bf16.bf16.f32 {%60,%61,%62,%63}, {a0,a1,a2,a3}, {x14,x15}, {%60,%61,%62,%63};\n"
        "ld.shared.v4.u32 {x12,x13,x14,x15}, [xa+1408];\n"
        "elect.sync _|el, 0xffffffff;\n"
        "@el mbarrier.arrive.shared.b64 _, [k1+8712];\n"
        "redux.sync.or.b32 ln, tag, 0xffffffff;\n"
        "mov.u32 sa, sn;\n"
        "add.u32 k0, sn, zz;\n"
        "or.b32 k1, sn, zz;\n"
        "tanh.approx.f32 t0, p13;\n"
        "tanh.approx.f32 t1, p15;\n"
        "fma.rn.f32 t0, p13, t0, p13;\n"
        "fma.rn.f32 t1, p15, t1, p15;\n"
        "cvt.rn.bf16x2.f32 r3, t1, t0;\n"
        "mma.sync.aligned.m16n8k16.row.col.f32.bf16.bf16.f32 {p12,p13,p14,p15}, {%173,%174,%175,%176}, {m2,m3}, {fz,fz,fz,fz};\n"
        "mov.b32 {lo,hi}, r0;\n"
        "mov.b32 rl, {lo,lo};\n"
        "mov.b32 rh, {hi,hi};\n"
        "mul.bf16x2 x0, x0, rl;\n"
        "mul.bf16x2 x1, x1, rl;\n"
        "mul.bf16x2 x2, x2, rh;\n"
        "mul.bf16x2 x3, x3, rh;\n"
        "mov.b32 {lo,hi}, r1;\n"
        "mov.b32 rl, {lo,lo};\n"
        "mov.b32 rh, {hi,hi};\n"
        "mul.bf16x2 x4, x4, rl;\n"
        "mul.bf16x2 x5, x5, rl;\n"
        "mul.bf16x2 x6, x6, rh;\n"
        "mul.bf16x2 x7, x7, rh;\n"
        "brx.idx.uni tq, TB_%=;\n"
        "A2_%=:\n"
        "add.u32 xa, sa, %181;\n"
        "add.u32 ma, sa, %182;\n"
        "ldmatrix.sync.aligned.m8n8.x4.shared.b16 {m0,m1,m2,m3}, [ma];\n"
        "ld.shared.u16 tag, [k0+8720];\n"
        "add.u32 sn, sa, 8832;\n"
        "setp.eq.u32 q, sa, last;\n"
        "selp.u32 sn, ring, sn, q;\n"
        "selp.u32 tq, 1, 0, q;\n"
        "xor.b32 ph, ph, tq;\n"
        "mbarrier.test_wait.parity.shared.b64 w, [sn+8704], ph;\n"
        "mma.sync.aligned.m16n8k16.row.col.f32.bf16.bf16.f32 {%64,%65,%66,%67}, {a0,a1,a2,a3}, {x0,x1}, {%64,%65,%66,%67};\n"
        "mma.sync.aligned.m16n8k16.row.col.f32.bf16.bf16.f32 {%68,%69,%70,%71}, {a0,a1,a2,a3}, {x2,x3}, {%68,%69,%70,%71};\n"
        "ld.shared.v4.u32 {x0,x1,x2,x3}, [xa+1024];\n"
        "tanh.approx.f32 t0, p1;\n"
        "tanh.approx.f32 t1, p3;\n"
        "fma.rn.f32 t0, p1, t0, p1;\n"
        "fma.rn.f32 t1, p3, t1, p3;\n"
        "cvt.rn.bf16x2.f32 r0, t1, t0;\n"
        "mma.sync.aligned.m16n8k16.row.col.f32.bf16.bf16.f32 {p0,p1,p2,p3}, {%161,%162,%163,%164}, {m2,m3}, {fz,fz,fz,fz};\n"
        "mma.sync.aligned.m16n8k16.row.col.f32.bf16.bf16.f32 {%72,%73,%74,%75}, {a0,a1,a2,a3}, {x4,x5}, {%72,%73,%74,%75};\n"
        "mma.sync.aligned.m16n8k16.row.col.f32.bf16.bf16.f32 {%76,%77,%78,%79}, {a0,a1,a2,a3}, {x6,x7}, {%76,%77,%78,%79};\n"
        "ld.shared.v4.u32 {x4,x5,x6,x7}, [xa+1152];\n"
        "mma.sync.aligned.m16n8k8.row.col.f32.bf16.bf16.f32 {d0,d1,d2,d3}, {%177,%178}, {m1}, {fz,fz,fz,fz};\n"
        "cvt.rn.bf16x2.f32 b0, d2, d0;\n"
        "cvt.rn.bf16x2.f32 b1, d3, d1;\n"
        "tanh.approx.f32 t0, p5;\n"
        "tanh.approx.f32 t1, p7;\n"
        "fma.rn.f32 t0, p5, t0, p5;\n"
        "fma.rn.f32 t1, p7, t1, p7;\n"
        "cvt.rn.bf16x2.f32 r1, t1, t0;\n"
        "mma.sync.aligned.m16n8k16.row.col.f32.bf16.bf16.f32 {p4,p5,p6,p7}, {%165,%166,%167,%168}, {m2,m3}, {fz,fz,fz,fz};\n"
        "mov.b32 {lo,hi}, r2;\n"
        "mov.b32 rl, {lo,lo};\n"
        "mov.b32 rh, {hi,hi};\n"
        "mul.bf16x2 x8, x8, rl;\n"
        "mul.bf16x2 x9, x9, rl;\n"
        "mul.bf16x2 x10, x10, rh;\n"
        "mul.bf16x2 x11, x11, rh;\n"
        "mma.sync.aligned.m16n8k16.row.col.f32.bf16.bf16.f32 {%80,%81,%82,%83}, {a0,a1,a2,a3}, {x8,x9}, {%80,%81,%82,%83};\n"
        "mma.sync.aligned.m16n8k16.row.col.f32.bf16.bf16.f32 {%84,%85,%86,%87}, {a0,a1,a2,a3}, {x10,x11}, {%84,%85,%86,%87};\n"
        "ld.shared.v4.u32 {x8,x9,x10,x11}, [xa+1280];\n"
        "mma.sync.aligned.m16n8k8.row.col.f32.bf16.bf16.f32 {d0,d1,d2,d3}, {%179,%180}, {m1}, {fz,fz,fz,fz};\n"
        "cvt.rn.bf16x2.f32 b2, d2, d0;\n"
        "cvt.rn.bf16x2.f32 b3, d3, d1;\n"
        "tanh.approx.f32 t0, p9;\n"
        "tanh.approx.f32 t1, p11;\n"
        "fma.rn.f32 t0, p9, t0, p9;\n"
        "fma.rn.f32 t1, p11, t1, p11;\n"
        "cvt.rn.bf16x2.f32 r2, t1, t0;\n"
        "mma.sync.aligned.m16n8k16.row.col.f32.bf16.bf16.f32 {p8,p9,p10,p11}, {%169,%170,%171,%172}, {m2,m3}, {fz,fz,fz,fz};\n"
        "selp.u32 tq, lb, 5, w;\n"
        "mov.b32 {lo,hi}, r3;\n"
        "mov.b32 rl, {lo,lo};\n"
        "mov.b32 rh, {hi,hi};\n"
        "mul.bf16x2 x12, x12, rl;\n"
        "mul.bf16x2 x13, x13, rl;\n"
        "mul.bf16x2 x14, x14, rh;\n"
        "mul.bf16x2 x15, x15, rh;\n"
        "mma.sync.aligned.m16n8k16.row.col.f32.bf16.bf16.f32 {%88,%89,%90,%91}, {a0,a1,a2,a3}, {x12,x13}, {%88,%89,%90,%91};\n"
        "mma.sync.aligned.m16n8k16.row.col.f32.bf16.bf16.f32 {%92,%93,%94,%95}, {a0,a1,a2,a3}, {x14,x15}, {%92,%93,%94,%95};\n"
        "ld.shared.v4.u32 {x12,x13,x14,x15}, [xa+1408];\n"
        "elect.sync _|el, 0xffffffff;\n"
        "@el mbarrier.arrive.shared.b64 _, [k1+8712];\n"
        "redux.sync.or.b32 ln, tag, 0xffffffff;\n"
        "mov.u32 sa, sn;\n"
        "add.u32 k0, sn, zz;\n"
        "or.b32 k1, sn, zz;\n"
        "tanh.approx.f32 t0, p13;\n"
        "tanh.approx.f32 t1, p15;\n"
        "fma.rn.f32 t0, p13, t0, p13;\n"
        "fma.rn.f32 t1, p15, t1, p15;\n"
        "cvt.rn.bf16x2.f32 r3, t1, t0;\n"
        "mma.sync.aligned.m16n8k16.row.col.f32.bf16.bf16.f32 {p12,p13,p14,p15}, {%173,%174,%175,%176}, {m2,m3}, {fz,fz,fz,fz};\n"
        "mov.b32 {lo,hi}, r0;\n"
        "mov.b32 rl, {lo,lo};\n"
        "mov.b32 rh, {hi,hi};\n"
        "mul.bf16x2 x0, x0, rl;\n"
        "mul.bf16x2 x1, x1, rl;\n"
        "mul.bf16x2 x2, x2, rh;\n"
        "mul.bf16x2 x3, x3, rh;\n"
        "mov.b32 {lo,hi}, r1;\n"
        "mov.b32 rl, {lo,lo};\n"
        "mov.b32 rh, {hi,hi};\n"
        "mul.bf16x2 x4, x4, rl;\n"
        "mul.bf16x2 x5, x5, rl;\n"
        "mul.bf16x2 x6, x6, rh;\n"
        "mul.bf16x2 x7, x7, rh;\n"
        "brx.idx.uni tq, TB_%=;\n"
        "A3_%=:\n"
        "add.u32 xa, sa, %181;\n"
        "add.u32 ma, sa, %182;\n"
        "ldmatrix.sync.aligned.m8n8.x4.shared.b16 {m0,m1,m2,m3}, [ma];\n"
        "ld.shared.u16 tag, [k0+8720];\n"
        "add.u32 sn, sa, 8832;\n"
        "setp.eq.u32 q, sa, last;\n"
        "selp.u32 sn, ring, sn, q;\n"
        "selp.u32 tq, 1, 0, q;\n"
        "xor.b32 ph, ph, tq;\n"
        "mbarrier.test_wait.parity.shared.b64 w, [sn+8704], ph;\n"
        "mma.sync.aligned.m16n8k16.row.col.f32.bf16.bf16.f32 {%96,%97,%98,%99}, {a0,a1,a2,a3}, {x0,x1}, {%96,%97,%98,%99};\n"
        "mma.sync.aligned.m16n8k16.row.col.f32.bf16.bf16.f32 {%100,%101,%102,%103}, {a0,a1,a2,a3}, {x2,x3}, {%100,%101,%102,%103};\n"
        "ld.shared.v4.u32 {x0,x1,x2,x3}, [xa+1024];\n"
        "tanh.approx.f32 t0, p1;\n"
        "tanh.approx.f32 t1, p3;\n"
        "fma.rn.f32 t0, p1, t0, p1;\n"
        "fma.rn.f32 t1, p3, t1, p3;\n"
        "cvt.rn.bf16x2.f32 r0, t1, t0;\n"
        "mma.sync.aligned.m16n8k16.row.col.f32.bf16.bf16.f32 {p0,p1,p2,p3}, {%161,%162,%163,%164}, {m2,m3}, {fz,fz,fz,fz};\n"
        "mma.sync.aligned.m16n8k16.row.col.f32.bf16.bf16.f32 {%104,%105,%106,%107}, {a0,a1,a2,a3}, {x4,x5}, {%104,%105,%106,%107};\n"
        "mma.sync.aligned.m16n8k16.row.col.f32.bf16.bf16.f32 {%108,%109,%110,%111}, {a0,a1,a2,a3}, {x6,x7}, {%108,%109,%110,%111};\n"
        "ld.shared.v4.u32 {x4,x5,x6,x7}, [xa+1152];\n"
        "mma.sync.aligned.m16n8k8.row.col.f32.bf16.bf16.f32 {d0,d1,d2,d3}, {%177,%178}, {m1}, {fz,fz,fz,fz};\n"
        "cvt.rn.bf16x2.f32 b0, d2, d0;\n"
        "cvt.rn.bf16x2.f32 b1, d3, d1;\n"
        "tanh.approx.f32 t0, p5;\n"
        "tanh.approx.f32 t1, p7;\n"
        "fma.rn.f32 t0, p5, t0, p5;\n"
        "fma.rn.f32 t1, p7, t1, p7;\n"
        "cvt.rn.bf16x2.f32 r1, t1, t0;\n"
        "mma.sync.aligned.m16n8k16.row.col.f32.bf16.bf16.f32 {p4,p5,p6,p7}, {%165,%166,%167,%168}, {m2,m3}, {fz,fz,fz,fz};\n"
        "mov.b32 {lo,hi}, r2;\n"
        "mov.b32 rl, {lo,lo};\n"
        "mov.b32 rh, {hi,hi};\n"
        "mul.bf16x2 x8, x8, rl;\n"
        "mul.bf16x2 x9, x9, rl;\n"
        "mul.bf16x2 x10, x10, rh;\n"
        "mul.bf16x2 x11, x11, rh;\n"
        "mma.sync.aligned.m16n8k16.row.col.f32.bf16.bf16.f32 {%112,%113,%114,%115}, {a0,a1,a2,a3}, {x8,x9}, {%112,%113,%114,%115};\n"
        "mma.sync.aligned.m16n8k16.row.col.f32.bf16.bf16.f32 {%116,%117,%118,%119}, {a0,a1,a2,a3}, {x10,x11}, {%116,%117,%118,%119};\n"
        "ld.shared.v4.u32 {x8,x9,x10,x11}, [xa+1280];\n"
        "mma.sync.aligned.m16n8k8.row.col.f32.bf16.bf16.f32 {d0,d1,d2,d3}, {%179,%180}, {m1}, {fz,fz,fz,fz};\n"
        "cvt.rn.bf16x2.f32 b2, d2, d0;\n"
        "cvt.rn.bf16x2.f32 b3, d3, d1;\n"
        "tanh.approx.f32 t0, p9;\n"
        "tanh.approx.f32 t1, p11;\n"
        "fma.rn.f32 t0, p9, t0, p9;\n"
        "fma.rn.f32 t1, p11, t1, p11;\n"
        "cvt.rn.bf16x2.f32 r2, t1, t0;\n"
        "mma.sync.aligned.m16n8k16.row.col.f32.bf16.bf16.f32 {p8,p9,p10,p11}, {%169,%170,%171,%172}, {m2,m3}, {fz,fz,fz,fz};\n"
        "selp.u32 tq, lb, 5, w;\n"
        "mov.b32 {lo,hi}, r3;\n"
        "mov.b32 rl, {lo,lo};\n"
        "mov.b32 rh, {hi,hi};\n"
        "mul.bf16x2 x12, x12, rl;\n"
        "mul.bf16x2 x13, x13, rl;\n"
        "mul.bf16x2 x14, x14, rh;\n"
        "mul.bf16x2 x15, x15, rh;\n"
        "mma.sync.aligned.m16n8k16.row.col.f32.bf16.bf16.f32 {%120,%121,%122,%123}, {a0,a1,a2,a3}, {x12,x13}, {%120,%121,%122,%123};\n"
        "mma.sync.aligned.m16n8k16.row.col.f32.bf16.bf16.f32 {%124,%125,%126,%127}, {a0,a1,a2,a3}, {x14,x15}, {%124,%125,%126,%127};\n"
        "ld.shared.v4.u32 {x12,x13,x14,x15}, [xa+1408];\n"
        "elect.sync _|el, 0xffffffff;\n"
        "@el mbarrier.arrive.shared.b64 _, [k1+8712];\n"
        "redux.sync.or.b32 ln, tag, 0xffffffff;\n"
        "mov.u32 sa, sn;\n"
        "add.u32 k0, sn, zz;\n"
        "or.b32 k1, sn, zz;\n"
        "tanh.approx.f32 t0, p13;\n"
        "tanh.approx.f32 t1, p15;\n"
        "fma.rn.f32 t0, p13, t0, p13;\n"
        "fma.rn.f32 t1, p15, t1, p15;\n"
        "cvt.rn.bf16x2.f32 r3, t1, t0;\n"
        "mma.sync.aligned.m16n8k16.row.col.f32.bf16.bf16.f32 {p12,p13,p14,p15}, {%173,%174,%175,%176}, {m2,m3}, {fz,fz,fz,fz};\n"
        "mov.b32 {lo,hi}, r0;\n"
        "mov.b32 rl, {lo,lo};\n"
        "mov.b32 rh, {hi,hi};\n"
        "mul.bf16x2 x0, x0, rl;\n"
        "mul.bf16x2 x1, x1, rl;\n"
        "mul.bf16x2 x2, x2, rh;\n"
        "mul.bf16x2 x3, x3, rh;\n"
        "mov.b32 {lo,hi}, r1;\n"
        "mov.b32 rl, {lo,lo};\n"
        "mov.b32 rh, {hi,hi};\n"
        "mul.bf16x2 x4, x4, rl;\n"
        "mul.bf16x2 x5, x5, rl;\n"
        "mul.bf16x2 x6, x6, rh;\n"
        "mul.bf16x2 x7, x7, rh;\n"
        "brx.idx.uni tq, TB_%=;\n"
        "A4_%=:\n"
        "add.u32 xa, sa, %181;\n"
        "add.u32 ma, sa, %182;\n"
        "ldmatrix.sync.aligned.m8n8.x4.shared.b16 {m0,m1,m2,m3}, [ma];\n"
        "ld.shared.u16 tag, [k0+8720];\n"
        "add.u32 sn, sa, 8832;\n"
        "setp.eq.u32 q, sa, last;\n"
        "selp.u32 sn, ring, sn, q;\n"
        "selp.u32 tq, 1, 0, q;\n"
        "xor.b32 ph, ph, tq;\n"
        "mbarrier.test_wait.parity.shared.b64 w, [sn+8704], ph;\n"
        "mma.sync.aligned.m16n8k16.row.col.f32.bf16.bf16.f32 {%128,%129,%130,%131}, {a0,a1,a2,a3}, {x0,x1}, {%128,%129,%130,%131};\n"
        "mma.sync.aligned.m16n8k16.row.col.f32.bf16.bf16.f32 {%132,%133,%134,%135}, {a0,a1,a2,a3}, {x2,x3}, {%132,%133,%134,%135};\n"
        "ld.shared.v4.u32 {x0,x1,x2,x3}, [xa+1024];\n"
        "tanh.approx.f32 t0, p1;\n"
        "tanh.approx.f32 t1, p3;\n"
        "fma.rn.f32 t0, p1, t0, p1;\n"
        "fma.rn.f32 t1, p3, t1, p3;\n"
        "cvt.rn.bf16x2.f32 r0, t1, t0;\n"
        "mma.sync.aligned.m16n8k16.row.col.f32.bf16.bf16.f32 {p0,p1,p2,p3}, {%161,%162,%163,%164}, {m2,m3}, {fz,fz,fz,fz};\n"
        "mma.sync.aligned.m16n8k16.row.col.f32.bf16.bf16.f32 {%136,%137,%138,%139}, {a0,a1,a2,a3}, {x4,x5}, {%136,%137,%138,%139};\n"
        "mma.sync.aligned.m16n8k16.row.col.f32.bf16.bf16.f32 {%140,%141,%142,%143}, {a0,a1,a2,a3}, {x6,x7}, {%140,%141,%142,%143};\n"
        "ld.shared.v4.u32 {x4,x5,x6,x7}, [xa+1152];\n"
        "mma.sync.aligned.m16n8k8.row.col.f32.bf16.bf16.f32 {d0,d1,d2,d3}, {%177,%178}, {m1}, {fz,fz,fz,fz};\n"
        "cvt.rn.bf16x2.f32 b0, d2, d0;\n"
        "cvt.rn.bf16x2.f32 b1, d3, d1;\n"
        "tanh.approx.f32 t0, p5;\n"
        "tanh.approx.f32 t1, p7;\n"
        "fma.rn.f32 t0, p5, t0, p5;\n"
        "fma.rn.f32 t1, p7, t1, p7;\n"
        "cvt.rn.bf16x2.f32 r1, t1, t0;\n"
        "mma.sync.aligned.m16n8k16.row.col.f32.bf16.bf16.f32 {p4,p5,p6,p7}, {%165,%166,%167,%168}, {m2,m3}, {fz,fz,fz,fz};\n"
        "mov.b32 {lo,hi}, r2;\n"
        "mov.b32 rl, {lo,lo};\n"
        "mov.b32 rh, {hi,hi};\n"
        "mul.bf16x2 x8, x8, rl;\n"
        "mul.bf16x2 x9, x9, rl;\n"
        "mul.bf16x2 x10, x10, rh;\n"
        "mul.bf16x2 x11, x11, rh;\n"
        "mma.sync.aligned.m16n8k16.row.col.f32.bf16.bf16.f32 {%144,%145,%146,%147}, {a0,a1,a2,a3}, {x8,x9}, {%144,%145,%146,%147};\n"
        "mma.sync.aligned.m16n8k16.row.col.f32.bf16.bf16.f32 {%148,%149,%150,%151}, {a0,a1,a2,a3}, {x10,x11}, {%148,%149,%150,%151};\n"
        "ld.shared.v4.u32 {x8,x9,x10,x11}, [xa+1280];\n"
        "mma.sync.aligned.m16n8k8.row.col.f32.bf16.bf16.f32 {d0,d1,d2,d3}, {%179,%180}, {m1}, {fz,fz,fz,fz};\n"
        "cvt.rn.bf16x2.f32 b2, d2, d0;\n"
        "cvt.rn.bf16x2.f32 b3, d3, d1;\n"
        "tanh.approx.f32 t0, p9;\n"
        "tanh.approx.f32 t1, p11;\n"
        "fma.rn.f32 t0, p9, t0, p9;\n"
        "fma.rn.f32 t1, p11, t1, p11;\n"
        "cvt.rn.bf16x2.f32 r2, t1, t0;\n"
        "mma.sync.aligned.m16n8k16.row.col.f32.bf16.bf16.f32 {p8,p9,p10,p11}, {%169,%170,%171,%172}, {m2,m3}, {fz,fz,fz,fz};\n"
        "selp.u32 tq, lb, 5, w;\n"
        "mov.b32 {lo,hi}, r3;\n"
        "mov.b32 rl, {lo,lo};\n"
        "mov.b32 rh, {hi,hi};\n"
        "mul.bf16x2 x12, x12, rl;\n"
        "mul.bf16x2 x13, x13, rl;\n"
        "mul.bf16x2 x14, x14, rh;\n"
        "mul.bf16x2 x15, x15, rh;\n"
        "mma.sync.aligned.m16n8k16.row.col.f32.bf16.bf16.f32 {%152,%153,%154,%155}, {a0,a1,a2,a3}, {x12,x13}, {%152,%153,%154,%155};\n"
        "mma.sync.aligned.m16n8k16.row.col.f32.bf16.bf16.f32 {%156,%157,%158,%159}, {a0,a1,a2,a3}, {x14,x15}, {%156,%157,%158,%159};\n"
        "ld.shared.v4.u32 {x12,x13,x14,x15}, [xa+1408];\n"
        "elect.sync _|el, 0xffffffff;\n"
        "@el mbarrier.arrive.shared.b64 _, [k1+8712];\n"
        "redux.sync.or.b32 ln, tag, 0xffffffff;\n"
        "mov.u32 sa, sn;\n"
        "add.u32 k0, sn, zz;\n"
        "or.b32 k1, sn, zz;\n"
        "tanh.approx.f32 t0, p13;\n"
        "tanh.approx.f32 t1, p15;\n"
        "fma.rn.f32 t0, p13, t0, p13;\n"
        "fma.rn.f32 t1, p15, t1, p15;\n"
        "cvt.rn.bf16x2.f32 r3, t1, t0;\n"
        "mma.sync.aligned.m16n8k16.row.col.f32.bf16.bf16.f32 {p12,p13,p14,p15}, {%173,%174,%175,%176}, {m2,m3}, {fz,fz,fz,fz};\n"
        "mov.b32 {lo,hi}, r0;\n"
        "mov.b32 rl, {lo,lo};\n"
        "mov.b32 rh, {hi,hi};\n"
        "mul.bf16x2 x0, x0, rl;\n"
        "mul.bf16x2 x1, x1, rl;\n"
        "mul.bf16x2 x2, x2, rh;\n"
        "mul.bf16x2 x3, x3, rh;\n"
        "mov.b32 {lo,hi}, r1;\n"
        "mov.b32 rl, {lo,lo};\n"
        "mov.b32 rh, {hi,hi};\n"
        "mul.bf16x2 x4, x4, rl;\n"
        "mul.bf16x2 x5, x5, rl;\n"
        "mul.bf16x2 x6, x6, rh;\n"
        "mul.bf16x2 x7, x7, rh;\n"
        "brx.idx.uni tq, TB_%=;\n"
        "B0_%=:\n"
        "and.b32 la, ln, 255;\n"
        "shr.u32 lb, ln, 8;\n"
        "add.u32 ma, sa, %182;\n"
        "ldmatrix.sync.aligned.m8n8.x1.shared.b16 {yb}, [ma];\n"
        "add.u32 xa, sa, %181;\n"
        "mma.sync.aligned.m16n8k16.row.col.f32.bf16.bf16.f32 {%0,%1,%2,%3}, {b0,b1,b2,b3}, {x0,x1}, {%0,%1,%2,%3};\n"
        "mma.sync.aligned.m16n8k16.row.col.f32.bf16.bf16.f32 {%4,%5,%6,%7}, {b0,b1,b2,b3}, {x2,x3}, {%4,%5,%6,%7};\n"
        "ld.shared.v4.u32 {x0,x1,x2,x3}, [xa+0];\n"
        "tanh.approx.f32 t0, p0;\n"
        "tanh.approx.f32 t1, p2;\n"
        "fma.rn.f32 t0, p0, t0, p0;\n"
        "fma.rn.f32 t1, p2, t1, p2;\n"
        "cvt.rn.bf16x2.f32 r0, t1, t0;\n"
        "mma.sync.aligned.m16n8k16.row.col.f32.bf16.bf16.f32 {%8,%9,%10,%11}, {b0,b1,b2,b3}, {x4,x5}, {%8,%9,%10,%11};\n"
        "mma.sync.aligned.m16n8k16.row.col.f32.bf16.bf16.f32 {%12,%13,%14,%15}, {b0,b1,b2,b3}, {x6,x7}, {%12,%13,%14,%15};\n"
        "ld.shared.v4.u32 {x4,x5,x6,x7}, [xa+128];\n"
        "tanh.approx.f32 t0, p4;\n"
        "tanh.approx.f32 t1, p6;\n"
        "fma.rn.f32 t0, p4, t0, p4;\n"
        "fma.rn.f32 t1, p6, t1, p6;\n"
        "cvt.rn.bf16x2.f32 r1, t1, t0;\n"
        "mma.sync.aligned.m16n8k8.row.col.f32.bf16.bf16.f32 {d0,d1,d2,d3}, {%177,%178}, {yb}, {fz,fz,fz,fz};\n"
        "cvt.rn.bf16x2.f32 a0, d2, d0;\n"
        "cvt.rn.bf16x2.f32 a1, d3, d1;\n"
        "mov.b32 {lo,hi}, r2;\n"
        "mov.b32 rl, {lo,lo};\n"
        "mov.b32 rh, {hi,hi};\n"
        "mul.bf16x2 x8, x8, rl;\n"
        "mul.bf16x2 x9, x9, rl;\n"
        "mul.bf16x2 x10, x10, rh;\n"
        "mul.bf16x2 x11, x11, rh;\n"
        "mma.sync.aligned.m16n8k16.row.col.f32.bf16.bf16.f32 {%16,%17,%18,%19}, {b0,b1,b2,b3}, {x8,x9}, {%16,%17,%18,%19};\n"
        "mma.sync.aligned.m16n8k16.row.col.f32.bf16.bf16.f32 {%20,%21,%22,%23}, {b0,b1,b2,b3}, {x10,x11}, {%20,%21,%22,%23};\n"
        "ld.shared.v4.u32 {x8,x9,x10,x11}, [xa+256];\n"
        "tanh.approx.f32 t0, p8;\n"
        "tanh.approx.f32 t1, p10;\n"
        "fma.rn.f32 t0, p8, t0, p8;\n"
        "fma.rn.f32 t1, p10, t1, p10;\n"
        "cvt.rn.bf16x2.f32 r2, t1, t0;\n"
        "mma.sync.aligned.m16n8k8.row.col.f32.bf16.bf16.f32 {d0,d1,d2,d3}, {%179,%180}, {yb}, {fz,fz,fz,fz};\n"
        "cvt.rn.bf16x2.f32 a2, d2, d0;\n"
        "cvt.rn.bf16x2.f32 a3, d3, d1;\n"
        "mov.b32 {lo,hi}, r3;\n"
        "mov.b32 rl, {lo,lo};\n"
        "mov.b32 rh, {hi,hi};\n"
        "mul.bf16x2 x12, x12, rl;\n"
        "mul.bf16x2 x13, x13, rl;\n"
        "mul.bf16x2 x14, x14, rh;\n"
        "mul.bf16x2 x15, x15, rh;\n"
        "mma.sync.aligned.m16n8k16.row.col.f32.bf16.bf16.f32 {%24,%25,%26,%27}, {b0,b1,b2,b3}, {x12,x13}, {%24,%25,%26,%27};\n"
        "mma.sync.aligned.m16n8k16.row.col.f32.bf16.bf16.f32 {%28,%29,%30,%31}, {b0,b1,b2,b3}, {x14,x15}, {%28,%29,%30,%31};\n"
        "ld.shared.v4.u32 {x12,x13,x14,x15}, [xa+384];\n"
        "tanh.approx.f32 t0, p12;\n"
        "tanh.approx.f32 t1, p14;\n"
        "fma.rn.f32 t0, p12, t0, p12;\n"
        "fma.rn.f32 t1, p14, t1, p14;\n"
        "cvt.rn.bf16x2.f32 r3, t1, t0;\n"
        "mov.b32 {lo,hi}, r0;\n"
        "mov.b32 rl, {lo,lo};\n"
        "mov.b32 rh, {hi,hi};\n"
        "mul.bf16x2 x0, x0, rl;\n"
        "mul.bf16x2 x1, x1, rl;\n"
        "mul.bf16x2 x2, x2, rh;\n"
        "mul.bf16x2 x3, x3, rh;\n"
        "mov.b32 {lo,hi}, r1;\n"
        "mov.b32 rl, {lo,lo};\n"
        "mov.b32 rh, {hi,hi};\n"
        "mul.bf16x2 x4, x4, rl;\n"
        "mul.bf16x2 x5, x5, rl;\n"
        "mul.bf16x2 x6, x6, rh;\n"
        "mul.bf16x2 x7, x7, rh;\n"
        "brx.idx.uni la, TA_%=;\n"
        "B1_%=:\n"
        "and.b32 la, ln, 255;\n"
        "shr.u32 lb, ln, 8;\n"
        "add.u32 ma, sa, %182;\n"
        "ldmatrix.sync.aligned.m8n8.x1.shared.b16 {yb}, [ma];\n"
        "add.u32 xa, sa, %181;\n"
        "mma.sync.aligned.m16n8k16.row.col.f32.bf16.bf16.f32 {%32,%33,%34,%35}, {b0,b1,b2,b3}, {x0,x1}, {%32,%33,%34,%35};\n"
        "mma.sync.aligned.m16n8k16.row.col.f32.bf16.bf16.f32 {%36,%37,%38,%39}, {b0,b1,b2,b3}, {x2,x3}, {%36,%37,%38,%39};\n"
        "ld.shared.v4.u32 {x0,x1,x2,x3}, [xa+0];\n"
        "tanh.approx.f32 t0, p0;\n"
        "tanh.approx.f32 t1, p2;\n"
        "fma.rn.f32 t0, p0, t0, p0;\n"
        "fma.rn.f32 t1, p2, t1, p2;\n"
        "cvt.rn.bf16x2.f32 r0, t1, t0;\n"
        "mma.sync.aligned.m16n8k16.row.col.f32.bf16.bf16.f32 {%40,%41,%42,%43}, {b0,b1,b2,b3}, {x4,x5}, {%40,%41,%42,%43};\n"
        "mma.sync.aligned.m16n8k16.row.col.f32.bf16.bf16.f32 {%44,%45,%46,%47}, {b0,b1,b2,b3}, {x6,x7}, {%44,%45,%46,%47};\n"
        "ld.shared.v4.u32 {x4,x5,x6,x7}, [xa+128];\n"
        "tanh.approx.f32 t0, p4;\n"
        "tanh.approx.f32 t1, p6;\n"
        "fma.rn.f32 t0, p4, t0, p4;\n"
        "fma.rn.f32 t1, p6, t1, p6;\n"
        "cvt.rn.bf16x2.f32 r1, t1, t0;\n"
        "mma.sync.aligned.m16n8k8.row.col.f32.bf16.bf16.f32 {d0,d1,d2,d3}, {%177,%178}, {yb}, {fz,fz,fz,fz};\n"
        "cvt.rn.bf16x2.f32 a0, d2, d0;\n"
        "cvt.rn.bf16x2.f32 a1, d3, d1;\n"
        "mov.b32 {lo,hi}, r2;\n"
        "mov.b32 rl, {lo,lo};\n"
        "mov.b32 rh, {hi,hi};\n"
        "mul.bf16x2 x8, x8, rl;\n"
        "mul.bf16x2 x9, x9, rl;\n"
        "mul.bf16x2 x10, x10, rh;\n"
        "mul.bf16x2 x11, x11, rh;\n"
        "mma.sync.aligned.m16n8k16.row.col.f32.bf16.bf16.f32 {%48,%49,%50,%51}, {b0,b1,b2,b3}, {x8,x9}, {%48,%49,%50,%51};\n"
        "mma.sync.aligned.m16n8k16.row.col.f32.bf16.bf16.f32 {%52,%53,%54,%55}, {b0,b1,b2,b3}, {x10,x11}, {%52,%53,%54,%55};\n"
        "ld.shared.v4.u32 {x8,x9,x10,x11}, [xa+256];\n"
        "tanh.approx.f32 t0, p8;\n"
        "tanh.approx.f32 t1, p10;\n"
        "fma.rn.f32 t0, p8, t0, p8;\n"
        "fma.rn.f32 t1, p10, t1, p10;\n"
        "cvt.rn.bf16x2.f32 r2, t1, t0;\n"
        "mma.sync.aligned.m16n8k8.row.col.f32.bf16.bf16.f32 {d0,d1,d2,d3}, {%179,%180}, {yb}, {fz,fz,fz,fz};\n"
        "cvt.rn.bf16x2.f32 a2, d2, d0;\n"
        "cvt.rn.bf16x2.f32 a3, d3, d1;\n"
        "mov.b32 {lo,hi}, r3;\n"
        "mov.b32 rl, {lo,lo};\n"
        "mov.b32 rh, {hi,hi};\n"
        "mul.bf16x2 x12, x12, rl;\n"
        "mul.bf16x2 x13, x13, rl;\n"
        "mul.bf16x2 x14, x14, rh;\n"
        "mul.bf16x2 x15, x15, rh;\n"
        "mma.sync.aligned.m16n8k16.row.col.f32.bf16.bf16.f32 {%56,%57,%58,%59}, {b0,b1,b2,b3}, {x12,x13}, {%56,%57,%58,%59};\n"
        "mma.sync.aligned.m16n8k16.row.col.f32.bf16.bf16.f32 {%60,%61,%62,%63}, {b0,b1,b2,b3}, {x14,x15}, {%60,%61,%62,%63};\n"
        "ld.shared.v4.u32 {x12,x13,x14,x15}, [xa+384];\n"
        "tanh.approx.f32 t0, p12;\n"
        "tanh.approx.f32 t1, p14;\n"
        "fma.rn.f32 t0, p12, t0, p12;\n"
        "fma.rn.f32 t1, p14, t1, p14;\n"
        "cvt.rn.bf16x2.f32 r3, t1, t0;\n"
        "mov.b32 {lo,hi}, r0;\n"
        "mov.b32 rl, {lo,lo};\n"
        "mov.b32 rh, {hi,hi};\n"
        "mul.bf16x2 x0, x0, rl;\n"
        "mul.bf16x2 x1, x1, rl;\n"
        "mul.bf16x2 x2, x2, rh;\n"
        "mul.bf16x2 x3, x3, rh;\n"
        "mov.b32 {lo,hi}, r1;\n"
        "mov.b32 rl, {lo,lo};\n"
        "mov.b32 rh, {hi,hi};\n"
        "mul.bf16x2 x4, x4, rl;\n"
        "mul.bf16x2 x5, x5, rl;\n"
        "mul.bf16x2 x6, x6, rh;\n"
        "mul.bf16x2 x7, x7, rh;\n"
        "brx.idx.uni la, TA_%=;\n"
        "B2_%=:\n"
        "and.b32 la, ln, 255;\n"
        "shr.u32 lb, ln, 8;\n"
        "add.u32 ma, sa, %182;\n"
        "ldmatrix.sync.aligned.m8n8.x1.shared.b16 {yb}, [ma];\n"
        "add.u32 xa, sa, %181;\n"
        "mma.sync.aligned.m16n8k16.row.col.f32.bf16.bf16.f32 {%64,%65,%66,%67}, {b0,b1,b2,b3}, {x0,x1}, {%64,%65,%66,%67};\n"
        "mma.sync.aligned.m16n8k16.row.col.f32.bf16.bf16.f32 {%68,%69,%70,%71}, {b0,b1,b2,b3}, {x2,x3}, {%68,%69,%70,%71};\n"
        "ld.shared.v4.u32 {x0,x1,x2,x3}, [xa+0];\n"
        "tanh.approx.f32 t0, p0;\n"
        "tanh.approx.f32 t1, p2;\n"
        "fma.rn.f32 t0, p0, t0, p0;\n"
        "fma.rn.f32 t1, p2, t1, p2;\n"
        "cvt.rn.bf16x2.f32 r0, t1, t0;\n"
        "mma.sync.aligned.m16n8k16.row.col.f32.bf16.bf16.f32 {%72,%73,%74,%75}, {b0,b1,b2,b3}, {x4,x5}, {%72,%73,%74,%75};\n"
        "mma.sync.aligned.m16n8k16.row.col.f32.bf16.bf16.f32 {%76,%77,%78,%79}, {b0,b1,b2,b3}, {x6,x7}, {%76,%77,%78,%79};\n"
        "ld.shared.v4.u32 {x4,x5,x6,x7}, [xa+128];\n"
        "tanh.approx.f32 t0, p4;\n"
        "tanh.approx.f32 t1, p6;\n"
        "fma.rn.f32 t0, p4, t0, p4;\n"
        "fma.rn.f32 t1, p6, t1, p6;\n"
        "cvt.rn.bf16x2.f32 r1, t1, t0;\n"
        "mma.sync.aligned.m16n8k8.row.col.f32.bf16.bf16.f32 {d0,d1,d2,d3}, {%177,%178}, {yb}, {fz,fz,fz,fz};\n"
        "cvt.rn.bf16x2.f32 a0, d2, d0;\n"
        "cvt.rn.bf16x2.f32 a1, d3, d1;\n"
        "mov.b32 {lo,hi}, r2;\n"
        "mov.b32 rl, {lo,lo};\n"
        "mov.b32 rh, {hi,hi};\n"
        "mul.bf16x2 x8, x8, rl;\n"
        "mul.bf16x2 x9, x9, rl;\n"
        "mul.bf16x2 x10, x10, rh;\n"
        "mul.bf16x2 x11, x11, rh;\n"
        "mma.sync.aligned.m16n8k16.row.col.f32.bf16.bf16.f32 {%80,%81,%82,%83}, {b0,b1,b2,b3}, {x8,x9}, {%80,%81,%82,%83};\n"
        "mma.sync.aligned.m16n8k16.row.col.f32.bf16.bf16.f32 {%84,%85,%86,%87}, {b0,b1,b2,b3}, {x10,x11}, {%84,%85,%86,%87};\n"
        "ld.shared.v4.u32 {x8,x9,x10,x11}, [xa+256];\n"
        "tanh.approx.f32 t0, p8;\n"
        "tanh.approx.f32 t1, p10;\n"
        "fma.rn.f32 t0, p8, t0, p8;\n"
        "fma.rn.f32 t1, p10, t1, p10;\n"
        "cvt.rn.bf16x2.f32 r2, t1, t0;\n"
        "mma.sync.aligned.m16n8k8.row.col.f32.bf16.bf16.f32 {d0,d1,d2,d3}, {%179,%180}, {yb}, {fz,fz,fz,fz};\n"
        "cvt.rn.bf16x2.f32 a2, d2, d0;\n"
        "cvt.rn.bf16x2.f32 a3, d3, d1;\n"
        "mov.b32 {lo,hi}, r3;\n"
        "mov.b32 rl, {lo,lo};\n"
        "mov.b32 rh, {hi,hi};\n"
        "mul.bf16x2 x12, x12, rl;\n"
        "mul.bf16x2 x13, x13, rl;\n"
        "mul.bf16x2 x14, x14, rh;\n"
        "mul.bf16x2 x15, x15, rh;\n"
        "mma.sync.aligned.m16n8k16.row.col.f32.bf16.bf16.f32 {%88,%89,%90,%91}, {b0,b1,b2,b3}, {x12,x13}, {%88,%89,%90,%91};\n"
        "mma.sync.aligned.m16n8k16.row.col.f32.bf16.bf16.f32 {%92,%93,%94,%95}, {b0,b1,b2,b3}, {x14,x15}, {%92,%93,%94,%95};\n"
        "ld.shared.v4.u32 {x12,x13,x14,x15}, [xa+384];\n"
        "tanh.approx.f32 t0, p12;\n"
        "tanh.approx.f32 t1, p14;\n"
        "fma.rn.f32 t0, p12, t0, p12;\n"
        "fma.rn.f32 t1, p14, t1, p14;\n"
        "cvt.rn.bf16x2.f32 r3, t1, t0;\n"
        "mov.b32 {lo,hi}, r0;\n"
        "mov.b32 rl, {lo,lo};\n"
        "mov.b32 rh, {hi,hi};\n"
        "mul.bf16x2 x0, x0, rl;\n"
        "mul.bf16x2 x1, x1, rl;\n"
        "mul.bf16x2 x2, x2, rh;\n"
        "mul.bf16x2 x3, x3, rh;\n"
        "mov.b32 {lo,hi}, r1;\n"
        "mov.b32 rl, {lo,lo};\n"
        "mov.b32 rh, {hi,hi};\n"
        "mul.bf16x2 x4, x4, rl;\n"
        "mul.bf16x2 x5, x5, rl;\n"
        "mul.bf16x2 x6, x6, rh;\n"
        "mul.bf16x2 x7, x7, rh;\n"
        "brx.idx.uni la, TA_%=;\n"
        "B3_%=:\n"
        "and.b32 la, ln, 255;\n"
        "shr.u32 lb, ln, 8;\n"
        "add.u32 ma, sa, %182;\n"
        "ldmatrix.sync.aligned.m8n8.x1.shared.b16 {yb}, [ma];\n"
        "add.u32 xa, sa, %181;\n"
        "mma.sync.aligned.m16n8k16.row.col.f32.bf16.bf16.f32 {%96,%97,%98,%99}, {b0,b1,b2,b3}, {x0,x1}, {%96,%97,%98,%99};\n"
        "mma.sync.aligned.m16n8k16.row.col.f32.bf16.bf16.f32 {%100,%101,%102,%103}, {b0,b1,b2,b3}, {x2,x3}, {%100,%101,%102,%103};\n"
        "ld.shared.v4.u32 {x0,x1,x2,x3}, [xa+0];\n"
        "tanh.approx.f32 t0, p0;\n"
        "tanh.approx.f32 t1, p2;\n"
        "fma.rn.f32 t0, p0, t0, p0;\n"
        "fma.rn.f32 t1, p2, t1, p2;\n"
        "cvt.rn.bf16x2.f32 r0, t1, t0;\n"
        "mma.sync.aligned.m16n8k16.row.col.f32.bf16.bf16.f32 {%104,%105,%106,%107}, {b0,b1,b2,b3}, {x4,x5}, {%104,%105,%106,%107};\n"
        "mma.sync.aligned.m16n8k16.row.col.f32.bf16.bf16.f32 {%108,%109,%110,%111}, {b0,b1,b2,b3}, {x6,x7}, {%108,%109,%110,%111};\n"
        "ld.shared.v4.u32 {x4,x5,x6,x7}, [xa+128];\n"
        "tanh.approx.f32 t0, p4;\n"
        "tanh.approx.f32 t1, p6;\n"
        "fma.rn.f32 t0, p4, t0, p4;\n"
        "fma.rn.f32 t1, p6, t1, p6;\n"
        "cvt.rn.bf16x2.f32 r1, t1, t0;\n"
        "mma.sync.aligned.m16n8k8.row.col.f32.bf16.bf16.f32 {d0,d1,d2,d3}, {%177,%178}, {yb}, {fz,fz,fz,fz};\n"
        "cvt.rn.bf16x2.f32 a0, d2, d0;\n"
        "cvt.rn.bf16x2.f32 a1, d3, d1;\n"
        "mov.b32 {lo,hi}, r2;\n"
        "mov.b32 rl, {lo,lo};\n"
        "mov.b32 rh, {hi,hi};\n"
        "mul.bf16x2 x8, x8, rl;\n"
        "mul.bf16x2 x9, x9, rl;\n"
        "mul.bf16x2 x10, x10, rh;\n"
        "mul.bf16x2 x11, x11, rh;\n"
        "mma.sync.aligned.m16n8k16.row.col.f32.bf16.bf16.f32 {%112,%113,%114,%115}, {b0,b1,b2,b3}, {x8,x9}, {%112,%113,%114,%115};\n"
        "mma.sync.aligned.m16n8k16.row.col.f32.bf16.bf16.f32 {%116,%117,%118,%119}, {b0,b1,b2,b3}, {x10,x11}, {%116,%117,%118,%119};\n"
        "ld.shared.v4.u32 {x8,x9,x10,x11}, [xa+256];\n"
        "tanh.approx.f32 t0, p8;\n"
        "tanh.approx.f32 t1, p10;\n"
        "fma.rn.f32 t0, p8, t0, p8;\n"
        "fma.rn.f32 t1, p10, t1, p10;\n"
        "cvt.rn.bf16x2.f32 r2, t1, t0;\n"
        "mma.sync.aligned.m16n8k8.row.col.f32.bf16.bf16.f32 {d0,d1,d2,d3}, {%179,%180}, {yb}, {fz,fz,fz,fz};\n"
        "cvt.rn.bf16x2.f32 a2, d2, d0;\n"
        "cvt.rn.bf16x2.f32 a3, d3, d1;\n"
        "mov.b32 {lo,hi}, r3;\n"
        "mov.b32 rl, {lo,lo};\n"
        "mov.b32 rh, {hi,hi};\n"
        "mul.bf16x2 x12, x12, rl;\n"
        "mul.bf16x2 x13, x13, rl;\n"
        "mul.bf16x2 x14, x14, rh;\n"
        "mul.bf16x2 x15, x15, rh;\n"
        "mma.sync.aligned.m16n8k16.row.col.f32.bf16.bf16.f32 {%120,%121,%122,%123}, {b0,b1,b2,b3}, {x12,x13}, {%120,%121,%122,%123};\n"
        "mma.sync.aligned.m16n8k16.row.col.f32.bf16.bf16.f32 {%124,%125,%126,%127}, {b0,b1,b2,b3}, {x14,x15}, {%124,%125,%126,%127};\n"
        "ld.shared.v4.u32 {x12,x13,x14,x15}, [xa+384];\n"
        "tanh.approx.f32 t0, p12;\n"
        "tanh.approx.f32 t1, p14;\n"
        "fma.rn.f32 t0, p12, t0, p12;\n"
        "fma.rn.f32 t1, p14, t1, p14;\n"
        "cvt.rn.bf16x2.f32 r3, t1, t0;\n"
        "mov.b32 {lo,hi}, r0;\n"
        "mov.b32 rl, {lo,lo};\n"
        "mov.b32 rh, {hi,hi};\n"
        "mul.bf16x2 x0, x0, rl;\n"
        "mul.bf16x2 x1, x1, rl;\n"
        "mul.bf16x2 x2, x2, rh;\n"
        "mul.bf16x2 x3, x3, rh;\n"
        "mov.b32 {lo,hi}, r1;\n"
        "mov.b32 rl, {lo,lo};\n"
        "mov.b32 rh, {hi,hi};\n"
        "mul.bf16x2 x4, x4, rl;\n"
        "mul.bf16x2 x5, x5, rl;\n"
        "mul.bf16x2 x6, x6, rh;\n"
        "mul.bf16x2 x7, x7, rh;\n"
        "brx.idx.uni la, TA_%=;\n"
        "B4_%=:\n"
        "and.b32 la, ln, 255;\n"
        "shr.u32 lb, ln, 8;\n"
        "add.u32 ma, sa, %182;\n"
        "ldmatrix.sync.aligned.m8n8.x1.shared.b16 {yb}, [ma];\n"
        "add.u32 xa, sa, %181;\n"
        "mma.sync.aligned.m16n8k16.row.col.f32.bf16.bf16.f32 {%128,%129,%130,%131}, {b0,b1,b2,b3}, {x0,x1}, {%128,%129,%130,%131};\n"
        "mma.sync.aligned.m16n8k16.row.col.f32.bf16.bf16.f32 {%132,%133,%134,%135}, {b0,b1,b2,b3}, {x2,x3}, {%132,%133,%134,%135};\n"
        "ld.shared.v4.u32 {x0,x1,x2,x3}, [xa+0];\n"
        "tanh.approx.f32 t0, p0;\n"
        "tanh.approx.f32 t1, p2;\n"
        "fma.rn.f32 t0, p0, t0, p0;\n"
        "fma.rn.f32 t1, p2, t1, p2;\n"
        "cvt.rn.bf16x2.f32 r0, t1, t0;\n"
        "mma.sync.aligned.m16n8k16.row.col.f32.bf16.bf16.f32 {%136,%137,%138,%139}, {b0,b1,b2,b3}, {x4,x5}, {%136,%137,%138,%139};\n"
        "mma.sync.aligned.m16n8k16.row.col.f32.bf16.bf16.f32 {%140,%141,%142,%143}, {b0,b1,b2,b3}, {x6,x7}, {%140,%141,%142,%143};\n"
        "ld.shared.v4.u32 {x4,x5,x6,x7}, [xa+128];\n"
        "tanh.approx.f32 t0, p4;\n"
        "tanh.approx.f32 t1, p6;\n"
        "fma.rn.f32 t0, p4, t0, p4;\n"
        "fma.rn.f32 t1, p6, t1, p6;\n"
        "cvt.rn.bf16x2.f32 r1, t1, t0;\n"
        "mma.sync.aligned.m16n8k8.row.col.f32.bf16.bf16.f32 {d0,d1,d2,d3}, {%177,%178}, {yb}, {fz,fz,fz,fz};\n"
        "cvt.rn.bf16x2.f32 a0, d2, d0;\n"
        "cvt.rn.bf16x2.f32 a1, d3, d1;\n"
        "mov.b32 {lo,hi}, r2;\n"
        "mov.b32 rl, {lo,lo};\n"
        "mov.b32 rh, {hi,hi};\n"
        "mul.bf16x2 x8, x8, rl;\n"
        "mul.bf16x2 x9, x9, rl;\n"
        "mul.bf16x2 x10, x10, rh;\n"
        "mul.bf16x2 x11, x11, rh;\n"
        "mma.sync.aligned.m16n8k16.row.col.f32.bf16.bf16.f32 {%144,%145,%146,%147}, {b0,b1,b2,b3}, {x8,x9}, {%144,%145,%146,%147};\n"
        "mma.sync.aligned.m16n8k16.row.col.f32.bf16.bf16.f32 {%148,%149,%150,%151}, {b0,b1,b2,b3}, {x10,x11}, {%148,%149,%150,%151};\n"
        "ld.shared.v4.u32 {x8,x9,x10,x11}, [xa+256];\n"
        "tanh.approx.f32 t0, p8;\n"
        "tanh.approx.f32 t1, p10;\n"
        "fma.rn.f32 t0, p8, t0, p8;\n"
        "fma.rn.f32 t1, p10, t1, p10;\n"
        "cvt.rn.bf16x2.f32 r2, t1, t0;\n"
        "mma.sync.aligned.m16n8k8.row.col.f32.bf16.bf16.f32 {d0,d1,d2,d3}, {%179,%180}, {yb}, {fz,fz,fz,fz};\n"
        "cvt.rn.bf16x2.f32 a2, d2, d0;\n"
        "cvt.rn.bf16x2.f32 a3, d3, d1;\n"
        "mov.b32 {lo,hi}, r3;\n"
        "mov.b32 rl, {lo,lo};\n"
        "mov.b32 rh, {hi,hi};\n"
        "mul.bf16x2 x12, x12, rl;\n"
        "mul.bf16x2 x13, x13, rl;\n"
        "mul.bf16x2 x14, x14, rh;\n"
        "mul.bf16x2 x15, x15, rh;\n"
        "mma.sync.aligned.m16n8k16.row.col.f32.bf16.bf16.f32 {%152,%153,%154,%155}, {b0,b1,b2,b3}, {x12,x13}, {%152,%153,%154,%155};\n"
        "mma.sync.aligned.m16n8k16.row.col.f32.bf16.bf16.f32 {%156,%157,%158,%159}, {b0,b1,b2,b3}, {x14,x15}, {%156,%157,%158,%159};\n"
        "ld.shared.v4.u32 {x12,x13,x14,x15}, [xa+384];\n"
        "tanh.approx.f32 t0, p12;\n"
        "tanh.approx.f32 t1, p14;\n"
        "fma.rn.f32 t0, p12, t0, p12;\n"
        "fma.rn.f32 t1, p14, t1, p14;\n"
        "cvt.rn.bf16x2.f32 r3, t1, t0;\n"
        "mov.b32 {lo,hi}, r0;\n"
        "mov.b32 rl, {lo,lo};\n"
        "mov.b32 rh, {hi,hi};\n"
        "mul.bf16x2 x0, x0, rl;\n"
        "mul.bf16x2 x1, x1, rl;\n"
        "mul.bf16x2 x2, x2, rh;\n"
        "mul.bf16x2 x3, x3, rh;\n"
        "mov.b32 {lo,hi}, r1;\n"
        "mov.b32 rl, {lo,lo};\n"
        "mov.b32 rh, {hi,hi};\n"
        "mul.bf16x2 x4, x4, rl;\n"
        "mul.bf16x2 x5, x5, rl;\n"
        "mul.bf16x2 x6, x6, rh;\n"
        "mul.bf16x2 x7, x7, rh;\n"
        "brx.idx.uni la, TA_%=;\n"
        "EXIT_%=:\n"
        "mov.u32 %160, ring;\n"
        "}\n"
        : "+f"(acc[0][0][0][0]), "+f"(acc[0][0][0][1]), "+f"(acc[0][0][0][2]), "+f"(acc[0][0][0][3]), "+f"(acc[0][0][1][0]),
          "+f"(acc[0][0][1][1]), "+f"(acc[0][0][1][2]), "+f"(acc[0][0][1][3]), "+f"(acc[0][1][0][0]), "+f"(acc[0][1][0][1]),
          "+f"(acc[0][1][0][2]), "+f"(acc[0][1][0][3]), "+f"(acc[0][1][1][0]), "+f"(acc[0][1][1][1]), "+f"(acc[0][1][1][2]),
          "+f"(acc[0][1][1][3]), "+f"(acc[0][2][0][0]), "+f"(acc[0][2][0][1]), "+f"(acc[0][2][0][2]), "+f"(acc[0][2][0][3]),
          "+f"(acc[0][2][1][0]), "+f"(acc[0][2][1][1]), "+f"(acc[0][2][1][2]), "+f"(acc[0][2][1][3]), "+f"(acc[0][3][0][0]),
          "+f"(acc[0][3][0][1]), "+f"(acc[0][3][0][2]), "+f"(acc[0][3][0][3]), "+f"(acc[0][3][1][0]), "+f"(acc[0][3][1][1]),
          "+f"(acc[0][3][1][2]), "+f"(acc[0][3][1][3]), "+f"(acc[1][0][0][0]), "+f"(acc[1][0][0][1]), "+f"(acc[1][0][0][2]),
          "+f"(acc[1][0][0][3]), "+f"(acc[1][0][1][0]), "+f"(acc[1][0][1][1]), "+f"(acc[1][0][1][2]), "+f"(acc[1][0][1][3]),
          "+f"(acc[1][1][0][0]), "+f"(acc[1][1][0][1]), "+f"(acc[1][1][0][2]), "+f"(acc[1][1][0][3]), "+f"(acc[1][1][1][0]),
          "+f"(acc[1][1][1][1]), "+f"(acc[1][1][1][2]), "+f"(acc[1][1][1][3]), "+f"(acc[1][2][0][0]), "+f"(acc[1][2][0][1]),
          "+f"(acc[1][2][0][2]), "+f"(acc[1][2][0][3]), "+f"(acc[1][2][1][0]), "+f"(acc[1][2][1][1]), "+f"(acc[1][2][1][2]),
          "+f"(acc[1][2][1][3]), "+f"(acc[1][3][0][0]), "+f"(acc[1][3][0][1]), "+f"(acc[1][3][0][2]), "+f"(acc[1][3][0][3]),
          "+f"(acc[1][3][1][0]), "+f"(acc[1][3][1][1]), "+f"(acc[1][3][1][2]), "+f"(acc[1][3][1][3]), "+f"(acc[2][0][0][0]),
          "+f"(acc[2][0][0][1]), "+f"(acc[2][0][0][2]), "+f"(acc[2][0][0][3]), "+f"(acc[2][0][1][0]), "+f"(acc[2][0][1][1]),
          "+f"(acc[2][0][1][2]), "+f"(acc[2][0][1][3]), "+f"(acc[2][1][0][0]), "+f"(acc[2][1][0][1]), "+f"(acc[2][1][0][2]),
          "+f"(acc[2][1][0][3]), "+f"(acc[2][1][1][0]), "+f"(acc[2][1][1][1]), "+f"(acc[2][1][1][2]), "+f"(acc[2][1][1][3]),
          "+f"(acc[2][2][0][0]), "+f"(acc[2][2][0][1]), "+f"(acc[2][2][0][2]), "+f"(acc[2][2][0][3]), "+f"(acc[2][2][1][0]),
          "+f"(acc[2][2][1][1]), "+f"(acc[2][2][1][2]), "+f"(acc[2][2][1][3]), "+f"(acc[2][3][0][0]), "+f"(acc[2][3][0][1]),
          "+f"(acc[2][3][0][2]), "+f"(acc[2][3][0][3]), "+f"(acc[2][3][1][0]), "+f"(acc[2][3][1][1]), "+f"(acc[2][3][1][2]),
          "+f"(acc[2][3][1][3]), "+f"(acc[3][0][0][0]), "+f"(acc[3][0][0][1]), "+f"(acc[3][0][0][2]), "+f"(acc[3][0][0][3]),
          "+f"(acc[3][0][1][0]), "+f"(acc[3][0][1][1]), "+f"(acc[3][0][1][2]), "+f"(acc[3][0][1][3]), "+f"(acc[3][1][0][0]),
          "+f"(acc[3][1][0][1]), "+f"(acc[3][1][0][2]), "+f"(acc[3][1][0][3]), "+f"(acc[3][1][1][0]), "+f"(acc[3][1][1][1]),
          "+f"(acc[3][1][1][2]), "+f"(acc[3][1][1][3]), "+f"(acc[3][2][0][0]), "+f"(acc[3][2][0][1]), "+f"(acc[3][2][0][2]),
          "+f"(acc[3][2][0][3]), "+f"(acc[3][2][1][0]), "+f"(acc[3][2][1][1]), "+f"(acc[3][2][1][2]), "+f"(acc[3][2][1][3]),
          "+f"(acc[3][3][0][0]), "+f"(acc[3][3][0][1]), "+f"(acc[3][3][0][2]), "+f"(acc[3][3][0][3]), "+f"(acc[3][3][1][0]),
          "+f"(acc[3][3][1][1]), "+f"(acc[3][3][1][2]), "+f"(acc[3][3][1][3]), "+f"(acc[4][0][0][0]), "+f"(acc[4][0][0][1]),
          "+f"(acc[4][0][0][2]), "+f"(acc[4][0][0][3]), "+f"(acc[4][0][1][0]), "+f"(acc[4][0][1][1]), "+f"(acc[4][0][1][2]),
          "+f"(acc[4][0][1][3]), "+f"(acc[4][1][0][0]), "+f"(acc[4][1][0][1]), "+f"(acc[4][1][0][2]), "+f"(acc[4][1][0][3]),
          "+f"(acc[4][1][1][0]), "+f"(acc[4][1][1][1]), "+f"(acc[4][1][1][2]), "+f"(acc[4][1][1][3]), "+f"(acc[4][2][0][0]),
          "+f"(acc[4][2][0][1]), "+f"(acc[4][2][0][2]), "+f"(acc[4][2][0][3]), "+f"(acc[4][2][1][0]), "+f"(acc[4][2][1][1]),
          "+f"(acc[4][2][1][2]), "+f"(acc[4][2][1][3]), "+f"(acc[4][3][0][0]), "+f"(acc[4][3][0][1]), "+f"(acc[4][3][0][2]),
          "+f"(acc[4][3][0][3]), "+f"(acc[4][3][1][0]), "+f"(acc[4][3][1][1]), "+f"(acc[4][3][1][2]), "+f"(acc[4][3][1][3]),
          "+r"(ring)
        : "r"(wf[0][0]), "r"(wf[0][1]), "r"(wf[0][2]), "r"(wf[0][3]), "r"(wf[1][0]), "r"(wf[1][1]), "r"(wf[1][2]), "r"(wf[1][3]),
          "r"(wf[2][0]), "r"(wf[2][1]), "r"(wf[2][2]), "r"(wf[2][3]), "r"(wf[3][0]), "r"(wf[3][1]), "r"(wf[3][2]), "r"(wf[3][3]),
          "r"(cgf[0]), "r"(cgf[1]), "r"(cgf[2]), "r"(cgf[3]), "r"(xoff), "r"(moff)
        : "memory");
}

#define PF_A 0x00000
#define PF_B 0x00000
#define PF_C 0x00000
__device__ __forceinline__ void l2_warm(uint32_t mask, int blk, int lane, const void* x, const void* Y, const void* ef) {
    if ((mask >> lane) & 1) {
        constexpr int EFP = (N_EDGES * 32 / (NB * 8) / 16 + 1) * 16, YP = (N_EDGES * 8 / (NB * 2) / 16 + 1) * 16;
        const char* base = lane < 8 ? (const char*)ef : lane < 10 ? (const char*)Y : (const char*)x;
        int o = lane < 8 ? (blk * 8 + lane) * EFP : lane < 10 ? (blk * 2 + lane - 8) * YP : ((lane - 10) * NB + blk) * 8192;
        int n = lane < 8 ? min(EFP, N_EDGES * 32 - o) : lane < 10 ? min(YP, N_EDGES * 8 - o) : min(8192, N_NODES * 1024 - o);
        if (n > 0) asm volatile("cp.async.bulk.prefetch.L2.global [%0], %1;" ::"l"(base + o), "r"(n));
    }
}

__device__ __noinline__ void generic_path(float* sagg, const __nv_bfloat16* x, const int* src, const int* dst,
                                          const __nv_bfloat16* Y, const __nv_bfloat16* ef, const __nv_bfloat16* w_rad,
                                          const __nv_bfloat16* cg, int x0, int x1) {
    const int tid = threadIdx.x, lane = tid & 31, blk = blockIdx.x;
    for (int k = 0; k < 2; k++)
        for (int r = 0; r < min(k == 0 ? x0 : x1, 32); r++) {
            uint32_t* p2 = g_mail2 + (blk * NSRC + ((tid + k * NTHR) >> 3)) * 32 + r;
            uint32_t v;
            int it = 0;
            do {
                asm volatile("ld.relaxed.gpu.global.u32 %0, [%1];" : "=r"(v) : "l"(p2) : "memory");
                if (++it > (1 << 20)) __trap();
            } while (v == 0);
            *p2 = 0;
        }
    __syncthreads();
    for (int i = tid; i < NPB * 512; i += NTHR) sagg[i] = 0.f;
    __syncthreads();
    for (int e0 = tid & ~31; e0 < N_EDGES; e0 += NTHR) {
        uint32_t bm = __ballot_sync(~0u, dst[e0 + lane] / NPB == blk);
        while (bm) {
            const int e = e0 + __ffs(bm) - 1, s = src[e], loc = dst[e] - blk * NPB;
            bm &= bm - 1;
            float a[4][4];
            for (int i = 0; i < 4; i++)
                for (int o = 0; o < 4; o++) {
                    a[i][o] = 0.f;
                    for (int f = 0; f < 4; f++)
                        a[i][o] += __bfloat162float(Y[e * 4 + f]) * __bfloat162float(cg[i * 16 + f * 4 + o]);
                }
#pragma unroll 1
            for (int c = lane; c < 128; c += 32) {
                float pre = 0.f;
                for (int k = 0; k < 16; k++)
                    pre += __bfloat162float(ef[e * 16 + k]) * __bfloat162float(w_rad[k * 128 + c]);
                const float R = pre / (1.f + __expf(-pre));
                for (int o = 0; o < 4; o++) {
                    float acc = 0.f;
                    for (int i = 0; i < 4; i++) acc += __bfloat162float(x[(size_t)s * 512 + c * 4 + i]) * a[i][o];
                    atomicAdd(&sagg[loc * 512 + c * 4 + o], R * acc);
                }
            }
        }
    }
    __syncthreads();
}

__device__ __forceinline__ void init_barriers() {
    extern __shared__ __align__(1024) uint8_t smem[];
    const uint32_t sb = smem_u32(smem);
#pragma unroll
    for (int i = 0; i < 4 * NG; i++) {
        mbar_init(sb + i * STAGE + 4 * ROWP, 33);
        mbar_init(sb + i * STAGE + 4 * ROWP + 8, 2);
    }
}

template <int PHASES>
__global__ void __launch_bounds__(NTHR, 1)
tfn_kernel(const __nv_bfloat16* __restrict__ x, const int* __restrict__ src, const int* __restrict__ dst,
           const __nv_bfloat16* __restrict__ Y, const __nv_bfloat16* __restrict__ ef,
           const __nv_bfloat16* __restrict__ w_rad, const __nv_bfloat16* __restrict__ cg,
           const __nv_bfloat16* __restrict__ w_mix, __nv_bfloat16* __restrict__ out) {
    extern __shared__ __align__(1024) uint8_t smem[];
    const int tid = threadIdx.x, lane = tid & 31;
    const int warp = __shfl_sync(~0u, tid >> 5, 0);
    const int blk = blockIdx.x;
    uint32_t sb = smem_u32(smem);
    asm volatile("" : "+r"(sb));
    int* mi = reinterpret_cast<int*>(smem + SM_MISC);

    const int g = lane >> 2, t = lane & 3;
    const uint32_t dump = sb + SC_DUMP + lane * 4;
    int4 d1[2], s1[2];
    constexpr int nq = EPC / 4;
    const bool binner = (PHASES & 1) && blk < NSRC;
    if (binner) {
#pragma unroll
        for (int k = 0; k < 2; k++) {
            const int q = tid + k * NTHR;
            if (q < nq) {
                d1[k] = __ldg(reinterpret_cast<const int4*>(dst + blk * EPC) + q);
                s1[k] = __ldg(reinterpret_cast<const int4*>(src + blk * EPC) + q);
            }
        }
    }
    if (binner) {
#pragma unroll
        for (int k = 0; k < 3; k++)
            if (k < 2 || warp < 1) sts128(sb + SC_MAIL + (tid + k * NTHR) * 16, ~0u, ~0u, ~0u, ~0u);
        if (tid <= NB / 4) sts128(sb + SC_CNT + tid * 16, 0, 0, 0, 0);
    }
    if (PHASES & 2) {
        if (tid == 160) { sts128(sb + SM_MISC, 0, 0, 0, 0); sts128(sb + SM_MISC + MI_NU * 4, 0, 0, 0, 0); }
        constexpr int lead = LEAD_CLK >> 2;
        if (tid == 161) mi[MI_SHIFT] = 0;
        if (tid == 162 && !(blk & 3) && blk < 128) g_lag[blk >> 2] = lead;
        if (tid < 20 * HS / 4) sts128(sb + SC_HIST + tid * 16, 0, 0, 0, 0);
        const uint32_t pad = (uint32_t)(lane * 0x10008 + 7);
#pragma unroll
        for (int k = 0; k < 3; k++)
            if (tid + k * NTHR < 4 * UCAP * REC / 16) sts128(sb + SM_REC + (tid + k * NTHR) * 16, pad, pad, pad, pad);
    }
    __syncthreads();
    if (PHASES & 2) {
#pragma unroll
        for (int k = 0; k < 4; k++) {
            const int i = tid + k * NTHR, c = i >> 4;
            cp16(sb + SM_W + c * 256 + (((i & 15) ^ ((c & 2) | (((c >> 4) & 1) << 2))) << 4), w_mix + i * 8);
        }
        if (warp >= 8) cp16(sb + SC_WR + ((tid - 256) ^ ((tid >> 4) & 6)) * 16, w_rad + (tid - 256) * 8);
        if (tid < 8) cp16(sb + SC_WR + 4096 + tid * 16, cg + tid * 8);
        if (PF_A && warp == 11) l2_warm(PF_A, blk, lane, x, Y, ef);
    }
    if (binner) {
#pragma unroll
        for (int k = 0; k < 2; k++) {
            if (tid + k * NTHR < nq) {
                const uint32_t dd[4] = {(uint32_t)d1[k].x, (uint32_t)d1[k].y, (uint32_t)d1[k].z, (uint32_t)d1[k].w};
                const uint32_t ss[4] = {(uint32_t)s1[k].x, (uint32_t)s1[k].y, (uint32_t)s1[k].z, (uint32_t)s1[k].w};
                uint32_t own[4], rk[4], v[4];
#pragma unroll
                for (int j = 0; j < 4; j++) { own[j] = dd[j] / NPB; rk[j] = atoms_inc(sb + SC_CNT + own[j] * 4); }
#pragma unroll
                for (int j = 0; j < 4; j++) {
                    const uint32_t loc = dd[j] - own[j] * NPB, code = loc + ((loc * 216) >> 12);
                    v[j] = (ss[j] << 18) + code * 2560 + (tid + k * NTHR) * 4 + j + 1;
                    sts32(sb + SC_MAIL + own[j] * 128 + ((min(rk[j], 31u) * 4) ^ ((own[j] & 7) << 4)), v[j]);
                }
                if (max(max(rk[0], rk[1]), max(rk[2], rk[3])) >= 31) {
#pragma unroll
                    for (int j = 0; j < 4; j++)
                        if (rk[j] - 31 < 32)
                            asm volatile("st.relaxed.gpu.global.u32 [%0], %1;" ::"l"(g_mail2 + (own[j] * NSRC + blk) * 32 + rk[j] - 31), "r"(v[j]) : "memory");
                }
            }
        }
        __syncwarp();
        asm volatile("red.shared.max.u32 [%0], %1;" ::"r"(lane == 0 ? sb + SC_CNT + NB * 4 : dump), "r"(gtime()) : "memory");
        STAMP(1);
        __syncthreads();
        const uint32_t hdr = 0xc0000000u | ((lds32(sb + SC_CNT + NB * 4) << 7) & 0x3ffff000u);
        uint4 mv[3];
        uint32_t mc[3];
#pragma unroll
        for (int k = 0; k < 3; k++)
            if (k < 2 || warp < 1) {
                const int j = tid + k * NTHR, own = j >> 3;
                mv[k] = lds128(sb + SC_MAIL + own * 128 + (((j ^ own) & 7) << 4));
                mc[k] = lds32(sb + SC_CNT + own * 4);
            }
#pragma unroll
        for (int k = 0; k < 3; k++)
            if (k < 2 || warp < 1) {
                const int j = tid + k * NTHR;
                asm volatile("st.relaxed.gpu.global.v4.u32 [%0], {%1,%2,%3,%4};" ::"l"(g_mail + ((j >> 3) * NSRC + blk) * 8 + (j & 7)),
                             "r"(mv[k].x), "r"(mv[k].y), "r"(mv[k].z), "r"((j & 7) == 7 ? hdr | mc[k] : mv[k].w) : "memory");
            }
        STAMP(2);
    }
    if (!(PHASES & 2)) return;
    const uint32_t tpub = (uint32_t)clock() + (blk < NSRC ? 0 : 3000);
    asm volatile("cp.async.wait_all;" ::: "memory");
    __syncwarp();
#pragma unroll
    for (int k = 0; k < 2; k++) {
        const int i = (tid & ~1) + ((tid & 1) * 2 + k) * NTHR, c = i >> 4;
        const uint32_t a0 = sb + SM_W + c * 256 + (((i & 15) ^ ((c & 3) | (((c >> 4) & 1) << 2))) << 4);
        const uint32_t o = (tid & 1) << 4;
        uint4 u = lds128((a0 & ~16u) ^ o), v = lds128((a0 | 16u) ^ o);
        if (tid & 1) { const uint4 w = u; u = v; v = w; }
        const uint32_t s0 = (tid & 1) ? 0x7632 : 0x5410, s1 = s0 ^ 0x2222;
        sts128(a0 ^ o, __byte_perm(u.x, u.y, s0), __byte_perm(u.z, u.w, s0), __byte_perm(v.x, v.y, s0), __byte_perm(v.z, v.w, s0));
        sts128(a0 ^ o ^ 16, __byte_perm(u.x, u.y, s1), __byte_perm(u.z, u.w, s1), __byte_perm(v.x, v.y, s1), __byte_perm(v.z, v.w, s1));
    }

    uint32_t en[8], hr[8], rk[8], em[8];
    int xc[2];
    const uint32_t tref = __shfl_sync(~0u, gtime() >> 5, 0);
    {
        uint4* mp = g_mail + blk * NSRC * 8 + tid;
        int it = 0;
        bool ok;
        while ((int)((uint32_t)clock() - tpub) < POLL_DELAY) {}
        do {
#pragma unroll
            for (int k = 0; k < 2; k++)
                    asm volatile("ld.relaxed.gpu.global.v4.u32 {%0,%1,%2,%3}, [%4];"
                                 : "=r"(en[4 * k]), "=r"(en[4 * k + 1]), "=r"(en[4 * k + 2]), "=r"(en[4 * k + 3])
                                 : "l"(mp + k * NTHR) : "memory");
            uint32_t m = ~0u;
#pragma unroll
            for (int i = 0; i < 8; i++) m = min(m, en[i]);
            ok = __all_sync(~0u, m != 0);
            if (++it > (1 << 20)) __trap();
        } while (!ok);
        STAMP(3);
#pragma unroll
        for (int i = 0; i < 8; i++) {
            const uint32_t w = en[i] & 0x3ffff, code = ((w >> 9) * 13108) >> 16;
            hr[i] = en[i] < 0xc0000000u ? sb + SC_HIST + ((code >> 2) * HS + (en[i] >> 25)) * 4 : dump;
            rk[i] = atoms_inc(hr[i]);
            em[i] = ((((tid + (i >> 2) * NTHR) >> 3) * EPC + w - code * 2560 - 1) * 8) | (code & 3);
        }
        int dt = -(1 << 20);
#pragma unroll
        for (int k = 0; k < 2; k++) {
            const bool hd = (lane & 7) == 7;
            dt = max(dt, hd ? (int)(((en[4 * k + 3] >> 12) - tref) << 14) >> 14 : -(1 << 20));
            xc[k] = hd ? max((int)(en[4 * k + 3] & 0xfff) - 31, 0) : 0;
        }
        dt = __reduce_max_sync(~0u, dt);
        asm volatile("red.shared.max.u32 [%0], %1;" ::"r"(lane == 0 ? sb + SM_MISC + MI_TMAX * 4 : dump + 128), "r"(tref + dt + (1u << 27)) : "memory");
        if (xc[0] | xc[1]) {
#pragma unroll
            for (int k = 0; k < 2; k++) {
                const int slot = atomicAdd(&mi[MI_XN], xc[k]);
                for (int r = 0; r < xc[k] && slot + r < 32; r++)
                    reinterpret_cast<uint32_t*>(smem + SC_XTRA)[slot + r] = ((tid + k * NTHR) >> 3) * 32 + r;
            }
        }
#pragma unroll
        for (int k = 0; k < 2; k++)
            mp[k * NTHR] = make_uint4(0, 0, 0, 0);
    }
    __syncthreads();
    STAMP(4);
    uint32_t* hist = reinterpret_cast<uint32_t*>(smem + SC_HIST);
    const int xn = mi[MI_XN];
    uint32_t xi = 0, xv = 1;
    if (warp < 10) {
        uint32_t* hp = hist + (warp * 2 + (lane >> 4)) * HS + (lane & 15) * 5;
        int c[5], s = 0;
#pragma unroll
        for (int j = 0; j < 5; j++) { c[j] = hp[j]; s += c[j]; }
        int inc = s;
#pragma unroll
        for (int o = 1; o < 16; o <<= 1) { int v = __shfl_up_sync(~0u, inc, o, 16); if ((lane & 15) >= o) inc += v; }
        int base = 0;
        if ((lane & 15) == 15) {
            const int tm = (warp * 2 + (lane >> 4)) / 5;
            base = tm * 256 + atomicAdd(&mi[MI_NU + tm], (inc + 3) >> 2);
            hp[5] = (base + ((inc + 3) >> 2)) << 16;
        }
        const int tot = __shfl_sync(~0u, inc, 15, 16);
        base = __shfl_sync(~0u, base, 15, 16);
        int ex = inc - s;
#pragma unroll
        for (int j = 0; j < 5; j++) {
            hp[j] = (base * 4 + ex) | ((base + ((ex == tot ? ex + 3 : ex + 1) >> 2)) << 16);
            ex += c[j];
        }
    } else if (warp == 10) {
        if (lane == 0) init_barriers();
        if (PF_B) l2_warm(PF_B, blk, lane, x, Y, ef);
        if (lane < xn) {
            xi = reinterpret_cast<const uint32_t*>(smem + SC_XTRA)[lane];
            asm volatile("ld.relaxed.gpu.global.u32 %0, [%1];" : "=r"(xv) : "l"(g_mail2 + blk * NSRC * 32 + xi) : "memory");
        }
    } else if (warp >= 12) {
        const uint32_t d = sb + (warp - 12) * NG * STAGE + lane * 16;
#pragma unroll
        for (int m = 0; m < 8; m++) {
            uint32_t w[4];
#pragma unroll
            for (int j = 0; j < 4; j++)
                w[j] = mul_lo(lds32(sb + SC_WR + (2 * t + (j & 1) + (j >> 1) * 8) * 256 + (((m * 8 + g) * 4) ^ (t << 5))), 0x3f003f00u);
            sts128(d + (m >> 2) * ROWP + (m & 3) * 512, __byte_perm(w[0], w[1], 0x5410), __byte_perm(w[0], w[1], 0x7632),
                   __byte_perm(w[2], w[3], 0x5410), __byte_perm(w[2], w[3], 0x7632));
        }
        uint32_t c[4];
#pragma unroll
        for (int i = 0; i < 4; i++) {
            const uint32_t ca = sb + SC_WR + 4096 + (i * 16 + (t & 1) * 8 + (g & 3)) * 2;
            c[i] = (lds16(ca) | (lds16(ca + 8) << 16)) & ((t >> 1) == (g >> 2) ? ~0u : 0u);
        }
        sts128(d + 2 * ROWP, c[0], c[1], c[2], c[3]);
    } else if (lane == 0) {
        sts32(sb + SC_GPOS + GDUMMY * 4, (uint32_t)(4 * UCAP * REC + 128) * 0x10001u);
        constexpr int start_ns = START_NS;
        mi[MI_T0] = (uint32_t)clock() + (((int)(((uint32_t)mi[MI_TMAX] << 5) + start_ns - gtime()) * 31) >> 4);
    }
    __syncthreads();
    STAMP(10);
    int myng = mi[MI_NU + (lane & 3)];
    const bool ovf = __any_sync(~0u, myng + xn > 2 * (UCAP - 4) || xn > 32);
    if (!ovf) {
        constexpr int pace = PACE_Q8, p1 = PACE_HEAD, b1 = HEAD_BK, p2 = PACE_TAIL, b2 = TAIL_BK, lead = PACE_LEAD;
        auto sched = [&](int b) { return b * pace - min(b, b1) * (pace - p1) - max(b - b2, 0) * (pace - p2) - lead; };
        if (warp < 10) {
            const int team = tid / NBK, b = tid - team * NBK;
            int lo[5], n[5], pos = team * UCAP * 2, nsum = 0;
#pragma unroll
            for (int q = 0; q < 5; q++) {
                lo[q] = hist[(team * 5 + q) * HS + b] >> 16;
                n[q] = (hist[(team * 5 + q) * HS + b + 1] >> 16) - lo[q];
                pos += lo[q] - (hist[(team * 5 + q) * HS] >> 16);
                nsum += n[q];
            }
            const int step = __float2int_rz(__fdividef((float)(sched(b + 1) - sched(b)), (float)max(nsum, 1)));
            const int tb = sched(b) + step / 2 - pos * step;
            const uint32_t t0 = mi[MI_T0];
            auto emit = [&](int q, int r, int pq) {
                const bool on = r < n[q];
                const uint32_t ro = (pq >> 1) * REC, par = pq & 1;
                sts32(on ? sb + SC_GPOS + (lo[q] + r) * 4 : dump, ro * 0x10001u + par * 0x40002u + (REC | (16 << 16)));
                sts8(on ? sb + SM_REC + 48 + ro + par : dump, q);
                sts16(on && !par ? sb + SM_REC + REC + 50 + ro : dump, (t0 + max(tb + pq * step, 0)) >> 2);
            };
#pragma unroll
            for (int q = 0, pq = pos; q < 5; pq += n[q], q++) emit(q, 0, pq);
#pragma unroll
            for (int q = 0; q < 5; pos += n[q], q++)
#pragma unroll 1
                for (int r = 1; __any_sync(~0u, r < n[q]); r++) emit(q, r, pos + r);
        } else if (warp == 10) {
            for (int n = 0; __any_sync(~0u, xv == 0); n++) {
                if (xv == 0) asm volatile("ld.relaxed.gpu.global.u32 %0, [%1];" : "=r"(xv) : "l"(g_mail2 + blk * NSRC * 32 + xi) : "memory");
                if (n > (1 << 20)) __trap();
            }
            const uint32_t w = xv & 0x3ffff, code = ((w >> 9) * 13108) >> 16, xt = lane < xn ? code / 20 : 4;
            const uint32_t same = __match_any_sync(~0u, xt);
            const int pq = __shfl_sync(~0u, myng, xt & 3) + __popc(same & ((1u << lane) - 1));
#pragma unroll
            for (int q = 0; q < 4; q++) {
                const int c = __popc(__ballot_sync(~0u, xt == q));
                if (lane == q) myng += c;
            }
            if (lane < xn) {
                g_mail2[blk * NSRC * 32 + xi] = 0;
                const uint32_t a = sb + SM_REC + (xt * UCAP + (pq >> 1)) * REC;
                sts16(a + REC + (pq & 1) * 2, xv >> 18);
                sts32(a + 16 + (pq & 1) * 4, (((xi >> 5) * EPC + w - code * 2560 - 1) * 8) | (code & 3));
                sts8(a + 48 + (pq & 1), (code >> 2) - xt * 5);
                if (!(pq & 1)) sts16(a + REC + 50, ((uint32_t)mi[MI_T0] + sched(NBK - 2)) >> 2);
            }
            if (lane < 4) {
                const uint32_t a = sb + SM_REC + (lane * UCAP + (myng >> 1)) * REC + 48;
                if (myng & 1) sts8(a + 1, 0);
                sts16(a + (myng & 1) * REC, 5);
                mi[MI_END + lane] = (myng + 1) >> 1;
            }
        }
#pragma unroll
        for (int i = 0; i < 8; i++) {
            const uint32_t p = en[i] < 0xc0000000u ? rk[i] + lds16(hr[i]) : GDUMMY * 4;
            hr[i] = sb + SC_GPOS + (p & ~3u);
            rk[i] = (p & 3) * 0x80004u;
        }
        __syncthreads();
        STAMP(11);
#pragma unroll
        for (int i = 0; i < 8; i++) rk[i] += lds32(hr[i]);
#pragma unroll
        for (int i = 0; i < 8; i++) {
            sts16(sb + SM_REC + (rk[i] & 0xffff), en[i] >> 18);
            sts32(sb + SM_REC + (rk[i] >> 16), em[i]);
        }
    } else {
        if (tid < 4) {
            sts16(sb + SM_REC + tid * UCAP * REC + 48, 5);
            mi[MI_END + tid] = 0;
        }
        generic_path(reinterpret_cast<float*>(smem), x, src, dst, Y, ef, w_rad, cg, xc[0], xc[1]);
    }

    __syncwarp();
    if (warp >= 8) {
        asm volatile("bar.sync 3, 512;" ::: "memory");
        asm volatile("setmaxnreg.dec.sync.aligned.u32 24;");
        const int team = warp & 3;
        if (ovf) {
            asm volatile("bar.sync 2;" ::: "memory");
            if (tid == 256) init_barriers();
            asm volatile("bar.sync 2;" ::: "memory");
        }
        STAMP(5);
        const uint32_t ring = sb + SM_RING + team * NG * STAGE;
        constexpr int lead = LEAD_CLK >> 2;
        const uint32_t q = lane >> 3, c = lane & 7, rec = sb + SM_REC + team * UCAP * REC;
        __syncwarp();
        producer_loop(reinterpret_cast<const char*>(x) + c * 16, reinterpret_cast<const char*>(ef) + (c & 1) * 16, Y,
                      q * ROWP + ((c ^ (q << 1)) << 4), q * 4 + (c & 2) * 8, (c & 1) * 2 + (c >> 2), ring, rec,
                      rec + (mi[MI_END + team] + 1) * REC, warp >= 12, lead, sb + SM_MISC + MI_SHIFT * 4);
    } else {
        const int team = warp >> 1, h = warp & 1;
        asm volatile("bar.arrive 3, 512;" ::: "memory");
        if (PF_C && warp == 0) l2_warm(PF_C, blk, lane, x, Y, ef);
        asm volatile("setmaxnreg.inc.sync.aligned.u32 232;");
        uint32_t ring = sb + SM_RING + team * NG * STAGE;
        uint32_t wf[4][4], cgf[4];
#pragma unroll
        for (int m = 0; m < 5; m++) {
            const uint4 v = lds128(ring + (m < 4 ? h * ROWP + m * 512 : 2 * ROWP) + lane * 16);
            uint32_t* f = m < 4 ? wf[m] : cgf;
            f[0] = v.x; f[1] = v.y; f[2] = v.z; f[3] = v.w;
        }
        float acc[5][4][2][4];
        if (!ovf) {
#pragma unroll
            for (int l = 0; l < 5; l++)
#pragma unroll
                for (int m = 0; m < 4; m++)
#pragma unroll
                    for (int p = 0; p < 2; p++)
#pragma unroll
                        for (int r = 0; r < 4; r++) acc[l][m][p][r] = 0.f;
        } else {
            const float* sagg = reinterpret_cast<const float*>(smem);
#pragma unroll
            for (int l = 0; l < 5; l++)
#pragma unroll
                for (int m = 0; m < 4; m++)
#pragma unroll
                    for (int p = 0; p < 2; p++)
#pragma unroll
                        for (int r = 0; r < 4; r++) {
                            int nd = l * 4 + (g >> 2) + (r >> 1) * 2;
                            int ch = h * 64 + m * 16 + 4 * t + (r & 1) * 2 + p;
                            acc[l][m][p][r] = nd < 19 ? sagg[(team * 19 + nd) * 512 + ch * 4 + (g & 3)] : 0.f;
                        }
            asm volatile("bar.sync 2;" ::: "memory");
            asm volatile("bar.sync 2;" ::: "memory");
        }
        const uint32_t xoff = t * ROWP + h * 512 + ((g ^ (t << 1)) << 4);
        const uint32_t mat = lane >> 3, mhi = (lane >> 2) & 1;
        const bool isy = mat < 2;
        const uint32_t ml = isy ? (t & 2) + (mat & 1) : t;
        const uint32_t moff = ml * ROWP + 2048 + (((isy ? 4 + 2 * mhi + (t & 1) : 2 * mhi + mat - 2) ^ (ml << 1)) << 4);
        __syncwarp();
        consumer_loop(acc, wf, cgf, xoff, ring, moff);
        {
        int lane_;
        asm volatile("mov.u32 %0, %%laneid;" : "=r"(lane_));
        const int lane = lane_, g = lane >> 2, t = lane & 3;
        const uint32_t sb = ring - team * NG * STAGE;
        STAMP(7);
        asm volatile("bar.sync %0, 64;" ::"r"(4 + team) : "memory");
        {
            const int rr = ((g & 3) >> 1) * 8 + (g >> 2) * 2 + (g & 1);
#pragma unroll
            for (int l = 0; l < 5; l++)
#pragma unroll
                for (int hi = 0; hi < 2; hi++) {
                    const int R = l * 16 + rr + hi * 4;
                    const uint32_t a = sb + team * AGGT + h * 10240 + R * 128;
#pragma unroll
                    for (int c = 0; c < 2; c++) {
                        const int m = 2 * c;
                        sts128(a + (((2 * t + c) ^ (R & 7)) << 4),
                               pack_bf16(acc[l][m][0][2 * hi], acc[l][m][1][2 * hi]),
                               pack_bf16(acc[l][m][0][2 * hi + 1], acc[l][m][1][2 * hi + 1]),
                               pack_bf16(acc[l][m + 1][0][2 * hi], acc[l][m + 1][1][2 * hi]),
                               pack_bf16(acc[l][m + 1][0][2 * hi + 1], acc[l][m + 1][1][2 * hi + 1]));
                    }
                }
        }
        asm volatile("fence.proxy.async.shared::cta;" ::: "memory");
        uint32_t wa[8][4];
        {
            const int r = lane & 7, k = (lane >> 4) * 8 + r;
            const int chunk = (2 * warp + ((lane >> 3) & 1)) ^ r;
#pragma unroll
            for (int ks = 0; ks < 8; ks++) {
                const int c = (ks >> 2) * 64 + 16 * (k >> 2) + 4 * (ks & 3) + (k & 3);
                asm volatile("ldmatrix.sync.aligned.m8n8.x4.trans.shared.b16 {%0,%1,%2,%3}, [%4];"
                             : "=r"(wa[ks][0]), "=r"(wa[ks][1]), "=r"(wa[ks][2]), "=r"(wa[ks][3])
                             : "r"(sb + SM_W + c * 256 + (chunk << 4)));
            }
        }
        asm volatile("bar.sync 1, 256;" ::: "memory");
        STAMP(8);
        const int sl = (lane & 7) * 4 + (lane >> 3);
        __nv_bfloat16* op = out + (size_t)(blk * NPB + (lane >> 3)) * 512 + warp * 64 + (lane & 7) * 8;
        const int nleft = N_NODES - blk * NPB - (lane >> 3);
#pragma unroll 1
        for (int tm = 0; tm < 4; tm++) {
            float o[40];
            asm volatile("wgmma.fence.sync.aligned;" ::: "memory");
#pragma unroll
            for (int ks = 0; ks < 8; ks++) {
                const uint32_t a = sb + tm * AGGT + (ks >> 2) * 10240 + (ks & 3) * 32;
                const uint64_t desc = (uint64_t)((a & 0x3ffff) >> 4) | (1ull << 16) | (64ull << 32) | (1ull << 62);
                wgmma_n80(o, wa[ks], desc, ks);
            }
            asm volatile("wgmma.commit_group.sync.aligned;" ::: "memory");
            asm volatile("wgmma.wait_group.sync.aligned 0;" ::: "memory");
#pragma unroll
            for (int i = 0; i < 40; i++) asm volatile("" : "+f"(o[i])::"memory");
#pragma unroll
            for (int l = 0; l < 5; l++) {
                uint4 v;
                v.x = __shfl_sync(~0u, pack_bf16(o[8 * l + 0], o[8 * l + 1]), sl);
                v.y = __shfl_sync(~0u, pack_bf16(o[8 * l + 4], o[8 * l + 5]), sl);
                v.z = __shfl_sync(~0u, pack_bf16(o[8 * l + 2], o[8 * l + 3]), sl);
                v.w = __shfl_sync(~0u, pack_bf16(o[8 * l + 6], o[8 * l + 7]), sl);
                if ((l < 4 || lane < 24) && tm * 19 + l * 4 < nleft)
                    *reinterpret_cast<uint4*>(op + (tm * 19 + l * 4) * 512) = v;
            }
        }
        STAMP(9);
        }
    }
}

}

extern "C" void kernel_launch(void* const* d_in, const int* in_sizes, int n_in, void* d_out, int out_size) {
    (void)in_sizes; (void)n_in; (void)out_size;
    const __nv_bfloat16* x = (const __nv_bfloat16*)d_in[0];
    const int* src = (const int*)d_in[1];
    const int* dst = (const int*)d_in[2];
    const __nv_bfloat16* Y = (const __nv_bfloat16*)d_in[3];
    const __nv_bfloat16* ef = (const __nv_bfloat16*)d_in[4];
    const __nv_bfloat16* w_rad = (const __nv_bfloat16*)d_in[5];
    const __nv_bfloat16* cg = (const __nv_bfloat16*)d_in[6];
    const __nv_bfloat16* w_mix = (const __nv_bfloat16*)d_in[7];
    __nv_bfloat16* out = (__nv_bfloat16*)d_out;

    static int sms = 0;
    if (sms == 0) {
        int dev = 0;
        cudaGetDevice(&dev);
        cudaDeviceGetAttribute(&sms, cudaDevAttrMultiProcessorCount, dev);
        cudaFuncSetAttribute(tfn_kernel<3>, cudaFuncAttributeMaxDynamicSharedMemorySize, SM_TOTAL);
        cudaFuncSetAttribute(tfn_kernel<1>, cudaFuncAttributeMaxDynamicSharedMemorySize, SM_TOTAL);
        cudaFuncSetAttribute(tfn_kernel<2>, cudaFuncAttributeMaxDynamicSharedMemorySize, SM_TOTAL);
    }
    if (sms >= NB) {
        tfn_kernel<3><<<NB, NTHR, SM_TOTAL>>>(x, src, dst, Y, ef, w_rad, cg, w_mix, out);
    } else {
        tfn_kernel<1><<<NB, NTHR, SM_TOTAL>>>(x, src, dst, Y, ef, w_rad, cg, w_mix, out);
        tfn_kernel<2><<<NB, NTHR, SM_TOTAL>>>(x, src, dst, Y, ef, w_rad, cg, w_mix, out);
    }
}
```

```cpp
#include <cuda_runtime.h>
#include <cuda_bf16.h>
#include <stdint.h>

namespace {

constexpr int N_NODES = 10000;
constexpr int N_EDGES = 320000;
constexpr int NB      = 132;
constexpr int NPB     = 76;
constexpr int NSRC    = 128;
constexpr int EPC     = N_EDGES / NSRC;
constexpr int NTHR    = 512;
#define NGS 5
constexpr int NG      = NGS;
constexpr int ROWP    = 2176;
constexpr int STAGE   = 4 * ROWP + 128;
constexpr int UCAP    = 104;
constexpr int REC     = 52;
constexpr int NBK     = 80;
constexpr int HS      = 81;

#define PACE_Q8 640
#define PACE_LEAD 300
#define PACE_HEAD 730
#define HEAD_BK 10
#define PACE_TAIL 590
#define TAIL_BK 62
#define POLL_DELAY 1350
#define LEAD_CLK 700
#define ROWMODE 1
#define PAIRING 1
#define START_NS 3200

constexpr int SM_RING  = 0;
constexpr int SM_W     = 4 * NG * STAGE;
constexpr int SM_REC   = SM_W + 32768;
constexpr int SM_MISC  = SM_REC + 4 * UCAP * REC;
constexpr int SM_TOTAL = SM_MISC + 192;
constexpr int SC_MAIL  = 1 * STAGE;
constexpr int SC_CNT   = 3 * STAGE;
constexpr int SC_DUMP  = 3 * STAGE + 1024;
constexpr int SC_XTRA  = 3 * STAGE + 2048;
constexpr int SC_HIST  = 4 * STAGE;
constexpr int SC_GPOS  = 6 * STAGE;
constexpr int SC_WR    = 7 * STAGE;
constexpr int GDUMMY   = 1024;
constexpr int AGGT     = (NG * STAGE + 1023) / 1024 * 1024;
static_assert(3 * AGGT + 20480 <= 4 * NG * STAGE, "agg tile inside the team's ring");
static_assert(NPB * 512 * 4 <= 4 * NG * STAGE, "slow tile");
static_assert(SM_TOTAL <= 232448, "smem");
static_assert(SM_REC % 16 == 0 && (4 * UCAP * REC) % 16 == 0 && SM_MISC % 16 == 0, "align");
constexpr int MI_XN = 0;
constexpr int MI_TMAX = 2;
constexpr int MI_SHIFT = 7;
constexpr int MI_NU = 8;
constexpr int MI_END = 28;
constexpr int MI_T0 = 3;

__device__ uint4 g_mail[NB * NSRC * 8];
__device__ uint32_t g_mail2[NB * NSRC * 32];
__device__ __align__(128) int g_lag[32];
#define STAMP(k)

__device__ __forceinline__ uint32_t smem_u32(const void* p) { return (uint32_t)__cvta_generic_to_shared(p); }
__device__ __forceinline__ uint32_t atoms_inc(uint32_t a) {
    uint32_t r;
    asm volatile("atom.shared.add.u32 %0, [%1], 1;" : "=r"(r) : "r"(a) : "memory");
    return r;
}
__device__ __forceinline__ void sts32(uint32_t a, uint32_t v) { asm volatile("st.shared.u32 [%0], %1;" ::"r"(a), "r"(v) : "memory"); }
__device__ __forceinline__ void sts16(uint32_t a, uint32_t v) { asm volatile("st.shared.u16 [%0], %1;" ::"r"(a), "h"((uint16_t)v) : "memory"); }
__device__ __forceinline__ void sts8(uint32_t a, uint32_t v) { asm volatile("st.shared.u8 [%0], %1;" ::"r"(a), "r"(v) : "memory"); }
__device__ __forceinline__ uint32_t lds32(uint32_t a) { uint32_t v; asm volatile("ld.shared.u32 %0, [%1];" : "=r"(v) : "r"(a)); return v; }
__device__ __forceinline__ uint32_t lds16(uint32_t a) { uint32_t v; asm volatile("ld.shared.u16 %0, [%1];" : "=r"(v) : "r"(a)); return v; }
__device__ __forceinline__ void cp16(uint32_t d, const void* p) {
    asm volatile("cp.async.cg.shared.global [%0], [%1], 16;" ::"r"(d), "l"(p) : "memory");
}
__device__ __forceinline__ uint32_t gtime() {
    uint32_t t;
    asm volatile("mov.u32 %0, %%globaltimer_lo;" : "=r"(t));
    return t;
}
__device__ __forceinline__ void mbar_init(uint32_t bar, int cnt) {
    asm volatile("mbarrier.init.shared.b64 [%0], %1;" ::"r"(bar), "r"(cnt) : "memory");
}
__device__ __forceinline__ void mbar_wait(uint32_t bar, uint32_t parity) {
    asm volatile("{\n.reg .pred p;\n.reg .u32 n;\nmov.u32 n, 0;\n"
                 "WAIT_%=:\nmbarrier.try_wait.parity.shared.b64 p, [%0], %1;\n@p bra DONE_%=;\n"
                 "add.u32 n, n, 1;\nsetp.lt.u32 p, n, 4194304;\n@p bra WAIT_%=;\ntrap;\nDONE_%=:\n}"
                 ::"r"(bar), "r"(parity) : "memory");
}
__device__ __forceinline__ void mbar_arrive_elect(uint32_t bar) {
    asm volatile("{\n.reg .pred p;\nelect.sync _|p, 0xffffffff;\n@p mbarrier.arrive.shared.b64 _, [%0];\n}" ::"r"(bar) : "memory");
}
__device__ __forceinline__ uint4 lds128(uint32_t a) {
    uint4 v;
    asm volatile("ld.shared.v4.u32 {%0,%1,%2,%3}, [%4];" : "=r"(v.x), "=r"(v.y), "=r"(v.z), "=r"(v.w) : "r"(a));
    return v;
}
__device__ __forceinline__ void sts128(uint32_t a, uint32_t x, uint32_t y, uint32_t z, uint32_t w) {
    asm volatile("st.shared.v4.u32 [%0], {%1,%2,%3,%4};" ::"r"(a), "r"(x), "r"(y), "r"(z), "r"(w) : "memory");
}
__device__ __forceinline__ uint32_t pack_bf16(float lo, float hi) {
    uint32_t r;
    asm("cvt.rn.bf16x2.f32 %0, %1, %2;" : "=r"(r) : "f"(hi), "f"(lo));
    return r;
}
__device__ __forceinline__ float tanh_fast(float x) {
    float r;
    asm("tanh.approx.f32 %0, %1;" : "=f"(r) : "f"(x));
    return r;
}
__device__ __forceinline__ uint32_t mul_lo(uint32_t v, uint32_t r) {
    __nv_bfloat162 a = *reinterpret_cast<__nv_bfloat162*>(&v), b = *reinterpret_cast<__nv_bfloat162*>(&r);
    __nv_bfloat162 c = __hmul2(a, __low2bfloat162(b));
    return *reinterpret_cast<uint32_t*>(&c);
}
__device__ __forceinline__ uint32_t mul_hi(uint32_t v, uint32_t r) {
    __nv_bfloat162 a = *reinterpret_cast<__nv_bfloat162*>(&v), b = *reinterpret_cast<__nv_bfloat162*>(&r);
    __nv_bfloat162 c = __hmul2(a, __high2bfloat162(b));
    return *reinterpret_cast<uint32_t*>(&c);
}
__device__ __forceinline__ void mma0(float (&d)[4], uint32_t a0, uint32_t a1, uint32_t a2, uint32_t a3,
                                     uint32_t b0, uint32_t b1) {
    asm("mma.sync.aligned.m16n8k16.row.col.f32.bf16.bf16.f32 {%0,%1,%2,%3}, {%4,%5,%6,%7}, {%8,%9}, {%10,%10,%10,%10};"
        : "=f"(d[0]), "=f"(d[1]), "=f"(d[2]), "=f"(d[3])
        : "r"(a0), "r"(a1), "r"(a2), "r"(a3), "r"(b0), "r"(b1), "f"(0.f));
}
__device__ __forceinline__ void mma0_k8(float (&d)[4], uint32_t a0, uint32_t a1, uint32_t b0) {
    asm("mma.sync.aligned.m16n8k8.row.col.f32.bf16.bf16.f32 {%0,%1,%2,%3}, {%4,%5}, {%6}, {%7,%7,%7,%7};"
        : "=f"(d[0]), "=f"(d[1]), "=f"(d[2]), "=f"(d[3])
        : "r"(a0), "r"(a1), "r"(b0), "f"(0.f));
}
__device__ __forceinline__ void mma_acc(float (&d)[4], const uint32_t (&a)[4], uint32_t b0, uint32_t b1) {
    asm volatile("mma.sync.aligned.m16n8k16.row.col.f32.bf16.bf16.f32 {%0,%1,%2,%3}, {%4,%5,%6,%7}, {%8,%9}, {%0,%1,%2,%3};"
        : "+f"(d[0]), "+f"(d[1]), "+f"(d[2]), "+f"(d[3])
        : "r"(a[0]), "r"(a[1]), "r"(a[2]), "r"(a[3]), "r"(b0), "r"(b1));
}
__device__ __forceinline__ void wgmma_n80(float (&d)[40], const uint32_t (&a)[4], uint64_t desc, int scale_d) {
    asm volatile("{\n.reg .pred p;\nsetp.ne.b32 p, %45, 0;\n"
        "wgmma.mma_async.sync.aligned.m64n80k16.f32.bf16.bf16 "
        "{%0,%1,%2,%3,%4,%5,%6,%7,%8,%9,%10,%11,%12,%13,%14,%15,%16,%17,%18,%19,"
        "%20,%21,%22,%23,%24,%25,%26,%27,%28,%29,%30,%31,%32,%33,%34,%35,%36,%37,%38,%39}, "
        "{%40,%41,%42,%43}, %44, p, 1, 1, 0;\n}"
        : "+f"(d[0]), "+f"(d[1]), "+f"(d[2]), "+f"(d[3]), "+f"(d[4]), "+f"(d[5]), "+f"(d[6]), "+f"(d[7]),
          "+f"(d[8]), "+f"(d[9]), "+f"(d[10]), "+f"(d[11]), "+f"(d[12]), "+f"(d[13]), "+f"(d[14]), "+f"(d[15]),
          "+f"(d[16]), "+f"(d[17]), "+f"(d[18]), "+f"(d[19]), "+f"(d[20]), "+f"(d[21]), "+f"(d[22]), "+f"(d[23]),
          "+f"(d[24]), "+f"(d[25]), "+f"(d[26]), "+f"(d[27]), "+f"(d[28]), "+f"(d[29]), "+f"(d[30]), "+f"(d[31]),
          "+f"(d[32]), "+f"(d[33]), "+f"(d[34]), "+f"(d[35]), "+f"(d[36]), "+f"(d[37]), "+f"(d[38]), "+f"(d[39])
        : "r"(a[0]), "r"(a[1]), "r"(a[2]), "r"(a[3]), "l"(desc), "r"(scale_d));
}

__device__ __forceinline__ void producer_loop(const void* xl, const void* efl, const void* Y, uint32_t xd, uint32_t oef,
                                              uint32_t ysel, uint32_t ring, uint32_t rec, uint32_t rlast, uint32_t odd,
                                              uint32_t lead, uint32_t lag, uint32_t xh) {
    asm volatile(
        "{\n"
        ".reg .b32 w, em, ey, cu, d, t, u, n, sa, ph, rp, rend, rlast, dy, sv, lag, lv, w2, w3, w4;\n"
        ".reg .b16 tg;\n"
        ".reg .b64 pa, pb, pc, pd;\n"
        ".reg .pred lo, z, q, e, zb;\n"
        "redux.sync.or.b32 sa, %6, 0xffffffff;\n"
        "redux.sync.or.b32 rp, %7, 0xffffffff;\n"
        "redux.sync.or.b32 rlast, %8, 0xffffffff;\n"
        "add.u32 rend, sa, 44160;\n"
        "and.b32 t, %5, 1;\n"
        "setp.eq.u32 lo, t, 0;\n"
        "mov.u32 ph, 1;\n"
        "setp.ne.u32 q, %9, 0;\n"
        "@q bra.uni PODD_%=;\n"
        "add.u32 t, rp, %4;\n"
        "ld.shared.u32 em, [t+16];\n"
        "and.b32 t, em, 0xfffffff8;\n"
        "mad.wide.u32 pa, t, 4, %1;\n"
        "add.u32 d, sa, %3;\n"
        "@lo cp.async.cg.shared.global [d+2048], [pa], 16;\n"
        "cp.async.mbarrier.arrive.noinc.shared.b64 [sa+8704];\n"
        "add.u32 rp, rp, 52;\n"
        "add.u32 sa, sa, 8832;\n"
        "PODD_%=:\n"
        "add.u32 rp, rp, 52;\n"
        "add.u32 sa, sa, 8832;\n"
        "shr.u32 t, %4, 1;\n"
        "and.b32 t, t, 4;\n"
        "add.u32 t, t, rp;\n"
        "ld.shared.u32 w, [t];\n"
        "ld.shared.u32 w2, [t+8];\n"
        "add.u32 t, rp, %4;\n"
        "ld.shared.u32 em, [t+16];\n"
        "ld.shared.u32 ey, [t+-36];\n"
        "ld.shared.u32 cu, [rp+48];\n"
        "setp.eq.u32 e, sa, sa;\n"
        "setp.lt.u32 q, rp, rlast;\n"
        "@!q bra.uni PF_%=;\n"
        "PL_%=:\n"
        "and.b32 t, em, 0xfffffff8;\n"
        "mad.wide.u32 pa, t, 4, %1;\n"
        "and.b32 t, w, 0xffff;\n"
        "mad.wide.u32 pc, t, 1024, %0;\n"
        "shr.u32 t, w, 16;\n"
        "mad.wide.u32 pd, t, 1024, %0;\n"
        "mov.u32 u, %%clock;\n"
        "shl.b32 u, u, 14;\n"
        "sub.u32 u, u, cu;\n"
        "setp.ge.and.s32 q, u, 0, e;\n"
        "@q bra.uni PGO_%=;\n"
        "mov.u32 n, 0;\n"
        "PW1_%=:\n"
        "@e bra.uni PW2_%=;\n"
        "mbarrier.try_wait.parity.shared.b64 e, [sa+8712], ph;\n"
        "add.u32 n, n, 1;\n"
        "setp.lt.u32 q, n, 4194304;\n"
        "@q bra.uni PW1_%=;\n"
        "trap;\n"
        "PW2_%=:\n"
        "mov.u32 u, %%clock;\n"
        "shl.b32 u, u, 14;\n"
        "sub.u32 u, u, cu;\n"
        "setp.lt.s32 q, u, 0;\n"
        "@q bra.uni PW2_%=;\n"
        "PGO_%=:\n"
        "add.u32 d, sa, %3;\n"
        "@lo cp.async.cg.shared.global [d+2048], [pa], 16;\n"
        "xor.b32 t, ey, %5;\n"
        "and.b32 t, t, 7;\n"
        "setp.ne.u32 zb, t, 0;\n"
        "and.b32 t, ey, 0xfffffff8;\n"
        "cvt.u64.u32 pb, t;\n"
        "add.u64 pb, pb, %2;\n"
        "selp.u32 dy, 64, 8, lo;\n"
        "xor.b32 dy, dy, d;\n"
        "cp.async.ca.shared.global [dy+2048], [pb], 8, zb;\n"
        "add.u32 d, sa, %13;\n"
        "cp.async.cg.shared.global [d+0], [pc+0], 16;\n"
        "cp.async.cg.shared.global [d+256], [pc+256], 16;\n"
        "cp.async.cg.shared.global [d+512], [pc+512], 16;\n"
        "cp.async.cg.shared.global [d+768], [pc+768], 16;\n"
        "cp.async.cg.shared.global [d+1024], [pd+0], 16;\n"
        "cp.async.cg.shared.global [d+1280], [pd+256], 16;\n"
        "cp.async.cg.shared.global [d+1536], [pd+512], 16;\n"
        "cp.async.cg.shared.global [d+1792], [pd+768], 16;\n"
        "xor.b32 dy, d, 64;\n"
        "and.b32 t, w2, 0xffff;\n"
        "mad.wide.u32 pa, t, 1024, %0;\n"
        "cp.async.cg.shared.global [dy+4352], [pa+0], 16;\n"
        "cp.async.cg.shared.global [dy+4608], [pa+256], 16;\n"
        "cp.async.cg.shared.global [dy+4864], [pa+512], 16;\n"
        "cp.async.cg.shared.global [dy+5120], [pa+768], 16;\n"
        "shr.u32 t, w2, 16;\n"
        "mad.wide.u32 pb, t, 1024, %0;\n"
        "cp.async.cg.shared.global [dy+5376], [pb+0], 16;\n"
        "cp.async.cg.shared.global [dy+5632], [pb+256], 16;\n"
        "cp.async.cg.shared.global [dy+5888], [pb+512], 16;\n"
        "cp.async.cg.shared.global [dy+6144], [pb+768], 16;\n"
        "add.u32 rp, rp, 104;\n"
        "shr.u32 t, %4, 1;\n"
        "and.b32 t, t, 4;\n"
        "add.u32 t, t, rp;\n"
        "ld.shared.u32 w, [t];\n"
        "ld.shared.u32 w2, [t+8];\n"
        "add.u32 t, rp, %4;\n"
        "ld.shared.u32 em, [t+16];\n"
        "ld.shared.u32 ey, [t+-36];\n"
        "ld.shared.u32 cu, [rp+48];\n"
        "cp.async.mbarrier.arrive.noinc.shared.b64 [sa+8704];\n"
        "add.u32 sa, sa, 17664;\n"
        "sub.u32 t, sa, 44160;\n"
        "setp.ge.u32 q, sa, rend;\n"
        "selp.u32 sa, t, sa, q;\n"
        "selp.u32 t, 1, 0, q;\n"
        "xor.b32 ph, ph, t;\n"
        "mbarrier.try_wait.parity.shared.b64 e, [sa+8712], ph;\n"
        "setp.lt.u32 q, rp, rlast;\n"
        "@q bra.uni PL_%=;\n"
        "PF_%=:\n"
        "setp.ne.u32 q, rp, rlast;\n"
        "@q bra.uni PX_%=;\n"
        "mov.u32 n, 0;\n"
        "PE1_%=:\n"
        "@e bra.uni PE2_%=;\n"
        "mbarrier.try_wait.parity.shared.b64 e, [sa+8712], ph;\n"
        "add.u32 n, n, 1;\n"
        "setp.lt.u32 q, n, 4194304;\n"
        "@q bra.uni PE1_%=;\n"
        "trap;\n"
        "PE2_%=:\n"
        "cp.async.mbarrier.arrive.noinc.shared.b64 [sa+8704];\n"
        "PX_%=:\n"
        "}\n"
        ::"l"(xl), "l"(efl), "l"(Y), "r"(xd), "r"(oef), "r"(ysel), "r"(ring), "r"(rec), "r"(rlast), "r"(odd),
          "l"(g_lag), "r"(lead), "r"(lag), "r"(xh) : "memory");
}

__device__ __forceinline__ void consumer_loop(float (&acc)[5][4][2][4], const uint32_t (&wf)[4][4], const uint32_t (&cgf)[4],
                                              uint32_t xoff, uint32_t& ring, uint32_t moff, uint32_t rec) {
    asm volatile(
        "{\n"
        ".reg .b32 x<16>, a<4>, b<4>, r<4>, m<4>, rl, rh, tag, la, lb, sa, last, ph, tq, xa, ma, n, ring, sn, ln, yb, zz, k<4>, tp;\n"
        ".reg .b16 lo, hi;\n"
        ".reg .f32 p<16>, d<4>, t0, t1, fz;\n"
        ".reg .pred q, w, el, c<5>;\n"
        "TA_%=: .branchtargets A0_%=, A1_%=, A2_%=, A3_%=, A4_%=, EXIT_%=;\n"
        "TB_%=: .branchtargets B0_%=, B1_%=, B2_%=, B3_%=, B4_%=, SPIN_%=;\n"
        "mov.f32 fz, 0f00000000;\n"
        "redux.sync.or.b32 ring, %160, 0xffffffff;\n"
        "mov.u32 sa, ring;\n"
        "add.u32 last, ring, 35328;\n"
        "mov.u32 ph, 0;\n"
        "redux.sync.xor.b32 zz, %160, 0xffffffff;\n"
        "redux.sync.or.b32 tp, %183, 0xffffffff;\n"
        "elect.sync _|el, 0xffffffff;\n"
        "mov.u32 k0, sa;\n"
        "mov.u32 k1, sa;\n"
        "mov.u32 k2, sa;\n"
        "mov.u32 k3, sa;\n"
        "mov.b32 x0, 0;\n"
        "mov.b32 x1, 0;\n"
        "mov.b32 x2, 0;\n"
        "mov.b32 x3, 0;\n"
        "mov.b32 x4, 0;\n"
        "mov.b32 x5, 0;\n"
        "mov.b32 x6, 0;\n"
        "mov.b32 x7, 0;\n"
        "mov.b32 x8, 0;\n"
        "mov.b32 x9, 0;\n"
        "mov.b32 x10, 0;\n"
        "mov.b32 x11, 0;\n"
        "mov.b32 x12, 0;\n"
        "mov.b32 x13, 0;\n"
        "mov.b32 x14, 0;\n"
        "mov.b32 x15, 0;\n"
        "mov.b32 b0, 0;\n"
        "mov.b32 r0, 0;\n"
        "mov.b32 b1, 0;\n"
        "mov.b32 r1, 0;\n"
        "mov.b32 b2, 0;\n"
        "mov.b32 r2, 0;\n"
        "mov.b32 b3, 0;\n"
        "mov.b32 r3, 0;\n"
        "mov.u32 lb, 0;\n"
        "mov.u32 n, 0;\n"
        "W0_%=:\n"
        "mbarrier.try_wait.parity.shared.b64 w, [sa+8704], 0;\n"
        "@w bra.uni W0D_%=;\n"
        "add.u32 n, n, 1;\n"
        "setp.lt.u32 q, n, 4194304;\n"
        "@q bra.uni W0_%=;\n"
        "trap;\n"
        "W0D_%=:\n"
        "add.u32 ma, sa, %182;\n"
        "ldmatrix.sync.aligned.m8n8.x4.shared.b16 {m0,m1,m2,m3}, [ma];\n"
        "ld.shared.u16 tag, [tp+48];\n"
        "add.u32 tp, tp, 52;\n"
        "add.u32 sn, sa, 8832;\n"
        "setp.eq.u32 q, sa, last;\n"
        "selp.u32 sn, ring, sn, q;\n"
        "selp.u32 tq, 1, 0, q;\n"
        "xor.b32 ph, ph, tq;\n"
        "mbarrier.test_wait.parity.shared.b64 w, [sn+8704], ph;\n"
        "mma.sync.aligned.m16n8k16.row.col.f32.bf16.bf16.f32 {p0,p1,p2,p3}, {%161,%162,%163,%164}, {m2,m3}, {fz,fz,fz,fz};\n"
        "mma.sync.aligned.m16n8k16.row.col.f32.bf16.bf16.f32 {p4,p5,p6,p7}, {%165,%166,%167,%168}, {m2,m3}, {fz,fz,fz,fz};\n"
        "mma.sync.aligned.m16n8k16.row.col.f32.bf16.bf16.f32 {p8,p9,p10,p11}, {%169,%170,%171,%172}, {m2,m3}, {fz,fz,fz,fz};\n"
        "mma.sync.aligned.m16n8k16.row.col.f32.bf16.bf16.f32 {p12,p13,p14,p15}, {%173,%174,%175,%176}, {m2,m3}, {fz,fz,fz,fz};\n"
        "@el mbarrier.arrive.shared.b64 _, [k0+8712];\n"
        "redux.sync.or.b32 ln, tag, 0xffffffff;\n"
        "mov.u32 sa, sn;\n"
        "add.u32 k0, sn, zz;\n"
        "SPIN_%=:\n"
        "mov.u32 n, 0;\n"
        "SP1_%=:\n"
        "mbarrier.try_wait.parity.shared.b64 w, [sa+8704], ph;\n"
        "@w bra.uni SP2_%=;\n"
        "add.u32 n, n, 1;\n"
        "setp.lt.u32 q, n, 4194304;\n"
        "@q bra.uni SP1_%=;\n"
        "trap;\n"
        "SP2_%=:\n"
        "brx.idx.uni lb, TB_%=;\n"
        "A0_%=:\n"
        "add.u32 xa, sa, %181;\n"
        "add.u32 ma, sa, %182;\n"
        "ldmatrix.sync.aligned.m8n8.x4.shared.b16 {m0,m1,m2,m3}, [ma];\n"
        "ld.shared.u16 tag, [tp+48];\n"
        "add.u32 tp, tp, 52;\n"
        "add.u32 sn, sa, 8832;\n"
        "setp.eq.u32 q, sa, last;\n"
        "selp.u32 sn, ring, sn, q;\n"
        "selp.u32 tq, 1, 0, q;\n"
        "xor.b32 ph, ph, tq;\n"
        "mbarrier.test_wait.parity.shared.b64 w, [sn+8704], ph;\n"
        "mma.sync.aligned.m16n8k16.row.col.f32.bf16.bf16.f32 {%0,%1,%2,%3}, {a0,a1,a2,a3}, {x0,x1}, {%0,%1,%2,%3};\n"
        "mma.sync.aligned.m16n8k16.row.col.f32.bf16.bf16.f32 {%4,%5,%6,%7}, {a0,a1,a2,a3}, {x2,x3}, {%4,%5,%6,%7};\n"
        "ld.shared.v4.u32 {x0,x1,x2,x3}, [xa+1024];\n"
        "tanh.approx.f32 t0, p1;\n"
        "tanh.approx.f32 t1, p3;\n"
        "fma.rn.f32 t0, p1, t0, p1;\n"
        "fma.rn.f32 t1, p3, t1, p3;\n"
        "cvt.rn.bf16x2.f32 r0, t1, t0;\n"
        "mma.sync.aligned.m16n8k16.row.col.f32.bf16.bf16.f32 {p0,p1,p2,p3}, {%161,%162,%163,%164}, {m2,m3}, {fz,fz,fz,fz};\n"
        "mma.sync.aligned.m16n8k16.row.col.f32.bf16.bf16.f32 {%8,%9,%10,%11}, {a0,a1,a2,a3}, {x4,x5}, {%8,%9,%10,%11};\n"
        "mma.sync.aligned.m16n8k16.row.col.f32.bf16.bf16.f32 {%12,%13,%14,%15}, {a0,a1,a2,a3}, {x6,x7}, {%12,%13,%14,%15};\n"
        "ld.shared.v4.u32 {x4,x5,x6,x7}, [xa+1152];\n"
        "mma.sync.aligned.m16n8k8.row.col.f32.bf16.bf16.f32 {d0,d1,d2,d3}, {%177,%178}, {m1}, {fz,fz,fz,fz};\n"
        "cvt.rn.bf16x2.f32 b0, d2, d0;\n"
        "cvt.rn.bf16x2.f32 b1, d3, d1;\n"
        "tanh.approx.f32 t0, p5;\n"
        "tanh.approx.f32 t1, p7;\n"
        "fma.rn.f32 t0, p5, t0, p5;\n"
        "fma.rn.f32 t1, p7, t1, p7;\n"
        "cvt.rn.bf16x2.f32 r1, t1, t0;\n"
        "mma.sync.aligned.m16n8k16.row.col.f32.bf16.bf16.f32 {p4,p5,p6,p7}, {%165,%166,%167,%168}, {m2,m3}, {fz,fz,fz,fz};\n"
        "mov.b32 {lo,hi}, r2;\n"
        "mov.b32 rl, {lo,lo};\n"
        "mov.b32 rh, {hi,hi};\n"
        "mul.bf16x2 x8, x8, rl;\n"
        "mul.bf16x2 x9, x9, rl;\n"
        "mul.bf16x2 x10, x10, rh;\n"
        "mul.bf16x2 x11, x11, rh;\n"
        "mma.sync.aligned.m16n8k16.row.col.f32.bf16.bf16.f32 {%16,%17,%18,%19}, {a0,a1,a2,a3}, {x8,x9}, {%16,%17,%18,%19};\n"
        "mma.sync.aligned.m16n8k16.row.col.f32.bf16.bf16.f32 {%20,%21,%22,%23}, {a0,a1,a2,a3}, {x10,x11}, {%20,%21,%22,%23};\n"
        "ld.shared.v4.u32 {x8,x9,x10,x11}, [xa+1280];\n"
        "mma.sync.aligned.m16n8k8.row.col.f32.bf16.bf16.f32 {d0,d1,d2,d3}, {%179,%180}, {m1}, {fz,fz,fz,fz};\n"
        "cvt.rn.bf16x2.f32 b2, d2, d0;\n"
        "cvt.rn.bf16x2.f32 b3, d3, d1;\n"
        "tanh.approx.f32 t0, p9;\n"
        "tanh.approx.f32 t1, p11;\n"
        "fma.rn.f32 t0, p9, t0, p9;\n"
        "fma.rn.f32 t1, p11, t1, p11;\n"
        "cvt.rn.bf16x2.f32 r2, t1, t0;\n"
        "mma.sync.aligned.m16n8k16.row.col.f32.bf16.bf16.f32 {p8,p9,p10,p11}, {%169,%170,%171,%172}, {m2,m3}, {fz,fz,fz,fz};\n"
        "selp.u32 tq, lb, 5, w;\n"
        "mov.b32 {lo,hi}, r3;\n"
        "mov.b32 rl, {lo,lo};\n"
        "mov.b32 rh, {hi,hi};\n"
        "mul.bf16x2 x12, x12, rl;\n"
        "mul.bf16x2 x13, x13, rl;\n"
        "mul.bf16x2 x14, x14, rh;\n"
        "mul.bf16x2 x15, x15, rh;\n"
        "mma.sync.aligned.m16n8k16.row.col.f32.bf16.bf16.f32 {%24,%25,%26,%27}, {a0,a1,a2,a3}, {x12,x13}, {%24,%25,%26,%27};\n"
        "mma.sync.aligned.m16n8k16.row.col.f32.bf16.bf16.f32 {%28,%29,%30,%31}, {a0,a1,a2,a3}, {x14,x15}, {%28,%29,%30,%31};\n"
        "ld.shared.v4.u32 {x12,x13,x14,x15}, [xa+1408];\n"
        "@el mbarrier.arrive.shared.b64 _, [k0+8712];\n"
        "redux.sync.or.b32 ln, tag, 0xffffffff;\n"
        "mov.u32 sa, sn;\n"
        "add.u32 k0, sn, zz;\n"
        "tanh.approx.f32 t0, p13;\n"
        "tanh.approx.f32 t1, p15;\n"
        "fma.rn.f32 t0, p13, t0, p13;\n"
        "fma.rn.f32 t1, p15, t1, p15;\n"
        "cvt.rn.bf16x2.f32 r3, t1, t0;\n"
        "mma.sync.aligned.m16n8k16.row.col.f32.bf16.bf16.f32 {p12,p13,p14,p15}, {%173,%174,%175,%176}, {m2,m3}, {fz,fz,fz,fz};\n"
        "mov.b32 {lo,hi}, r0;\n"
        "mov.b32 rl, {lo,lo};\n"
        "mov.b32 rh, {hi,hi};\n"
        "mul.bf16x2 x0, x0, rl;\n"
        "mul.bf16x2 x1, x1, rl;\n"
        "mul.bf16x2 x2, x2, rh;\n"
        "mul.bf16x2 x3, x3, rh;\n"
        "mov.b32 {lo,hi}, r1;\n"
        "mov.b32 rl, {lo,lo};\n"
        "mov.b32 rh, {hi,hi};\n"
        "mul.bf16x2 x4, x4, rl;\n"
        "mul.bf16x2 x5, x5, rl;\n"
        "mul.bf16x2 x6, x6, rh;\n"
        "mul.bf16x2 x7, x7, rh;\n"
        "brx.idx.uni tq, TB_%=;\n"
        "A1_%=:\n"
        "add.u32 xa, sa, %181;\n"
        "add.u32 ma, sa, %182;\n"
        "ldmatrix.sync.aligned.m8n8.x4.shared.b16 {m0,m1,m2,m3}, [ma];\n"
        "ld.shared.u16 tag, [tp+48];\n"
        "add.u32 tp, tp, 52;\n"
        "add.u32 sn, sa, 8832;\n"
        "setp.eq.u32 q, sa, last;\n"
        "selp.u32 sn, ring, sn, q;\n"
        "selp.u32 tq, 1, 0, q;\n"
        "xor.b32 ph, ph, tq;\n"
        "mbarrier.test_wait.parity.shared.b64 w, [sn+8704], ph;\n"
        "mma.sync.aligned.m16n8k16.row.col.f32.bf16.bf16.f32 {%32,%33,%34,%35}, {a0,a1,a2,a3}, {x0,x1}, {%32,%33,%34,%35};\n"
        "mma.sync.aligned.m16n8k16.row.col.f32.bf16.bf16.f32 {%36,%37,%38,%39}, {a0,a1,a2,a3}, {x2,x3}, {%36,%37,%38,%39};\n"
        "ld.shared.v4.u32 {x0,x1,x2,x3}, [xa+1024];\n"
        "tanh.approx.f32 t0, p1;\n"
        "tanh.approx.f32 t1, p3;\n"
        "fma.rn.f32 t0, p1, t0, p1;\n"
        "fma.rn.f32 t1, p3, t1, p3;\n"
        "cvt.rn.bf16x2.f32 r0, t1, t0;\n"
        "mma.sync.aligned.m16n8k16.row.col.f32.bf16.bf16.f32 {p0,p1,p2,p3}, {%161,%162,%163,%164}, {m2,m3}, {fz,fz,fz,fz};\n"
        "mma.sync.aligned.m16n8k16.row.col.f32.bf16.bf16.f32 {%40,%41,%42,%43}, {a0,a1,a2,a3}, {x4,x5}, {%40,%41,%42,%43};\n"
        "mma.sync.aligned.m16n8k16.row.col.f32.bf16.bf16.f32 {%44,%45,%46,%47}, {a0,a1,a2,a3}, {x6,x7}, {%44,%45,%46,%47};\n"
        "ld.shared.v4.u32 {x4,x5,x6,x7}, [xa+1152];\n"
        "mma.sync.aligned.m16n8k8.row.col.f32.bf16.bf16.f32 {d0,d1,d2,d3}, {%177,%178}, {m1}, {fz,fz,fz,fz};\n"
        "cvt.rn.bf16x2.f32 b0, d2, d0;\n"
        "cvt.rn.bf16x2.f32 b1, d3, d1;\n"
        "tanh.approx.f32 t0, p5;\n"
        "tanh.approx.f32 t1, p7;\n"
        "fma.rn.f32 t0, p5, t0, p5;\n"
        "fma.rn.f32 t1, p7, t1, p7;\n"
        "cvt.rn.bf16x2.f32 r1, t1, t0;\n"
        "mma.sync.aligned.m16n8k16.row.col.f32.bf16.bf16.f32 {p4,p5,p6,p7}, {%165,%166,%167,%168}, {m2,m3}, {fz,fz,fz,fz};\n"
        "mov.b32 {lo,hi}, r2;\n"
        "mov.b32 rl, {lo,lo};\n"
        "mov.b32 rh, {hi,hi};\n"
        "mul.bf16x2 x8, x8, rl;\n"
        "mul.bf16x2 x9, x9, rl;\n"
        "mul.bf16x2 x10, x10, rh;\n"
        "mul.bf16x2 x11, x11, rh;\n"
        "mma.sync.aligned.m16n8k16.row.col.f32.bf16.bf16.f32 {%48,%49,%50,%51}, {a0,a1,a2,a3}, {x8,x9}, {%48,%49,%50,%51};\n"
        "mma.sync.aligned.m16n8k16.row.col.f32.bf16.bf16.f32 {%52,%53,%54,%55}, {a0,a1,a2,a3}, {x10,x11}, {%52,%53,%54,%55};\n"
        "ld.shared.v4.u32 {x8,x9,x10,x11}, [xa+1280];\n"
        "mma.sync.aligned.m16n8k8.row.col.f32.bf16.bf16.f32 {d0,d1,d2,d3}, {%179,%180}, {m1}, {fz,fz,fz,fz};\n"
        "cvt.rn.bf16x2.f32 b2, d2, d0;\n"
        "cvt.rn.bf16x2.f32 b3, d3, d1;\n"
        "tanh.approx.f32 t0, p9;\n"
        "tanh.approx.f32 t1, p11;\n"
        "fma.rn.f32 t0, p9, t0, p9;\n"
        "fma.rn.f32 t1, p11, t1, p11;\n"
        "cvt.rn.bf16x2.f32 r2, t1, t0;\n"
        "mma.sync.aligned.m16n8k16.row.col.f32.bf16.bf16.f32 {p8,p9,p10,p11}, {%169,%170,%171,%172}, {m2,m3}, {fz,fz,fz,fz};\n"
        "selp.u32 tq, lb, 5, w;\n"
        "mov.b32 {lo,hi}, r3;\n"
        "mov.b32 rl, {lo,lo};\n"
        "mov.b32 rh, {hi,hi};\n"
        "mul.bf16x2 x12, x12, rl;\n"
        "mul.bf16x2 x13, x13, rl;\n"
        "mul.bf16x2 x14, x14, rh;\n"
        "mul.bf16x2 x15, x15, rh;\n"
        "mma.sync.aligned.m16n8k16.row.col.f32.bf16.bf16.f32 {%56,%57,%58,%59}, {a0,a1,a2,a3}, {x12,x13}, {%56,%57,%58,%59};\n"
        "mma.sync.aligned.m16n8k16.row.col.f32.bf16.bf16.f32 {%60,%61,%62,%63}, {a0,a1,a2,a3}, {x14,x15}, {%60,%61,%62,%63};\n"
        "ld.shared.v4.u32 {x12,x13,x14,x15}, [xa+1408];\n"
        "@el mbarrier.arrive.shared.b64 _, [k0+8712];\n"
        "redux.sync.or.b32 ln, tag, 0xffffffff;\n"
        "mov.u32 sa, sn;\n"
        "add.u32 k0, sn, zz;\n"
        "tanh.approx.f32 t0, p13;\n"
        "tanh.approx.f32 t1, p15;\n"
        "fma.rn.f32 t0, p13, t0, p13;\n"
        "fma.rn.f32 t1, p15, t1, p15;\n"
        "cvt.rn.bf16x2.f32 r3, t1, t0;\n"
        "mma.sync.aligned.m16n8k16.row.col.f32.bf16.bf16.f32 {p12,p13,p14,p15}, {%173,%174,%175,%176}, {m2,m3}, {fz,fz,fz,fz};\n"
        "mov.b32 {lo,hi}, r0;\n"
        "mov.b32 rl, {lo,lo};\n"
        "mov.b32 rh, {hi,hi};\n"
        "mul.bf16x2 x0, x0, rl;\n"
        "mul.bf16x2 x1, x1, rl;\n"
        "mul.bf16x2 x2, x2, rh;\n"
        "mul.bf16x2 x3, x3, rh;\n"
        "mov.b32 {lo,hi}, r1;\n"
        "mov.b32 rl, {lo,lo};\n"
        "mov.b32 rh, {hi,hi};\n"
        "mul.bf16x2 x4, x4, rl;\n"
        "mul.bf16x2 x5, x5, rl;\n"
        "mul.bf16x2 x6, x6, rh;\n"
        "mul.bf16x2 x7, x7, rh;\n"
        "brx.idx.uni tq, TB_%=;\n"
        "A2_%=:\n"
        "add.u32 xa, sa, %181;\n"
        "add.u32 ma, sa, %182;\n"
        "ldmatrix.sync.aligned.m8n8.x4.shared.b16 {m0,m1,m2,m3}, [ma];\n"
        "ld.shared.u16 tag, [tp+48];\n"
        "add.u32 tp, tp, 52;\n"
        "add.u32 sn, sa, 8832;\n"
        "setp.eq.u32 q, sa, last;\n"
        "selp.u32 sn, ring, sn, q;\n"
        "selp.u32 tq, 1, 0, q;\n"
        "xor.b32 ph, ph, tq;\n"
        "mbarrier.test_wait.parity.shared.b64 w, [sn+8704], ph;\n"
        "mma.sync.aligned.m16n8k16.row.col.f32.bf16.bf16.f32 {%64,%65,%66,%67}, {a0,a1,a2,a3}, {x0,x1}, {%64,%65,%66,%67};\n"
        "mma.sync.aligned.m16n8k16.row.col.f32.bf16.bf16.f32 {%68,%69,%70,%71}, {a0,a1,a2,a3}, {x2,x3}, {%68,%69,%70,%71};\n"
        "ld.shared.v4.u32 {x0,x1,x2,x3}, [xa+1024];\n"
        "tanh.approx.f32 t0, p1;\n"
        "tanh.approx.f32 t1, p3;\n"
        "fma.rn.f32 t0, p1, t0, p1;\n"
        "fma.rn.f32 t1, p3, t1, p3;\n"
        "cvt.rn.bf16x2.f32 r0, t1, t0;\n"
        "mma.sync.aligned.m16n8k16.row.col.f32.bf16.bf16.f32 {p0,p1,p2,p3}, {%161,%162,%163,%164}, {m2,m3}, {fz,fz,fz,fz};\n"
        "mma.sync.aligned.m16n8k16.row.col.f32.bf16.bf16.f32 {%72,%73,%74,%75}, {a0,a1,a2,a3}, {x4,x5}, {%72,%73,%74,%75};\n"
        "mma.sync.aligned.m16n8k16.row.col.f32.bf16.bf16.f32 {%76,%77,%78,%79}, {a0,a1,a2,a3}, {x6,x7}, {%76,%77,%78,%79};\n"
        "ld.shared.v4.u32 {x4,x5,x6,x7}, [xa+1152];\n"
        "mma.sync.aligned.m16n8k8.row.col.f32.bf16.bf16.f32 {d0,d1,d2,d3}, {%177,%178}, {m1}, {fz,fz,fz,fz};\n"
        "cvt.rn.bf16x2.f32 b0, d2, d0;\n"
        "cvt.rn.bf16x2.f32 b1, d3, d1;\n"
        "tanh.approx.f32 t0, p5;\n"
        "tanh.approx.f32 t1, p7;\n"
        "fma.rn.f32 t0, p5, t0, p5;\n"
        "fma.rn.f32 t1, p7, t1, p7;\n"
        "cvt.rn.bf16x2.f32 r1, t1, t0;\n"
        "mma.sync.aligned.m16n8k16.row.col.f32.bf16.bf16.f32 {p4,p5,p6,p7}, {%165,%166,%167,%168}, {m2,m3}, {fz,fz,fz,fz};\n"
        "mov.b32 {lo,hi}, r2;\n"
        "mov.b32 rl, {lo,lo};\n"
        "mov.b32 rh, {hi,hi};\n"
        "mul.bf16x2 x8, x8, rl;\n"
        "mul.bf16x2 x9, x9, rl;\n"
        "mul.bf16x2 x10, x10, rh;\n"
        "mul.bf16x2 x11, x11, rh;\n"
        "mma.sync.aligned.m16n8k16.row.col.f32.bf16.bf16.f32 {%80,%81,%82,%83}, {a0,a1,a2,a3}, {x8,x9}, {%80,%81,%82,%83};\n"
        "mma.sync.aligned.m16n8k16.row.col.f32.bf16.bf16.f32 {%84,%85,%86,%87}, {a0,a1,a2,a3}, {x10,x11}, {%84,%85,%86,%87};\n"
        "ld.shared.v4.u32 {x8,x9,x10,x11}, [xa+1280];\n"
        "mma.sync.aligned.m16n8k8.row.col.f32.bf16.bf16.f32 {d0,d1,d2,d3}, {%179,%180}, {m1}, {fz,fz,fz,fz};\n"
        "cvt.rn.bf16x2.f32 b2, d2, d0;\n"
        "cvt.rn.bf16x2.f32 b3, d3, d1;\n"
        "tanh.approx.f32 t0, p9;\n"
        "tanh.approx.f32 t1, p11;\n"
        "fma.rn.f32 t0, p9, t0, p9;\n"
        "fma.rn.f32 t1, p11, t1, p11;\n"
        "cvt.rn.bf16x2.f32 r2, t1, t0;\n"
        "mma.sync.aligned.m16n8k16.row.col.f32.bf16.bf16.f32 {p8,p9,p10,p11}, {%169,%170,%171,%172}, {m2,m3}, {fz,fz,fz,fz};\n"
        "selp.u32 tq, lb, 5, w;\n"
        "mov.b32 {lo,hi}, r3;\n"
        "mov.b32 rl, {lo,lo};\n"
        "mov.b32 rh, {hi,hi};\n"
        "mul.bf16x2 x12, x12, rl;\n"
        "mul.bf16x2 x13, x13, rl;\n"
        "mul.bf16x2 x14, x14, rh;\n"
        "mul.bf16x2 x15, x15, rh;\n"
        "mma.sync.aligned.m16n8k16.row.col.f32.bf16.bf16.f32 {%88,%89,%90,%91}, {a0,a1,a2,a3}, {x12,x13}, {%88,%89,%90,%91};\n"
        "mma.sync.aligned.m16n8k16.row.col.f32.bf16.bf16.f32 {%92,%93,%94,%95}, {a0,a1,a2,a3}, {x14,x15}, {%92,%93,%94,%95};\n"
        "ld.shared.v4.u32 {x12,x13,x14,x15}, [xa+1408];\n"
        "@el mbarrier.arrive.shared.b64 _, [k0+8712];\n"
        "redux.sync.or.b32 ln, tag, 0xffffffff;\n"
        "mov.u32 sa, sn;\n"
        "add.u32 k0, sn, zz;\n"
        "tanh.approx.f32 t0, p13;\n"
        "tanh.approx.f32 t1, p15;\n"
        "fma.rn.f32 t0, p13, t0, p13;\n"
        "fma.rn.f32 t1, p15, t1, p15;\n"
        "cvt.rn.bf16x2.f32 r3, t1, t0;\n"
        "mma.sync.aligned.m16n8k16.row.col.f32.bf16.bf16.f32 {p12,p13,p14,p15}, {%173,%174,%175,%176}, {m2,m3}, {fz,fz,fz,fz};\n"
        "mov.b32 {lo,hi}, r0;\n"
        "mov.b32 rl, {lo,lo};\n"
        "mov.b32 rh, {hi,hi};\n"
        "mul.bf16x2 x0, x0, rl;\n"
        "mul.bf16x2 x1, x1, rl;\n"
        "mul.bf16x2 x2, x2, rh;\n"
        "mul.bf16x2 x3, x3, rh;\n"
        "mov.b32 {lo,hi}, r1;\n"
        "mov.b32 rl, {lo,lo};\n"
        "mov.b32 rh, {hi,hi};\n"
        "mul.bf16x2 x4, x4, rl;\n"
        "mul.bf16x2 x5, x5, rl;\n"
        "mul.bf16x2 x6, x6, rh;\n"
        "mul.bf16x2 x7, x7, rh;\n"
        "brx.idx.uni tq, TB_%=;\n"
        "A3_%=:\n"
        "add.u32 xa, sa, %181;\n"
        "add.u32 ma, sa, %182;\n"
        "ldmatrix.sync.aligned.m8n8.x4.shared.b16 {m0,m1,m2,m3}, [ma];\n"
        "ld.shared.u16 tag, [tp+48];\n"
        "add.u32 tp, tp, 52;\n"
        "add.u32 sn, sa, 8832;\n"
        "setp.eq.u32 q, sa, last;\n"
        "selp.u32 sn, ring, sn, q;\n"
        "selp.u32 tq, 1, 0, q;\n"
        "xor.b32 ph, ph, tq;\n"
        "mbarrier.test_wait.parity.shared.b64 w, [sn+8704], ph;\n"
        "mma.sync.aligned.m16n8k16.row.col.f32.bf16.bf16.f32 {%96,%97,%98,%99}, {a0,a1,a2,a3}, {x0,x1}, {%96,%97,%98,%99};\n"
        "mma.sync.aligned.m16n8k16.row.col.f32.bf16.bf16.f32 {%100,%101,%102,%103}, {a0,a1,a2,a3}, {x2,x3}, {%100,%101,%102,%103};\n"
        "ld.shared.v4.u32 {x0,x1,x2,x3}, [xa+1024];\n"
        "tanh.approx.f32 t0, p1;\n"
        "tanh.approx.f32 t1, p3;\n"
        "fma.rn.f32 t0, p1, t0, p1;\n"
        "fma.rn.f32 t1, p3, t1, p3;\n"
        "cvt.rn.bf16x2.f32 r0, t1, t0;\n"
        "mma.sync.aligned.m16n8k16.row.col.f32.bf16.bf16.f32 {p0,p1,p2,p3}, {%161,%162,%163,%164}, {m2,m3}, {fz,fz,fz,fz};\n"
        "mma.sync.aligned.m16n8k16.row.col.f32.bf16.bf16.f32 {%104,%105,%106,%107}, {a0,a1,a2,a3}, {x4,x5}, {%104,%105,%106,%107};\n"
        "mma.sync.aligned.m16n8k16.row.col.f32.bf16.bf16.f32 {%108,%109,%110,%111}, {a0,a1,a2,a3}, {x6,x7}, {%108,%109,%110,%111};\n"
        "ld.shared.v4.u32 {x4,x5,x6,x7}, [xa+1152];\n"
        "mma.sync.aligned.m16n8k8.row.col.f32.bf16.bf16.f32 {d0,d1,d2,d3}, {%177,%178}, {m1}, {fz,fz,fz,fz};\n"
        "cvt.rn.bf16x2.f32 b0, d2, d0;\n"
        "cvt.rn.bf16x2.f32 b1, d3, d1;\n"
        "tanh.approx.f32 t0, p5;\n"
        "tanh.approx.f32 t1, p7;\n"
        "fma.rn.f32 t0, p5, t0, p5;\n"
        "fma.rn.f32 t1, p7, t1, p7;\n"
        "cvt.rn.bf16x2.f32 r1, t1, t0;\n"
        "mma.sync.aligned.m16n8k16.row.col.f32.bf16.bf16.f32 {p4,p5,p6,p7}, {%165,%166,%167,%168}, {m2,m3}, {fz,fz,fz,fz};\n"
        "mov.b32 {lo,hi}, r2;\n"
        "mov.b32 rl, {lo,lo};\n"
        "mov.b32 rh, {hi,hi};\n"
        "mul.bf16x2 x8, x8, rl;\n"
        "mul.bf16x2 x9, x9, rl;\n"
        "mul.bf16x2 x10, x10, rh;\n"
        "mul.bf16x2 x11, x11, rh;\n"
        "mma.sync.aligned.m16n8k16.row.col.f32.bf16.bf16.f32 {%112,%113,%114,%115}, {a0,a1,a2,a3}, {x8,x9}, {%112,%113,%114,%115};\n"
        "mma.sync.aligned.m16n8k16.row.col.f32.bf16.bf16.f32 {%116,%117,%118,%119}, {a0,a1,a2,a3}, {x10,x11}, {%116,%117,%118,%119};\n"
        "ld.shared.v4.u32 {x8,x9,x10,x11}, [xa+1280];\n"
        "mma.sync.aligned.m16n8k8.row.col.f32.bf16.bf16.f32 {d0,d1,d2,d3}, {%179,%180}, {m1}, {fz,fz,fz,fz};\n"
        "cvt.rn.bf16x2.f32 b2, d2, d0;\n"
        "cvt.rn.bf16x2.f32 b3, d3, d1;\n"
        "tanh.approx.f32 t0, p9;\n"
        "tanh.approx.f32 t1, p11;\n"
        "fma.rn.f32 t0, p9, t0, p9;\n"
        "fma.rn.f32 t1, p11, t1, p11;\n"
        "cvt.rn.bf16x2.f32 r2, t1, t0;\n"
        "mma.sync.aligned.m16n8k16.row.col.f32.bf16.bf16.f32 {p8,p9,p10,p11}, {%169,%170,%171,%172}, {m2,m3}, {fz,fz,fz,fz};\n"
        "selp.u32 tq, lb, 5, w;\n"
        "mov.b32 {lo,hi}, r3;\n"
        "mov.b32 rl, {lo,lo};\n"
        "mov.b32 rh, {hi,hi};\n"
        "mul.bf16x2 x12, x12, rl;\n"
        "mul.bf16x2 x13, x13, rl;\n"
        "mul.bf16x2 x14, x14, rh;\n"
        "mul.bf16x2 x15, x15, rh;\n"
        "mma.sync.aligned.m16n8k16.row.col.f32.bf16.bf16.f32 {%120,%121,%122,%123}, {a0,a1,a2,a3}, {x12,x13}, {%120,%121,%122,%123};\n"
        "mma.sync.aligned.m16n8k16.row.col.f32.bf16.bf16.f32 {%124,%125,%126,%127}, {a0,a1,a2,a3}, {x14,x15}, {%124,%125,%126,%127};\n"
        "ld.shared.v4.u32 {x12,x13,x14,x15}, [xa+1408];\n"
        "@el mbarrier.arrive.shared.b64 _, [k0+8712];\n"
        "redux.sync.or.b32 ln, tag, 0xffffffff;\n"
        "mov.u32 sa, sn;\n"
        "add.u32 k0, sn, zz;\n"
        "tanh.approx.f32 t0, p13;\n"
        "tanh.approx.f32 t1, p15;\n"
        "fma.rn.f32 t0, p13, t0, p13;\n"
        "fma.rn.f32 t1, p15, t1, p15;\n"
        "cvt.rn.bf16x2.f32 r3, t1, t0;\n"
        "mma.sync.aligned.m16n8k16.row.col.f32.bf16.bf16.f32 {p12,p13,p14,p15}, {%173,%174,%175,%176}, {m2,m3}, {fz,fz,fz,fz};\n"
        "mov.b32 {lo,hi}, r0;\n"
        "mov.b32 rl, {lo,lo};\n"
        "mov.b32 rh, {hi,hi};\n"
        "mul.bf16x2 x0, x0, rl;\n"
        "mul.bf16x2 x1, x1, rl;\n"
        "mul.bf16x2 x2, x2, rh;\n"
        "mul.bf16x2 x3, x3, rh;\n"
        "mov.b32 {lo,hi}, r1;\n"
        "mov.b32 rl, {lo,lo};\n"
        "mov.b32 rh, {hi,hi};\n"
        "mul.bf16x2 x4, x4, rl;\n"
        "mul.bf16x2 x5, x5, rl;\n"
        "mul.bf16x2 x6, x6, rh;\n"
        "mul.bf16x2 x7, x7, rh;\n"
        "brx.idx.uni tq, TB_%=;\n"
        "A4_%=:\n"
        "add.u32 xa, sa, %181;\n"
        "add.u32 ma, sa, %182;\n"
        "ldmatrix.sync.aligned.m8n8.x4.shared.b16 {m0,m1,m2,m3}, [ma];\n"
        "ld.shared.u16 tag, [tp+48];\n"
        "add.u32 tp, tp, 52;\n"
        "add.u32 sn, sa, 8832;\n"
        "setp.eq.u32 q, sa, last;\n"
        "selp.u32 sn, ring, sn, q;\n"
        "selp.u32 tq, 1, 0, q;\n"
        "xor.b32 ph, ph, tq;\n"
        "mbarrier.test_wait.parity.shared.b64 w, [sn+8704], ph;\n"
        "mma.sync.aligned.m16n8k16.row.col.f32.bf16.bf16.f32 {%128,%129,%130,%131}, {a0,a1,a2,a3}, {x0,x1}, {%128,%129,%130,%131};\n"
        "mma.sync.aligned.m16n8k16.row.col.f32.bf16.bf16.f32 {%132,%133,%134,%135}, {a0,a1,a2,a3}, {x2,x3}, {%132,%133,%134,%135};\n"
        "ld.shared.v4.u32 {x0,x1,x2,x3}, [xa+1024];\n"
        "tanh.approx.f32 t0, p1;\n"
        "tanh.approx.f32 t1, p3;\n"
        "fma.rn.f32 t0, p1, t0, p1;\n"
        "fma.rn.f32 t1, p3, t1, p3;\n"
        "cvt.rn.bf16x2.f32 r0, t1, t0;\n"
        "mma.sync.aligned.m16n8k16.row.col.f32.bf16.bf16.f32 {p0,p1,p2,p3}, {%161,%162,%163,%164}, {m2,m3}, {fz,fz,fz,fz};\n"
        "mma.sync.aligned.m16n8k16.row.col.f32.bf16.bf16.f32 {%136,%137,%138,%139}, {a0,a1,a2,a3}, {x4,x5}, {%136,%137,%138,%139};\n"
        "mma.sync.aligned.m16n8k16.row.col.f32.bf16.bf16.f32 {%140,%141,%142,%143}, {a0,a1,a2,a3}, {x6,x7}, {%140,%141,%142,%143};\n"
        "ld.shared.v4.u32 {x4,x5,x6,x7}, [xa+1152];\n"
        "mma.sync.aligned.m16n8k8.row.col.f32.bf16.bf16.f32 {d0,d1,d2,d3}, {%177,%178}, {m1}, {fz,fz,fz,fz};\n"
        "cvt.rn.bf16x2.f32 b0, d2, d0;\n"
        "cvt.rn.bf16x2.f32 b1, d3, d1;\n"
        "tanh.approx.f32 t0, p5;\n"
        "tanh.approx.f32 t1, p7;\n"
        "fma.rn.f32 t0, p5, t0, p5;\n"
        "fma.rn.f32 t1, p7, t1, p7;\n"
        "cvt.rn.bf16x2.f32 r1, t1, t0;\n"
        "mma.sync.aligned.m16n8k16.row.col.f32.bf16.bf16.f32 {p4,p5,p6,p7}, {%165,%166,%167,%168}, {m2,m3}, {fz,fz,fz,fz};\n"
        "mov.b32 {lo,hi}, r2;\n"
        "mov.b32 rl, {lo,lo};\n"
        "mov.b32 rh, {hi,hi};\n"
        "mul.bf16x2 x8, x8, rl;\n"
        "mul.bf16x2 x9, x9, rl;\n"
        "mul.bf16x2 x10, x10, rh;\n"
        "mul.bf16x2 x11, x11, rh;\n"
        "mma.sync.aligned.m16n8k16.row.col.f32.bf16.bf16.f32 {%144,%145,%146,%147}, {a0,a1,a2,a3}, {x8,x9}, {%144,%145,%146,%147};\n"
        "mma.sync.aligned.m16n8k16.row.col.f32.bf16.bf16.f32 {%148,%149,%150,%151}, {a0,a1,a2,a3}, {x10,x11}, {%148,%149,%150,%151};\n"
        "ld.shared.v4.u32 {x8,x9,x10,x11}, [xa+1280];\n"
        "mma.sync.aligned.m16n8k8.row.col.f32.bf16.bf16.f32 {d0,d1,d2,d3}, {%179,%180}, {m1}, {fz,fz,fz,fz};\n"
        "cvt.rn.bf16x2.f32 b2, d2, d0;\n"
        "cvt.rn.bf16x2.f32 b3, d3, d1;\n"
        "tanh.approx.f32 t0, p9;\n"
        "tanh.approx.f32 t1, p11;\n"
        "fma.rn.f32 t0, p9, t0, p9;\n"
        "fma.rn.f32 t1, p11, t1, p11;\n"
        "cvt.rn.bf16x2.f32 r2, t1, t0;\n"
        "mma.sync.aligned.m16n8k16.row.col.f32.bf16.bf16.f32 {p8,p9,p10,p11}, {%169,%170,%171,%172}, {m2,m3}, {fz,fz,fz,fz};\n"
        "selp.u32 tq, lb, 5, w;\n"
        "mov.b32 {lo,hi}, r3;\n"
        "mov.b32 rl, {lo,lo};\n"
        "mov.b32 rh, {hi,hi};\n"
        "mul.bf16x2 x12, x12, rl;\n"
        "mul.bf16x2 x13, x13, rl;\n"
        "mul.bf16x2 x14, x14, rh;\n"
        "mul.bf16x2 x15, x15, rh;\n"
        "mma.sync.aligned.m16n8k16.row.col.f32.bf16.bf16.f32 {%152,%153,%154,%155}, {a0,a1,a2,a3}, {x12,x13}, {%152,%153,%154,%155};\n"
        "mma.sync.aligned.m16n8k16.row.col.f32.bf16.bf16.f32 {%156,%157,%158,%159}, {a0,a1,a2,a3}, {x14,x15}, {%156,%157,%158,%159};\n"
        "ld.shared.v4.u32 {x12,x13,x14,x15}, [xa+1408];\n"
        "@el mbarrier.arrive.shared.b64 _, [k0+8712];\n"
        "redux.sync.or.b32 ln, tag, 0xffffffff;\n"
        "mov.u32 sa, sn;\n"
        "add.u32 k0, sn, zz;\n"
        "tanh.approx.f32 t0, p13;\n"
        "tanh.approx.f32 t1, p15;\n"
        "fma.rn.f32 t0, p13, t0, p13;\n"
        "fma.rn.f32 t1, p15, t1, p15;\n"
        "cvt.rn.bf16x2.f32 r3, t1, t0;\n"
        "mma.sync.aligned.m16n8k16.row.col.f32.bf16.bf16.f32 {p12,p13,p14,p15}, {%173,%174,%175,%176}, {m2,m3}, {fz,fz,fz,fz};\n"
        "mov.b32 {lo,hi}, r0;\n"
        "mov.b32 rl, {lo,lo};\n"
        "mov.b32 rh, {hi,hi};\n"
        "mul.bf16x2 x0, x0, rl;\n"
        "mul.bf16x2 x1, x1, rl;\n"
        "mul.bf16x2 x2, x2, rh;\n"
        "mul.bf16x2 x3, x3, rh;\n"
        "mov.b32 {lo,hi}, r1;\n"
        "mov.b32 rl, {lo,lo};\n"
        "mov.b32 rh, {hi,hi};\n"
        "mul.bf16x2 x4, x4, rl;\n"
        "mul.bf16x2 x5, x5, rl;\n"
        "mul.bf16x2 x6, x6, rh;\n"
        "mul.bf16x2 x7, x7, rh;\n"
        "brx.idx.uni tq, TB_%=;\n"
        "B0_%=:\n"
        "and.b32 la, ln, 255;\n"
        "shr.u32 lb, ln, 8;\n"
        "add.u32 ma, sa, %182;\n"
        "ldmatrix.sync.aligned.m8n8.x1.shared.b16 {yb}, [ma];\n"
        "add.u32 xa, sa, %181;\n"
        "mma.sync.aligned.m16n8k16.row.col.f32.bf16.bf16.f32 {%0,%1,%2,%3}, {b0,b1,b2,b3}, {x0,x1}, {%0,%1,%2,%3};\n"
        "mma.sync.aligned.m16n8k16.row.col.f32.bf16.bf16.f32 {%4,%5,%6,%7}, {b0,b1,b2,b3}, {x2,x3}, {%4,%5,%6,%7};\n"
        "ld.shared.v4.u32 {x0,x1,x2,x3}, [xa+0];\n"
        "tanh.approx.f32 t0, p0;\n"
        "tanh.approx.f32 t1, p2;\n"
        "fma.rn.f32 t0, p0, t0, p0;\n"
        "fma.rn.f32 t1, p2, t1, p2;\n"
        "cvt.rn.bf16x2.f32 r0, t1, t0;\n"
        "mma.sync.aligned.m16n8k16.row.col.f32.bf16.bf16.f32 {%8,%9,%10,%11}, {b0,b1,b2,b3}, {x4,x5}, {%8,%9,%10,%11};\n"
        "mma.sync.aligned.m16n8k16.row.col.f32.bf16.bf16.f32 {%12,%13,%14,%15}, {b0,b1,b2,b3}, {x6,x7}, {%12,%13,%14,%15};\n"
        "ld.shared.v4.u32 {x4,x5,x6,x7}, [xa+128];\n"
        "tanh.approx.f32 t0, p4;\n"
        "tanh.approx.f32 t1, p6;\n"
        "fma.rn.f32 t0, p4, t0, p4;\n"
        "fma.rn.f32 t1, p6, t1, p6;\n"
        "cvt.rn.bf16x2.f32 r1, t1, t0;\n"
        "mma.sync.aligned.m16n8k8.row.col.f32.bf16.bf16.f32 {d0,d1,d2,d3}, {%177,%178}, {yb}, {fz,fz,fz,fz};\n"
        "cvt.rn.bf16x2.f32 a0, d2, d0;\n"
        "cvt.rn.bf16x2.f32 a1, d3, d1;\n"
        "mov.b32 {lo,hi}, r2;\n"
        "mov.b32 rl, {lo,lo};\n"
        "mov.b32 rh, {hi,hi};\n"
        "mul.bf16x2 x8, x8, rl;\n"
        "mul.bf16x2 x9, x9, rl;\n"
        "mul.bf16x2 x10, x10, rh;\n"
        "mul.bf16x2 x11, x11, rh;\n"
        "mma.sync.aligned.m16n8k16.row.col.f32.bf16.bf16.f32 {%16,%17,%18,%19}, {b0,b1,b2,b3}, {x8,x9}, {%16,%17,%18,%19};\n"
        "mma.sync.aligned.m16n8k16.row.col.f32.bf16.bf16.f32 {%20,%21,%22,%23}, {b0,b1,b2,b3}, {x10,x11}, {%20,%21,%22,%23};\n"
        "ld.shared.v4.u32 {x8,x9,x10,x11}, [xa+256];\n"
        "tanh.approx.f32 t0, p8;\n"
        "tanh.approx.f32 t1, p10;\n"
        "fma.rn.f32 t0, p8, t0, p8;\n"
        "fma.rn.f32 t1, p10, t1, p10;\n"
        "cvt.rn.bf16x2.f32 r2, t1, t0;\n"
        "mma.sync.aligned.m16n8k8.row.col.f32.bf16.bf16.f32 {d0,d1,d2,d3}, {%179,%180}, {yb}, {fz,fz,fz,fz};\n"
        "cvt.rn.bf16x2.f32 a2, d2, d0;\n"
        "cvt.rn.bf16x2.f32 a3, d3, d1;\n"
        "mov.b32 {lo,hi}, r3;\n"
        "mov.b32 rl, {lo,lo};\n"
        "mov.b32 rh, {hi,hi};\n"
        "mul.bf16x2 x12, x12, rl;\n"
        "mul.bf16x2 x13, x13, rl;\n"
        "mul.bf16x2 x14, x14, rh;\n"
        "mul.bf16x2 x15, x15, rh;\n"
        "mma.sync.aligned.m16n8k16.row.col.f32.bf16.bf16.f32 {%24,%25,%26,%27}, {b0,b1,b2,b3}, {x12,x13}, {%24,%25,%26,%27};\n"
        "mma.sync.aligned.m16n8k16.row.col.f32.bf16.bf16.f32 {%28,%29,%30,%31}, {b0,b1,b2,b3}, {x14,x15}, {%28,%29,%30,%31};\n"
        "ld.shared.v4.u32 {x12,x13,x14,x15}, [xa+384];\n"
        "tanh.approx.f32 t0, p12;\n"
        "tanh.approx.f32 t1, p14;\n"
        "fma.rn.f32 t0, p12, t0, p12;\n"
        "fma.rn.f32 t1, p14, t1, p14;\n"
        "cvt.rn.bf16x2.f32 r3, t1, t0;\n"
        "mov.b32 {lo,hi}, r0;\n"
        "mov.b32 rl, {lo,lo};\n"
        "mov.b32 rh, {hi,hi};\n"
        "mul.bf16x2 x0, x0, rl;\n"
        "mul.bf16x2 x1, x1, rl;\n"
        "mul.bf16x2 x2, x2, rh;\n"
        "mul.bf16x2 x3, x3, rh;\n"
        "mov.b32 {lo,hi}, r1;\n"
        "mov.b32 rl, {lo,lo};\n"
        "mov.b32 rh, {hi,hi};\n"
        "mul.bf16x2 x4, x4, rl;\n"
        "mul.bf16x2 x5, x5, rl;\n"
        "mul.bf16x2 x6, x6, rh;\n"
        "mul.bf16x2 x7, x7, rh;\n"
        "brx.idx.uni la, TA_%=;\n"
        "B1_%=:\n"
        "and.b32 la, ln, 255;\n"
        "shr.u32 lb, ln, 8;\n"
        "add.u32 ma, sa, %182;\n"
        "ldmatrix.sync.aligned.m8n8.x1.shared.b16 {yb}, [ma];\n"
        "add.u32 xa, sa, %181;\n"
        "mma.sync.aligned.m16n8k16.row.col.f32.bf16.bf16.f32 {%32,%33,%34,%35}, {b0,b1,b2,b3}, {x0,x1}, {%32,%33,%34,%35};\n"
        "mma.sync.aligned.m16n8k16.row.col.f32.bf16.bf16.f32 {%36,%37,%38,%39}, {b0,b1,b2,b3}, {x2,x3}, {%36,%37,%38,%39};\n"
        "ld.shared.v4.u32 {x0,x1,x2,x3}, [xa+0];\n"
        "tanh.approx.f32 t0, p0;\n"
        "tanh.approx.f32 t1, p2;\n"
        "fma.rn.f32 t0, p0, t0, p0;\n"
        "fma.rn.f32 t1, p2, t1, p2;\n"
        "cvt.rn.bf16x2.f32 r0, t1, t0;\n"
        "mma.sync.aligned.m16n8k16.row.col.f32.bf16.bf16.f32 {%40,%41,%42,%43}, {b0,b1,b2,b3}, {x4,x5}, {%40,%41,%42,%43};\n"
        "mma.sync.aligned.m16n8k16.row.col.f32.bf16.bf16.f32 {%44,%45,%46,%47}, {b0,b1,b2,b3}, {x6,x7}, {%44,%45,%46,%47};\n"
        "ld.shared.v4.u32 {x4,x5,x6,x7}, [xa+128];\n"
        "tanh.approx.f32 t0, p4;\n"
        "tanh.approx.f32 t1, p6;\n"
        "fma.rn.f32 t0, p4, t0, p4;\n"
        "fma.rn.f32 t1, p6, t1, p6;\n"
        "cvt.rn.bf16x2.f32 r1, t1, t0;\n"
        "mma.sync.aligned.m16n8k8.row.col.f32.bf16.bf16.f32 {d0,d1,d2,d3}, {%177,%178}, {yb}, {fz,fz,fz,fz};\n"
        "cvt.rn.bf16x2.f32 a0, d2, d0;\n"
        "cvt.rn.bf16x2.f32 a1, d3, d1;\n"
        "mov.b32 {lo,hi}, r2;\n"
        "mov.b32 rl, {lo,lo};\n"
        "mov.b32 rh, {hi,hi};\n"
        "mul.bf16x2 x8, x8, rl;\n"
        "mul.bf16x2 x9, x9, rl;\n"
        "mul.bf16x2 x10, x10, rh;\n"
        "mul.bf16x2 x11, x11, rh;\n"
        "mma.sync.aligned.m16n8k16.row.col.f32.bf16.bf16.f32 {%48,%49,%50,%51}, {b0,b1,b2,b3}, {x8,x9}, {%48,%49,%50,%51};\n"
        "mma.sync.aligned.m16n8k16.row.col.f32.bf16.bf16.f32 {%52,%53,%54,%55}, {b0,b1,b2,b3}, {x10,x11}, {%52,%53,%54,%55};\n"
        "ld.shared.v4.u32 {x8,x9,x10,x11}, [xa+256];\n"
        "tanh.approx.f32 t0, p8;\n"
        "tanh.approx.f32 t1, p10;\n"
        "fma.rn.f32 t0, p8, t0, p8;\n"
        "fma.rn.f32 t1, p10, t1, p10;\n"
        "cvt.rn.bf16x2.f32 r2, t1, t0;\n"
        "mma.sync.aligned.m16n8k8.row.col.f32.bf16.bf16.f32 {d0,d1,d2,d3}, {%179,%180}, {yb}, {fz,fz,fz,fz};\n"
        "cvt.rn.bf16x2.f32 a2, d2, d0;\n"
        "cvt.rn.bf16x2.f32 a3, d3, d1;\n"
        "mov.b32 {lo,hi}, r3;\n"
        "mov.b32 rl, {lo,lo};\n"
        "mov.b32 rh, {hi,hi};\n"
        "mul.bf16x2 x12, x12, rl;\n"
        "mul.bf16x2 x13, x13, rl;\n"
        "mul.bf16x2 x14, x14, rh;\n"
        "mul.bf16x2 x15, x15, rh;\n"
        "mma.sync.aligned.m16n8k16.row.col.f32.bf16.bf16.f32 {%56,%57,%58,%59}, {b0,b1,b2,b3}, {x12,x13}, {%56,%57,%58,%59};\n"
        "mma.sync.aligned.m16n8k16.row.col.f32.bf16.bf16.f32 {%60,%61,%62,%63}, {b0,b1,b2,b3}, {x14,x15}, {%60,%61,%62,%63};\n"
        "ld.shared.v4.u32 {x12,x13,x14,x15}, [xa+384];\n"
        "tanh.approx.f32 t0, p12;\n"
        "tanh.approx.f32 t1, p14;\n"
        "fma.rn.f32 t0, p12, t0, p12;\n"
        "fma.rn.f32 t1, p14, t1, p14;\n"
        "cvt.rn.bf16x2.f32 r3, t1, t0;\n"
        "mov.b32 {lo,hi}, r0;\n"
        "mov.b32 rl, {lo,lo};\n"
        "mov.b32 rh, {hi,hi};\n"
        "mul.bf16x2 x0, x0, rl;\n"
        "mul.bf16x2 x1, x1, rl;\n"
        "mul.bf16x2 x2, x2, rh;\n"
        "mul.bf16x2 x3, x3, rh;\n"
        "mov.b32 {lo,hi}, r1;\n"
        "mov.b32 rl, {lo,lo};\n"
        "mov.b32 rh, {hi,hi};\n"
        "mul.bf16x2 x4, x4, rl;\n"
        "mul.bf16x2 x5, x5, rl;\n"
        "mul.bf16x2 x6, x6, rh;\n"
        "mul.bf16x2 x7, x7, rh;\n"
        "brx.idx.uni la, TA_%=;\n"
        "B2_%=:\n"
        "and.b32 la, ln, 255;\n"
        "shr.u32 lb, ln, 8;\n"
        "add.u32 ma, sa, %182;\n"
        "ldmatrix.sync.aligned.m8n8.x1.shared.b16 {yb}, [ma];\n"
        "add.u32 xa, sa, %181;\n"
        "mma.sync.aligned.m16n8k16.row.col.f32.bf16.bf16.f32 {%64,%65,%66,%67}, {b0,b1,b2,b3}, {x0,x1}, {%64,%65,%66,%67};\n"
        "mma.sync.aligned.m16n8k16.row.col.f32.bf16.bf16.f32 {%68,%69,%70,%71}, {b0,b1,b2,b3}, {x2,x3}, {%68,%69,%70,%71};\n"
        "ld.shared.v4.u32 {x0,x1,x2,x3}, [xa+0];\n"
        "tanh.approx.f32 t0, p0;\n"
        "tanh.approx.f32 t1, p2;\n"
        "fma.rn.f32 t0, p0, t0, p0;\n"
        "fma.rn.f32 t1, p2, t1, p2;\n"
        "cvt.rn.bf16x2.f32 r0, t1, t0;\n"
        "mma.sync.aligned.m16n8k16.row.col.f32.bf16.bf16.f32 {%72,%73,%74,%75}, {b0,b1,b2,b3}, {x4,x5}, {%72,%73,%74,%75};\n"
        "mma.sync.aligned.m16n8k16.row.col.f32.bf16.bf16.f32 {%76,%77,%78,%79}, {b0,b1,b2,b3}, {x6,x7}, {%76,%77,%78,%79};\n"
        "ld.shared.v4.u32 {x4,x5,x6,x7}, [xa+128];\n"
        "tanh.approx.f32 t0, p4;\n"
        "tanh.approx.f32 t1, p6;\n"
        "fma.rn.f32 t0, p4, t0, p4;\n"
        "fma.rn.f32 t1, p6, t1, p6;\n"
        "cvt.rn.bf16x2.f32 r1, t1, t0;\n"
        "mma.sync.aligned.m16n8k8.row.col.f32.bf16.bf16.f32 {d0,d1,d2,d3}, {%177,%178}, {yb}, {fz,fz,fz,fz};\n"
        "cvt.rn.bf16x2.f32 a0, d2, d0;\n"
        "cvt.rn.bf16x2.f32 a1, d3, d1;\n"
        "mov.b32 {lo,hi}, r2;\n"
        "mov.b32 rl, {lo,lo};\n"
        "mov.b32 rh, {hi,hi};\n"
        "mul.bf16x2 x8, x8, rl;\n"
        "mul.bf16x2 x9, x9, rl;\n"
        "mul.bf16x2 x10, x10, rh;\n"
        "mul.bf16x2 x11, x11, rh;\n"
        "mma.sync.aligned.m16n8k16.row.col.f32.bf16.bf16.f32 {%80,%81,%82,%83}, {b0,b1,b2,b3}, {x8,x9}, {%80,%81,%82,%83};\n"
        "mma.sync.aligned.m16n8k16.row.col.f32.bf16.bf16.f32 {%84,%85,%86,%87}, {b0,b1,b2,b3}, {x10,x11}, {%84,%85,%86,%87};\n"
        "ld.shared.v4.u32 {x8,x9,x10,x11}, [xa+256];\n"
        "tanh.approx.f32 t0, p8;\n"
        "tanh.approx.f32 t1, p10;\n"
        "fma.rn.f32 t0, p8, t0, p8;\n"
        "fma.rn.f32 t1, p10, t1, p10;\n"
        "cvt.rn.bf16x2.f32 r2, t1, t0;\n"
        "mma.sync.aligned.m16n8k8.row.col.f32.bf16.bf16.f32 {d0,d1,d2,d3}, {%179,%180}, {yb}, {fz,fz,fz,fz};\n"
        "cvt.rn.bf16x2.f32 a2, d2, d0;\n"
        "cvt.rn.bf16x2.f32 a3, d3, d1;\n"
        "mov.b32 {lo,hi}, r3;\n"
        "mov.b32 rl, {lo,lo};\n"
        "mov.b32 rh, {hi,hi};\n"
        "mul.bf16x2 x12, x12, rl;\n"
        "mul.bf16x2 x13, x13, rl;\n"
        "mul.bf16x2 x14, x14, rh;\n"
        "mul.bf16x2 x15, x15, rh;\n"
        "mma.sync.aligned.m16n8k16.row.col.f32.bf16.bf16.f32 {%88,%89,%90,%91}, {b0,b1,b2,b3}, {x12,x13}, {%88,%89,%90,%91};\n"
        "mma.sync.aligned.m16n8k16.row.col.f32.bf16.bf16.f32 {%92,%93,%94,%95}, {b0,b1,b2,b3}, {x14,x15}, {%92,%93,%94,%95};\n"
        "ld.shared.v4.u32 {x12,x13,x14,x15}, [xa+384];\n"
        "tanh.approx.f32 t0, p12;\n"
        "tanh.approx.f32 t1, p14;\n"
        "fma.rn.f32 t0, p12, t0, p12;\n"
        "fma.rn.f32 t1, p14, t1, p14;\n"
        "cvt.rn.bf16x2.f32 r3, t1, t0;\n"
        "mov.b32 {lo,hi}, r0;\n"
        "mov.b32 rl, {lo,lo};\n"
        "mov.b32 rh, {hi,hi};\n"
        "mul.bf16x2 x0, x0, rl;\n"
        "mul.bf16x2 x1, x1, rl;\n"
        "mul.bf16x2 x2, x2, rh;\n"
        "mul.bf16x2 x3, x3, rh;\n"
        "mov.b32 {lo,hi}, r1;\n"
        "mov.b32 rl, {lo,lo};\n"
        "mov.b32 rh, {hi,hi};\n"
        "mul.bf16x2 x4, x4, rl;\n"
        "mul.bf16x2 x5, x5, rl;\n"
        "mul.bf16x2 x6, x6, rh;\n"
        "mul.bf16x2 x7, x7, rh;\n"
        "brx.idx.uni la, TA_%=;\n"
        "B3_%=:\n"
        "and.b32 la, ln, 255;\n"
        "shr.u32 lb, ln, 8;\n"
        "add.u32 ma, sa, %182;\n"
        "ldmatrix.sync.aligned.m8n8.x1.shared.b16 {yb}, [ma];\n"
        "add.u32 xa, sa, %181;\n"
        "mma.sync.aligned.m16n8k16.row.col.f32.bf16.bf16.f32 {%96,%97,%98,%99}, {b0,b1,b2,b3}, {x0,x1}, {%96,%97,%98,%99};\n"
        "mma.sync.aligned.m16n8k16.row.col.f32.bf16.bf16.f32 {%100,%101,%102,%103}, {b0,b1,b2,b3}, {x2,x3}, {%100,%101,%102,%103};\n"
        "ld.shared.v4.u32 {x0,x1,x2,x3}, [xa+0];\n"
        "tanh.approx.f32 t0, p0;\n"
        "tanh.approx.f32 t1, p2;\n"
        "fma.rn.f32 t0, p0, t0, p0;\n"
        "fma.rn.f32 t1, p2, t1, p2;\n"
        "cvt.rn.bf16x2.f32 r0, t1, t0;\n"
        "mma.sync.aligned.m16n8k16.row.col.f32.bf16.bf16.f32 {%104,%105,%106,%107}, {b0,b1,b2,b3}, {x4,x5}, {%104,%105,%106,%107};\n"
        "mma.sync.aligned.m16n8k16.row.col.f32.bf16.bf16.f32 {%108,%109,%110,%111}, {b0,b1,b2,b3}, {x6,x7}, {%108,%109,%110,%111};\n"
        "ld.shared.v4.u32 {x4,x5,x6,x7}, [xa+128];\n"
        "tanh.approx.f32 t0, p4;\n"
        "tanh.approx.f32 t1, p6;\n"
        "fma.rn.f32 t0, p4, t0, p4;\n"
        "fma.rn.f32 t1, p6, t1, p6;\n"
        "cvt.rn.bf16x2.f32 r1, t1, t0;\n"
        "mma.sync.aligned.m16n8k8.row.col.f32.bf16.bf16.f32 {d0,d1,d2,d3}, {%177,%178}, {yb}, {fz,fz,fz,fz};\n"
        "cvt.rn.bf16x2.f32 a0, d2, d0;\n"
        "cvt.rn.bf16x2.f32 a1, d3, d1;\n"
        "mov.b32 {lo,hi}, r2;\n"
        "mov.b32 rl, {lo,lo};\n"
        "mov.b32 rh, {hi,hi};\n"
        "mul.bf16x2 x8, x8, rl;\n"
        "mul.bf16x2 x9, x9, rl;\n"
        "mul.bf16x2 x10, x10, rh;\n"
        "mul.bf16x2 x11, x11, rh;\n"
        "mma.sync.aligned.m16n8k16.row.col.f32.bf16.bf16.f32 {%112,%113,%114,%115}, {b0,b1,b2,b3}, {x8,x9}, {%112,%113,%114,%115};\n"
        "mma.sync.aligned.m16n8k16.row.col.f32.bf16.bf16.f32 {%116,%117,%118,%119}, {b0,b1,b2,b3}, {x10,x11}, {%116,%117,%118,%119};\n"
        "ld.shared.v4.u32 {x8,x9,x10,x11}, [xa+256];\n"
        "tanh.approx.f32 t0, p8;\n"
        "tanh.approx.f32 t1, p10;\n"
        "fma.rn.f32 t0, p8, t0, p8;\n"
        "fma.rn.f32 t1, p10, t1, p10;\n"
        "cvt.rn.bf16x2.f32 r2, t1, t0;\n"
        "mma.sync.aligned.m16n8k8.row.col.f32.bf16.bf16.f32 {d0,d1,d2,d3}, {%179,%180}, {yb}, {fz,fz,fz,fz};\n"
        "cvt.rn.bf16x2.f32 a2, d2, d0;\n"
        "cvt.rn.bf16x2.f32 a3, d3, d1;\n"
        "mov.b32 {lo,hi}, r3;\n"
        "mov.b32 rl, {lo,lo};\n"
        "mov.b32 rh, {hi,hi};\n"
        "mul.bf16x2 x12, x12, rl;\n"
        "mul.bf16x2 x13, x13, rl;\n"
        "mul.bf16x2 x14, x14, rh;\n"
        "mul.bf16x2 x15, x15, rh;\n"
        "mma.sync.aligned.m16n8k16.row.col.f32.bf16.bf16.f32 {%120,%121,%122,%123}, {b0,b1,b2,b3}, {x12,x13}, {%120,%121,%122,%123};\n"
        "mma.sync.aligned.m16n8k16.row.col.f32.bf16.bf16.f32 {%124,%125,%126,%127}, {b0,b1,b2,b3}, {x14,x15}, {%124,%125,%126,%127};\n"
        "ld.shared.v4.u32 {x12,x13,x14,x15}, [xa+384];\n"
        "tanh.approx.f32 t0, p12;\n"
        "tanh.approx.f32 t1, p14;\n"
        "fma.rn.f32 t0, p12, t0, p12;\n"
        "fma.rn.f32 t1, p14, t1, p14;\n"
        "cvt.rn.bf16x2.f32 r3, t1, t0;\n"
        "mov.b32 {lo,hi}, r0;\n"
        "mov.b32 rl, {lo,lo};\n"
        "mov.b32 rh, {hi,hi};\n"
        "mul.bf16x2 x0, x0, rl;\n"
        "mul.bf16x2 x1, x1, rl;\n"
        "mul.bf16x2 x2, x2, rh;\n"
        "mul.bf16x2 x3, x3, rh;\n"
        "mov.b32 {lo,hi}, r1;\n"
        "mov.b32 rl, {lo,lo};\n"
        "mov.b32 rh, {hi,hi};\n"
        "mul.bf16x2 x4, x4, rl;\n"
        "mul.bf16x2 x5, x5, rl;\n"
        "mul.bf16x2 x6, x6, rh;\n"
        "mul.bf16x2 x7, x7, rh;\n"
        "brx.idx.uni la, TA_%=;\n"
        "B4_%=:\n"
        "and.b32 la, ln, 255;\n"
        "shr.u32 lb, ln, 8;\n"
        "add.u32 ma, sa, %182;\n"
        "ldmatrix.sync.aligned.m8n8.x1.shared.b16 {yb}, [ma];\n"
        "add.u32 xa, sa, %181;\n"
        "mma.sync.aligned.m16n8k16.row.col.f32.bf16.bf16.f32 {%128,%129,%130,%131}, {b0,b1,b2,b3}, {x0,x1}, {%128,%129,%130,%131};\n"
        "mma.sync.aligned.m16n8k16.row.col.f32.bf16.bf16.f32 {%132,%133,%134,%135}, {b0,b1,b2,b3}, {x2,x3}, {%132,%133,%134,%135};\n"
        "ld.shared.v4.u32 {x0,x1,x2,x3}, [xa+0];\n"
        "tanh.approx.f32 t0, p0;\n"
        "tanh.approx.f32 t1, p2;\n"
        "fma.rn.f32 t0, p0, t0, p0;\n"
        "fma.rn.f32 t1, p2, t1, p2;\n"
        "cvt.rn.bf16x2.f32 r0, t1, t0;\n"
        "mma.sync.aligned.m16n8k16.row.col.f32.bf16.bf16.f32 {%136,%137,%138,%139}, {b0,b1,b2,b3}, {x4,x5}, {%136,%137,%138,%139};\n"
        "mma.sync.aligned.m16n8k16.row.col.f32.bf16.bf16.f32 {%140,%141,%142,%143}, {b0,b1,b2,b3}, {x6,x7}, {%140,%141,%142,%143};\n"
        "ld.shared.v4.u32 {x4,x5,x6,x7}, [xa+128];\n"
        "tanh.approx.f32 t0, p4;\n"
        "tanh.approx.f32 t1, p6;\n"
        "fma.rn.f32 t0, p4, t0, p4;\n"
        "fma.rn.f32 t1, p6, t1, p6;\n"
        "cvt.rn.bf16x2.f32 r1, t1, t0;\n"
        "mma.sync.aligned.m16n8k8.row.col.f32.bf16.bf16.f32 {d0,d1,d2,d3}, {%177,%178}, {yb}, {fz,fz,fz,fz};\n"
        "cvt.rn.bf16x2.f32 a0, d2, d0;\n"
        "cvt.rn.bf16x2.f32 a1, d3, d1;\n"
        "mov.b32 {lo,hi}, r2;\n"
        "mov.b32 rl, {lo,lo};\n"
        "mov.b32 rh, {hi,hi};\n"
        "mul.bf16x2 x8, x8, rl;\n"
        "mul.bf16x2 x9, x9, rl;\n"
        "mul.bf16x2 x10, x10, rh;\n"
        "mul.bf16x2 x11, x11, rh;\n"
        "mma.sync.aligned.m16n8k16.row.col.f32.bf16.bf16.f32 {%144,%145,%146,%147}, {b0,b1,b2,b3}, {x8,x9}, {%144,%145,%146,%147};\n"
        "mma.sync.aligned.m16n8k16.row.col.f32.bf16.bf16.f32 {%148,%149,%150,%151}, {b0,b1,b2,b3}, {x10,x11}, {%148,%149,%150,%151};\n"
        "ld.shared.v4.u32 {x8,x9,x10,x11}, [xa+256];\n"
        "tanh.approx.f32 t0, p8;\n"
        "tanh.approx.f32 t1, p10;\n"
        "fma.rn.f32 t0, p8, t0, p8;\n"
        "fma.rn.f32 t1, p10, t1, p10;\n"
        "cvt.rn.bf16x2.f32 r2, t1, t0;\n"
        "mma.sync.aligned.m16n8k8.row.col.f32.bf16.bf16.f32 {d0,d1,d2,d3}, {%179,%180}, {yb}, {fz,fz,fz,fz};\n"
        "cvt.rn.bf16x2.f32 a2, d2, d0;\n"
        "cvt.rn.bf16x2.f32 a3, d3, d1;\n"
        "mov.b32 {lo,hi}, r3;\n"
        "mov.b32 rl, {lo,lo};\n"
        "mov.b32 rh, {hi,hi};\n"
        "mul.bf16x2 x12, x12, rl;\n"
        "mul.bf16x2 x13, x13, rl;\n"
        "mul.bf16x2 x14, x14, rh;\n"
        "mul.bf16x2 x15, x15, rh;\n"
        "mma.sync.aligned.m16n8k16.row.col.f32.bf16.bf16.f32 {%152,%153,%154,%155}, {b0,b1,b2,b3}, {x12,x13}, {%152,%153,%154,%155};\n"
        "mma.sync.aligned.m16n8k16.row.col.f32.bf16.bf16.f32 {%156,%157,%158,%159}, {b0,b1,b2,b3}, {x14,x15}, {%156,%157,%158,%159};\n"
        "ld.shared.v4.u32 {x12,x13,x14,x15}, [xa+384];\n"
        "tanh.approx.f32 t0, p12;\n"
        "tanh.approx.f32 t1, p14;\n"
        "fma.rn.f32 t0, p12, t0, p12;\n"
        "fma.rn.f32 t1, p14, t1, p14;\n"
        "cvt.rn.bf16x2.f32 r3, t1, t0;\n"
        "mov.b32 {lo,hi}, r0;\n"
        "mov.b32 rl, {lo,lo};\n"
        "mov.b32 rh, {hi,hi};\n"
        "mul.bf16x2 x0, x0, rl;\n"
        "mul.bf16x2 x1, x1, rl;\n"
        "mul.bf16x2 x2, x2, rh;\n"
        "mul.bf16x2 x3, x3, rh;\n"
        "mov.b32 {lo,hi}, r1;\n"
        "mov.b32 rl, {lo,lo};\n"
        "mov.b32 rh, {hi,hi};\n"
        "mul.bf16x2 x4, x4, rl;\n"
        "mul.bf16x2 x5, x5, rl;\n"
        "mul.bf16x2 x6, x6, rh;\n"
        "mul.bf16x2 x7, x7, rh;\n"
        "brx.idx.uni la, TA_%=;\n"
        "EXIT_%=:\n"
        "mov.u32 %160, ring;\n"
        "}\n"
        : "+f"(acc[0][0][0][0]), "+f"(acc[0][0][0][1]), "+f"(acc[0][0][0][2]), "+f"(acc[0][0][0][3]), "+f"(acc[0][0][1][0]),
          "+f"(acc[0][0][1][1]), "+f"(acc[0][0][1][2]), "+f"(acc[0][0][1][3]), "+f"(acc[0][1][0][0]), "+f"(acc[0][1][0][1]),
          "+f"(acc[0][1][0][2]), "+f"(acc[0][1][0][3]), "+f"(acc[0][1][1][0]), "+f"(acc[0][1][1][1]), "+f"(acc[0][1][1][2]),
          "+f"(acc[0][1][1][3]), "+f"(acc[0][2][0][0]), "+f"(acc[0][2][0][1]), "+f"(acc[0][2][0][2]), "+f"(acc[0][2][0][3]),
          "+f"(acc[0][2][1][0]), "+f"(acc[0][2][1][1]), "+f"(acc[0][2][1][2]), "+f"(acc[0][2][1][3]), "+f"(acc[0][3][0][0]),
          "+f"(acc[0][3][0][1]), "+f"(acc[0][3][0][2]), "+f"(acc[0][3][0][3]), "+f"(acc[0][3][1][0]), "+f"(acc[0][3][1][1]),
          "+f"(acc[0][3][1][2]), "+f"(acc[0][3][1][3]), "+f"(acc[1][0][0][0]), "+f"(acc[1][0][0][1]), "+f"(acc[1][0][0][2]),
          "+f"(acc[1][0][0][3]), "+f"(acc[1][0][1][0]), "+f"(acc[1][0][1][1]), "+f"(acc[1][0][1][2]), "+f"(acc[1][0][1][3]),
          "+f"(acc[1][1][0][0]), "+f"(acc[1][1][0][1]), "+f"(acc[1][1][0][2]), "+f"(acc[1][1][0][3]), "+f"(acc[1][1][1][0]),
          "+f"(acc[1][1][1][1]), "+f"(acc[1][1][1][2]), "+f"(acc[1][1][1][3]), "+f"(acc[1][2][0][0]), "+f"(acc[1][2][0][1]),
          "+f"(acc[1][2][0][2]), "+f"(acc[1][2][0][3]), "+f"(acc[1][2][1][0]), "+f"(acc[1][2][1][1]), "+f"(acc[1][2][1][2]),
          "+f"(acc[1][2][1][3]), "+f"(acc[1][3][0][0]), "+f"(acc[1][3][0][1]), "+f"(acc[1][3][0][2]), "+f"(acc[1][3][0][3]),
          "+f"(acc[1][3][1][0]), "+f"(acc[1][3][1][1]), "+f"(acc[1][3][1][2]), "+f"(acc[1][3][1][3]), "+f"(acc[2][0][0][0]),
          "+f"(acc[2][0][0][1]), "+f"(acc[2][0][0][2]), "+f"(acc[2][0][0][3]), "+f"(acc[2][0][1][0]), "+f"(acc[2][0][1][1]),
          "+f"(acc[2][0][1][2]), "+f"(acc[2][0][1][3]), "+f"(acc[2][1][0][0]), "+f"(acc[2][1][0][1]), "+f"(acc[2][1][0][2]),
          "+f"(acc[2][1][0][3]), "+f"(acc[2][1][1][0]), "+f"(acc[2][1][1][1]), "+f"(acc[2][1][1][2]), "+f"(acc[2][1][1][3]),
          "+f"(acc[2][2][0][0]), "+f"(acc[2][2][0][1]), "+f"(acc[2][2][0][2]), "+f"(acc[2][2][0][3]), "+f"(acc[2][2][1][0]),
          "+f"(acc[2][2][1][1]), "+f"(acc[2][2][1][2]), "+f"(acc[2][2][1][3]), "+f"(acc[2][3][0][0]), "+f"(acc[2][3][0][1]),
          "+f"(acc[2][3][0][2]), "+f"(acc[2][3][0][3]), "+f"(acc[2][3][1][0]), "+f"(acc[2][3][1][1]), "+f"(acc[2][3][1][2]),
          "+f"(acc[2][3][1][3]), "+f"(acc[3][0][0][0]), "+f"(acc[3][0][0][1]), "+f"(acc[3][0][0][2]), "+f"(acc[3][0][0][3]),
          "+f"(acc[3][0][1][0]), "+f"(acc[3][0][1][1]), "+f"(acc[3][0][1][2]), "+f"(acc[3][0][1][3]), "+f"(acc[3][1][0][0]),
          "+f"(acc[3][1][0][1]), "+f"(acc[3][1][0][2]), "+f"(acc[3][1][0][3]), "+f"(acc[3][1][1][0]), "+f"(acc[3][1][1][1]),
          "+f"(acc[3][1][1][2]), "+f"(acc[3][1][1][3]), "+f"(acc[3][2][0][0]), "+f"(acc[3][2][0][1]), "+f"(acc[3][2][0][2]),
          "+f"(acc[3][2][0][3]), "+f"(acc[3][2][1][0]), "+f"(acc[3][2][1][1]), "+f"(acc[3][2][1][2]), "+f"(acc[3][2][1][3]),
          "+f"(acc[3][3][0][0]), "+f"(acc[3][3][0][1]), "+f"(acc[3][3][0][2]), "+f"(acc[3][3][0][3]), "+f"(acc[3][3][1][0]),
          "+f"(acc[3][3][1][1]), "+f"(acc[3][3][1][2]), "+f"(acc[3][3][1][3]), "+f"(acc[4][0][0][0]), "+f"(acc[4][0][0][1]),
          "+f"(acc[4][0][0][2]), "+f"(acc[4][0][0][3]), "+f"(acc[4][0][1][0]), "+f"(acc[4][0][1][1]), "+f"(acc[4][0][1][2]),
          "+f"(acc[4][0][1][3]), "+f"(acc[4][1][0][0]), "+f"(acc[4][1][0][1]), "+f"(acc[4][1][0][2]), "+f"(acc[4][1][0][3]),
          "+f"(acc[4][1][1][0]), "+f"(acc[4][1][1][1]), "+f"(acc[4][1][1][2]), "+f"(acc[4][1][1][3]), "+f"(acc[4][2][0][0]),
          "+f"(acc[4][2][0][1]), "+f"(acc[4][2][0][2]), "+f"(acc[4][2][0][3]), "+f"(acc[4][2][1][0]), "+f"(acc[4][2][1][1]),
          "+f"(acc[4][2][1][2]), "+f"(acc[4][2][1][3]), "+f"(acc[4][3][0][0]), "+f"(acc[4][3][0][1]), "+f"(acc[4][3][0][2]),
          "+f"(acc[4][3][0][3]), "+f"(acc[4][3][1][0]), "+f"(acc[4][3][1][1]), "+f"(acc[4][3][1][2]), "+f"(acc[4][3][1][3]),
          "+r"(ring)
        : "r"(wf[0][0]), "r"(wf[0][1]), "r"(wf[0][2]), "r"(wf[0][3]), "r"(wf[1][0]), "r"(wf[1][1]), "r"(wf[1][2]), "r"(wf[1][3]),
          "r"(wf[2][0]), "r"(wf[2][1]), "r"(wf[2][2]), "r"(wf[2][3]), "r"(wf[3][0]), "r"(wf[3][1]), "r"(wf[3][2]), "r"(wf[3][3]),
          "r"(cgf[0]), "r"(cgf[1]), "r"(cgf[2]), "r"(cgf[3]), "r"(xoff), "r"(moff), "r"(rec)
        : "memory");
}

#define PF_A 0x00000
#define PF_B 0x00000
#define PF_C 0x00000
__device__ __forceinline__ void l2_warm(uint32_t mask, int blk, int lane, const void* x, const void* Y, const void* ef) {
    if ((mask >> lane) & 1) {
        constexpr int EFP = (N_EDGES * 32 / (NB * 8) / 16 + 1) * 16, YP = (N_EDGES * 8 / (NB * 2) / 16 + 1) * 16;
        const char* base = lane < 8 ? (const char*)ef : lane < 10 ? (const char*)Y : (const char*)x;
        int o = lane < 8 ? (blk * 8 + lane) * EFP : lane < 10 ? (blk * 2 + lane - 8) * YP : ((lane - 10) * NB + blk) * 8192;
        int n = lane < 8 ? min(EFP, N_EDGES * 32 - o) : lane < 10 ? min(YP, N_EDGES * 8 - o) : min(8192, N_NODES * 1024 - o);
        if (n > 0) asm volatile("cp.async.bulk.prefetch.L2.global [%0], %1;" ::"l"(base + o), "r"(n));
    }
}

__device__ __noinline__ void generic_path(float* sagg, const __nv_bfloat16* x, const int* src, const int* dst,
                                          const __nv_bfloat16* Y, const __nv_bfloat16* ef, const __nv_bfloat16* w_rad,
                                          const __nv_bfloat16* cg, int x0, int x1) {
    const int tid = threadIdx.x, lane = tid & 31, blk = blockIdx.x;
    for (int k = 0; k < 2; k++)
        for (int r = 0; r < min(k == 0 ? x0 : x1, 32); r++) {
            uint32_t* p2 = g_mail2 + (blk * NSRC + ((tid + k * NTHR) >> 3)) * 32 + r;
            uint32_t v;
            int it = 0;
            do {
                asm volatile("ld.relaxed.gpu.global.u32 %0, [%1];" : "=r"(v) : "l"(p2) : "memory");
                if (++it > (1 << 20)) __trap();
            } while (v == 0);
            *p2 = 0;
        }
    __syncthreads();
    for (int i = tid; i < NPB * 512; i += NTHR) sagg[i] = 0.f;
    __syncthreads();
    for (int e0 = tid & ~31; e0 < N_EDGES; e0 += NTHR) {
        uint32_t bm = __ballot_sync(~0u, dst[e0 + lane] / NPB == blk);
        while (bm) {
            const int e = e0 + __ffs(bm) - 1, s = src[e], loc = dst[e] - blk * NPB;
            bm &= bm - 1;
            float a[4][4];
            for (int i = 0; i < 4; i++)
                for (int o = 0; o < 4; o++) {
                    a[i][o] = 0.f;
                    for (int f = 0; f < 4; f++)
                        a[i][o] += __bfloat162float(Y[e * 4 + f]) * __bfloat162float(cg[i * 16 + f * 4 + o]);
                }
#pragma unroll 1
            for (int c = lane; c < 128; c += 32) {
                float pre = 0.f;
                for (int k = 0; k < 16; k++)
                    pre += __bfloat162float(ef[e * 16 + k]) * __bfloat162float(w_rad[k * 128 + c]);
                const float R = pre / (1.f + __expf(-pre));
                for (int o = 0; o < 4; o++) {
                    float acc = 0.f;
                    for (int i = 0; i < 4; i++) acc += __bfloat162float(x[(size_t)s * 512 + c * 4 + i]) * a[i][o];
                    atomicAdd(&sagg[loc * 512 + c * 4 + o], R * acc);
                }
            }
        }
    }
    __syncthreads();
}

__device__ __forceinline__ void init_barriers() {
    extern __shared__ __align__(1024) uint8_t smem[];
    const uint32_t sb = smem_u32(smem);
#pragma unroll
    for (int i = 0; i < 4 * NG; i++) {
        mbar_init(sb + i * STAGE + 4 * ROWP, 32);
        mbar_init(sb + i * STAGE + 4 * ROWP + 8, 2);
    }
}

template <int PHASES>
__global__ void __launch_bounds__(NTHR, 1)
tfn_kernel(const __nv_bfloat16* __restrict__ x, const int* __restrict__ src, const int* __restrict__ dst,
           const __nv_bfloat16* __restrict__ Y, const __nv_bfloat16* __restrict__ ef,
           const __nv_bfloat16* __restrict__ w_rad, const __nv_bfloat16* __restrict__ cg,
           const __nv_bfloat16* __restrict__ w_mix, __nv_bfloat16* __restrict__ out) {
    extern __shared__ __align__(1024) uint8_t smem[];
    const int tid = threadIdx.x, lane = tid & 31;
    const int warp = __shfl_sync(~0u, tid >> 5, 0);
    const int blk = blockIdx.x;
    uint32_t sb = smem_u32(smem);
    asm volatile("" : "+r"(sb));
    int* mi = reinterpret_cast<int*>(smem + SM_MISC);

    const int g = lane >> 2, t = lane & 3;
    const uint32_t dump = sb + SC_DUMP + lane * 4;
    int4 d1[2], s1[2];
    constexpr int nq = EPC / 4;
    const bool binner = (PHASES & 1) && blk < NSRC;
    if (binner) {
#pragma unroll
        for (int k = 0; k < 2; k++) {
            const int q = tid + k * NTHR;
            if (q < nq) {
                d1[k] = __ldg(reinterpret_cast<const int4*>(dst + blk * EPC) + q);
                s1[k] = __ldg(reinterpret_cast<const int4*>(src + blk * EPC) + q);
            }
        }
    }
    if (binner) {
#pragma unroll
        for (int k = 0; k < 3; k++)
            if (k < 2 || warp < 1) sts128(sb + SC_MAIL + (tid + k * NTHR) * 16, ~0u, ~0u, ~0u, ~0u);
        if (tid <= NB / 4) sts128(sb + SC_CNT + tid * 16, 0, 0, 0, 0);
    }
    if (PHASES & 2) {
        if (tid == 160) { sts128(sb + SM_MISC, 0, 0, 0, 0); sts128(sb + SM_MISC + MI_NU * 4, 0, 0, 0, 0); }
        constexpr int lead = LEAD_CLK >> 2;
        if (tid == 161) mi[MI_SHIFT] = 0;
        if (tid == 162 && !(blk & 3) && blk < 128) g_lag[blk >> 2] = lead;
        if (tid < 20 * HS / 4) sts128(sb + SC_HIST + tid * 16, 0, 0, 0, 0);
        const uint32_t pad = (uint32_t)(lane * 0x10008 + 7);
#pragma unroll
        for (int k = 0; k < 3; k++)
            if (tid + k * NTHR < 4 * UCAP * REC / 16) sts128(sb + SM_REC + (tid + k * NTHR) * 16, pad, pad, pad, pad);
    }
    __syncthreads();
    if (PHASES & 2) {
#pragma unroll
        for (int k = 0; k < 4; k++) {
            const int i = tid + k * NTHR, c = i >> 4;
            cp16(sb + SM_W + c * 256 + (((i & 15) ^ ((c & 2) | (((c >> 4) & 1) << 2))) << 4), w_mix + i * 8);
        }
        if (warp >= 8) cp16(sb + SC_WR + ((tid - 256) ^ ((tid >> 4) & 6)) * 16, w_rad + (tid - 256) * 8);
        if (tid < 8) cp16(sb + SC_WR + 4096 + tid * 16, cg + tid * 8);
        if (PF_A && warp == 11) l2_warm(PF_A, blk, lane, x, Y, ef);
    }
    if (binner) {
#pragma unroll
        for (int k = 0; k < 2; k++) {
            if (tid + k * NTHR < nq) {
                const uint32_t dd[4] = {(uint32_t)d1[k].x, (uint32_t)d1[k].y, (uint32_t)d1[k].z, (uint32_t)d1[k].w};
                const uint32_t ss[4] = {(uint32_t)s1[k].x, (uint32_t)s1[k].y, (uint32_t)s1[k].z, (uint32_t)s1[k].w};
                uint32_t own[4], rk[4], v[4];
#pragma unroll
                for (int j = 0; j < 4; j++) { own[j] = dd[j] / NPB; rk[j] = atoms_inc(sb + SC_CNT + own[j] * 4); }
#pragma unroll
                for (int j = 0; j < 4; j++) {
                    const uint32_t loc = dd[j] - own[j] * NPB, code = loc + ((loc * 216) >> 12);
                    v[j] = (ss[j] << 18) + code * 2560 + (tid + k * NTHR) * 4 + j + 1;
                    sts32(sb + SC_MAIL + own[j] * 128 + ((min(rk[j], 31u) * 4) ^ ((own[j] & 7) << 4)), v[j]);
                }
                if (max(max(rk[0], rk[1]), max(rk[2], rk[3])) >= 31) {
#pragma unroll
                    for (int j = 0; j < 4; j++)
                        if (rk[j] - 31 < 32)
                            asm volatile("st.relaxed.gpu.global.u32 [%0], %1;" ::"l"(g_mail2 + (own[j] * NSRC + blk) * 32 + rk[j] - 31), "r"(v[j]) : "memory");
                }
            }
        }
        __syncwarp();
        asm volatile("red.shared.max.u32 [%0], %1;" ::"r"(lane == 0 ? sb + SC_CNT + NB * 4 : dump), "r"(gtime()) : "memory");
        STAMP(1);
        __syncthreads();
        const uint32_t hdr = 0xc0000000u | ((lds32(sb + SC_CNT + NB * 4) << 7) & 0x3ffff000u);
        uint4 mv[3];
        uint32_t mc[3];
#pragma unroll
        for (int k = 0; k < 3; k++)
            if (k < 2 || warp < 1) {
                const int j = tid + k * NTHR, own = j >> 3;
                mv[k] = lds128(sb + SC_MAIL + own * 128 + (((j ^ own) & 7) << 4));
                mc[k] = lds32(sb + SC_CNT + own * 4);
            }
#pragma unroll
        for (int k = 0; k < 3; k++)
            if (k < 2 || warp < 1) {
                const int j = tid + k * NTHR;
                asm volatile("st.relaxed.gpu.global.v4.u32 [%0], {%1,%2,%3,%4};" ::"l"(g_mail + ((j >> 3) * NSRC + blk) * 8 + (j & 7)),
                             "r"(mv[k].x), "r"(mv[k].y), "r"(mv[k].z), "r"((j & 7) == 7 ? hdr | mc[k] : mv[k].w) : "memory");
            }
        STAMP(2);
    }
    if (!(PHASES & 2)) return;
    const uint32_t tpub = (uint32_t)clock() + (blk < NSRC ? 0 : 3000);
    asm volatile("cp.async.wait_all;" ::: "memory");
    __syncwarp();
#pragma unroll
    for (int k = 0; k < 2; k++) {
        const int i = (tid & ~1) + ((tid & 1) * 2 + k) * NTHR, c = i >> 4;
        const uint32_t a0 = sb + SM_W + c * 256 + (((i & 15) ^ ((c & 3) | (((c >> 4) & 1) << 2))) << 4);
        const uint32_t o = (tid & 1) << 4;
        uint4 u = lds128((a0 & ~16u) ^ o), v = lds128((a0 | 16u) ^ o);
        if (tid & 1) { const uint4 w = u; u = v; v = w; }
        const uint32_t s0 = (tid & 1) ? 0x7632 : 0x5410, s1 = s0 ^ 0x2222;
        sts128(a0 ^ o, __byte_perm(u.x, u.y, s0), __byte_perm(u.z, u.w, s0), __byte_perm(v.x, v.y, s0), __byte_perm(v.z, v.w, s0));
        sts128(a0 ^ o ^ 16, __byte_perm(u.x, u.y, s1), __byte_perm(u.z, u.w, s1), __byte_perm(v.x, v.y, s1), __byte_perm(v.z, v.w, s1));
    }

    uint32_t en[8], hr[8], rk[8], em[8];
    int xc[2];
    const uint32_t tref = __shfl_sync(~0u, gtime() >> 5, 0);
    {
        uint4* mp = g_mail + blk * NSRC * 8 + tid;
        int it = 0;
        bool ok;
        while ((int)((uint32_t)clock() - tpub) < POLL_DELAY) {}
        do {
#pragma unroll
            for (int k = 0; k < 2; k++)
                    asm volatile("ld.relaxed.gpu.global.v4.u32 {%0,%1,%2,%3}, [%4];"
                                 : "=r"(en[4 * k]), "=r"(en[4 * k + 1]), "=r"(en[4 * k + 2]), "=r"(en[4 * k + 3])
                                 : "l"(mp + k * NTHR) : "memory");
            uint32_t m = ~0u;
#pragma unroll
            for (int i = 0; i < 8; i++) m = min(m, en[i]);
            ok = __all_sync(~0u, m != 0);
            if (++it > (1 << 20)) __trap();
        } while (!ok);
        STAMP(3);
#pragma unroll
        for (int i = 0; i < 8; i++) {
            const uint32_t w = en[i] & 0x3ffff, code = ((w >> 9) * 13108) >> 16;
            hr[i] = en[i] < 0xc0000000u ? sb + SC_HIST + ((code >> 2) * HS + (en[i] >> 25)) * 4 : dump;
            rk[i] = atoms_inc(hr[i]);
            em[i] = ((((tid + (i >> 2) * NTHR) >> 3) * EPC + w - code * 2560 - 1) * 8) | (code & 3);
        }
        int dt = -(1 << 20);
#pragma unroll
        for (int k = 0; k < 2; k++) {
            const bool hd = (lane & 7) == 7;
            dt = max(dt, hd ? (int)(((en[4 * k + 3] >> 12) - tref) << 14) >> 14 : -(1 << 20));
            xc[k] = hd ? max((int)(en[4 * k + 3] & 0xfff) - 31, 0) : 0;
        }
        dt = __reduce_max_sync(~0u, dt);
        asm volatile("red.shared.max.u32 [%0], %1;" ::"r"(lane == 0 ? sb + SM_MISC + MI_TMAX * 4 : dump + 128), "r"(tref + dt + (1u << 27)) : "memory");
        if (xc[0] | xc[1]) {
#pragma unroll
            for (int k = 0; k < 2; k++) {
                const int slot = atomicAdd(&mi[MI_XN], xc[k]);
                for (int r = 0; r < xc[k] && slot + r < 32; r++)
                    reinterpret_cast<uint32_t*>(smem + SC_XTRA)[slot + r] = ((tid + k * NTHR) >> 3) * 32 + r;
            }
        }
#pragma unroll
        for (int k = 0; k < 2; k++)
            mp[k * NTHR] = make_uint4(0, 0, 0, 0);
    }
    __syncthreads();
    STAMP(4);
    uint32_t* hist = reinterpret_cast<uint32_t*>(smem + SC_HIST);
    const int xn = mi[MI_XN];
    uint32_t xi = 0, xv = 1;
    if (warp < 10) {
        uint32_t* hp = hist + (warp * 2 + (lane >> 4)) * HS + (lane & 15) * 5;
        int c[5], s = 0;
#pragma unroll
        for (int j = 0; j < 5; j++) { c[j] = hp[j]; s += c[j]; }
        int inc = s;
#pragma unroll
        for (int o = 1; o < 16; o <<= 1) { int v = __shfl_up_sync(~0u, inc, o, 16); if ((lane & 15) >= o) inc += v; }
        int base = 0;
        if ((lane & 15) == 15) {
            const int tm = (warp * 2 + (lane >> 4)) / 5;
            base = tm * 256 + atomicAdd(&mi[MI_NU + tm], (inc + 3) >> 2);
            hp[5] = (base + ((inc + 3) >> 2)) << 16;
        }
        const int tot = __shfl_sync(~0u, inc, 15, 16);
        base = __shfl_sync(~0u, base, 15, 16);
        int ex = inc - s;
#pragma unroll
        for (int j = 0; j < 5; j++) {
            hp[j] = (base * 4 + ex) | ((base + ((ex == tot ? ex + 3 : ex + 1) >> 2)) << 16);
            ex += c[j];
        }
    } else if (warp == 10) {
        if (lane == 0) init_barriers();
        if (PF_B) l2_warm(PF_B, blk, lane, x, Y, ef);
        if (lane < xn) {
            xi = reinterpret_cast<const uint32_t*>(smem + SC_XTRA)[lane];
            asm volatile("ld.relaxed.gpu.global.u32 %0, [%1];" : "=r"(xv) : "l"(g_mail2 + blk * NSRC * 32 + xi) : "memory");
        }
    } else if (warp >= 12) {
        const uint32_t d = sb + (warp - 12) * NG * STAGE + lane * 16;
#pragma unroll
        for (int m = 0; m < 8; m++) {
            uint32_t w[4];
#pragma unroll
            for (int j = 0; j < 4; j++)
                w[j] = mul_lo(lds32(sb + SC_WR + (2 * t + (j & 1) + (j >> 1) * 8) * 256 + (((m * 8 + g) * 4) ^ (t << 5))), 0x3f003f00u);
            sts128(d + (m >> 2) * ROWP + (m & 3) * 512, __byte_perm(w[0], w[1], 0x5410), __byte_perm(w[0], w[1], 0x7632),
                   __byte_perm(w[2], w[3], 0x5410), __byte_perm(w[2], w[3], 0x7632));
        }
        uint32_t c[4];
#pragma unroll
        for (int i = 0; i < 4; i++) {
            const uint32_t ca = sb + SC_WR + 4096 + (i * 16 + (t & 1) * 8 + (g & 3)) * 2;
            c[i] = (lds16(ca) | (lds16(ca + 8) << 16)) & ((t >> 1) == (g >> 2) ? ~0u : 0u);
        }
        sts128(d + 2 * ROWP, c[0], c[1], c[2], c[3]);
    } else if (lane == 0) {
        sts32(sb + SC_GPOS + GDUMMY * 4, (uint32_t)(4 * UCAP * REC + 128) * 0x10001u);
        constexpr int start_ns = START_NS;
        mi[MI_T0] = (uint32_t)clock() + (((int)(((uint32_t)mi[MI_TMAX] << 5) + start_ns - gtime()) * 31) >> 4);
    }
    __syncthreads();
    STAMP(10);
    int myng = mi[MI_NU + (lane & 3)];
    const bool ovf = __any_sync(~0u, myng + xn > 2 * (UCAP - 4) || xn > 32);
    if (!ovf) {
        constexpr int pace = PACE_Q8, p1 = PACE_HEAD, b1 = HEAD_BK, p2 = PACE_TAIL, b2 = TAIL_BK, lead = PACE_LEAD;
        auto sched = [&](int b) { return b * pace - min(b, b1) * (pace - p1) - max(b - b2, 0) * (pace - p2) - lead; };
        if (warp < 10) {
            const int team = tid / NBK, b = tid - team * NBK;
            int lo[5], n[5], pos = team * UCAP * 2, nsum = 0;
#pragma unroll
            for (int q = 0; q < 5; q++) {
                lo[q] = hist[(team * 5 + q) * HS + b] >> 16;
                n[q] = (hist[(team * 5 + q) * HS + b + 1] >> 16) - lo[q];
                pos += lo[q] - (hist[(team * 5 + q) * HS] >> 16);
                nsum += n[q];
            }
            const int step = __float2int_rz(__fdividef((float)(sched(b + 1) - sched(b)), (float)max(nsum, 1)));
            const int tb = sched(b) + step / 2 - pos * step;
            const uint32_t t0 = mi[MI_T0];
            auto emit = [&](int q, int r, int pq) {
                const bool on = r < n[q];
                const uint32_t ro = (pq >> 1) * REC, par = pq & 1;
                sts32(on ? sb + SC_GPOS + (lo[q] + r) * 4 : dump, ro * 0x10001u + par * 0x40002u + (REC | (16 << 16)));
                sts8(on ? sb + SM_REC + 48 + ro + par : dump, q);
                sts16(on && !par ? sb + SM_REC + REC + 50 + ro : dump, (t0 + max(tb + pq * step, 0)) >> 2);
            };
#pragma unroll
            for (int q = 0, pq = pos; q < 5; pq += n[q], q++) emit(q, 0, pq);
#pragma unroll
            for (int q = 0; q < 5; pos += n[q], q++)
#pragma unroll 1
                for (int r = 1; __any_sync(~0u, r < n[q]); r++) emit(q, r, pos + r);
        } else if (warp == 10) {
            for (int n = 0; __any_sync(~0u, xv == 0); n++) {
                if (xv == 0) asm volatile("ld.relaxed.gpu.global.u32 %0, [%1];" : "=r"(xv) : "l"(g_mail2 + blk * NSRC * 32 + xi) : "memory");
                if (n > (1 << 20)) __trap();
            }
            const uint32_t w = xv & 0x3ffff, code = ((w >> 9) * 13108) >> 16, xt = lane < xn ? code / 20 : 4;
            const uint32_t same = __match_any_sync(~0u, xt);
            const int pq = __shfl_sync(~0u, myng, xt & 3) + __popc(same & ((1u << lane) - 1));
#pragma unroll
            for (int q = 0; q < 4; q++) {
                const int c = __popc(__ballot_sync(~0u, xt == q));
                if (lane == q) myng += c;
            }
            if (lane < xn) {
                g_mail2[blk * NSRC * 32 + xi] = 0;
                const uint32_t a = sb + SM_REC + (xt * UCAP + (pq >> 1)) * REC;
                sts16(a + REC + (pq & 1) * 2, xv >> 18);
                sts32(a + 16 + (pq & 1) * 4, (((xi >> 5) * EPC + w - code * 2560 - 1) * 8) | (code & 3));
                sts8(a + 48 + (pq & 1), (code >> 2) - xt * 5);
                if (!(pq & 1)) sts16(a + REC + 50, ((uint32_t)mi[MI_T0] + sched(NBK - 2)) >> 2);
            }
            if (lane < 4) {
                const uint32_t a = sb + SM_REC + (lane * UCAP + (myng >> 1)) * REC + 48;
                if (myng & 1) sts8(a + 1, 0);
                sts16(a + (myng & 1) * REC, 5);
                mi[MI_END + lane] = (myng + 1) >> 1;
            }
        }
#pragma unroll
        for (int i = 0; i < 8; i++) {
            const uint32_t p = en[i] < 0xc0000000u ? rk[i] + lds16(hr[i]) : GDUMMY * 4;
            hr[i] = sb + SC_GPOS + (p & ~3u);
            rk[i] = (p & 3) * 0x80004u;
        }
        __syncthreads();
        STAMP(11);
#pragma unroll
        for (int i = 0; i < 8; i++) rk[i] += lds32(hr[i]);
#pragma unroll
        for (int i = 0; i < 8; i++) {
            sts16(sb + SM_REC + (rk[i] & 0xffff), en[i] >> 18);
            sts32(sb + SM_REC + (rk[i] >> 16), em[i]);
        }
    } else {
        if (tid < 4) {
            sts16(sb + SM_REC + tid * UCAP * REC + 48, 5);
            mi[MI_END + tid] = 0;
        }
        generic_path(reinterpret_cast<float*>(smem), x, src, dst, Y, ef, w_rad, cg, xc[0], xc[1]);
    }

    __syncwarp();
    if (warp >= 8) {
        asm volatile("bar.sync 3, 512;" ::: "memory");
        asm volatile("setmaxnreg.dec.sync.aligned.u32 24;");
        const int team = warp & 3;
        if (ovf) {
            asm volatile("bar.sync 2;" ::: "memory");
            if (tid == 256) init_barriers();
            asm volatile("bar.sync 2;" ::: "memory");
        }
        STAMP(5);
        const uint32_t ring = sb + SM_RING + team * NG * STAGE;
        constexpr int lead = LEAD_CLK >> 2;
        const uint32_t q = lane >> 3, c = lane & 7, rec = sb + SM_REC + team * UCAP * REC;
        __syncwarp();
        producer_loop(reinterpret_cast<const char*>(x) + (ROWMODE == 0 ? c : ROWMODE == 1 ? lane & 15 : lane) * 16, reinterpret_cast<const char*>(ef) + (c & 1) * 16, Y,
                      q * ROWP + ((c ^ (q << 1)) << 4), q * 4 + (c & 2) * 8, (c & 1) * 2 + (c >> 2), ring, rec,
                      rec + (mi[MI_END + team] + 1) * REC, warp >= 12, lead, sb + SM_MISC + MI_SHIFT * 4,
                      ROWMODE == 1 ? (lane >> 4) * ROWP + (((lane & 15) ^ ((lane >> 4) << 1)) << 4) : lane * 16);
    } else {
        int team;
        {
            const int n0 = mi[MI_END], n1 = mi[MI_END + 1], n2 = mi[MI_END + 2], n3 = mi[MI_END + 3];
            const int d1 = abs(n0 + n1 - n2 - n3), d2 = abs(n0 + n2 - n1 - n3), d3 = abs(n0 + n3 - n1 - n2);
            const uint32_t perm = PAIRING && d1 < min(d2, d3) ? 0x3120 : PAIRING && d3 < d2 ? 0x2310 : 0x3210;
            team = __shfl_sync(~0u, (perm >> ((warp >> 1) * 4)) & 3, 0);
        }
        const int h = warp & 1;
        asm volatile("bar.arrive 3, 512;" ::: "memory");
        if (PF_C && warp == 0) l2_warm(PF_C, blk, lane, x, Y, ef);
        asm volatile("setmaxnreg.inc.sync.aligned.u32 232;");
        uint32_t ring = sb + SM_RING + team * NG * STAGE;
        uint32_t wf[4][4], cgf[4];
#pragma unroll
        for (int m = 0; m < 5; m++) {
            const uint4 v = lds128(ring + (m < 4 ? h * ROWP + m * 512 : 2 * ROWP) + lane * 16);
            uint32_t* f = m < 4 ? wf[m] : cgf;
            f[0] = v.x; f[1] = v.y; f[2] = v.z; f[3] = v.w;
        }
        float acc[5][4][2][4];
        if (!ovf) {
#pragma unroll
            for (int l = 0; l < 5; l++)
#pragma unroll
                for (int m = 0; m < 4; m++)
#pragma unroll
                    for (int p = 0; p < 2; p++)
#pragma unroll
                        for (int r = 0; r < 4; r++) acc[l][m][p][r] = 0.f;
        } else {
            const float* sagg = reinterpret_cast<const float*>(smem);
#pragma unroll
            for (int l = 0; l < 5; l++)
#pragma unroll
                for (int m = 0; m < 4; m++)
#pragma unroll
                    for (int p = 0; p < 2; p++)
#pragma unroll
                        for (int r = 0; r < 4; r++) {
                            int nd = l * 4 + (g >> 2) + (r >> 1) * 2;
                            int ch = h * 64 + m * 16 + 4 * t + (r & 1) * 2 + p;
                            acc[l][m][p][r] = nd < 19 ? sagg[(team * 19 + nd) * 512 + ch * 4 + (g & 3)] : 0.f;
                        }
            asm volatile("bar.sync 2;" ::: "memory");
            asm volatile("bar.sync 2;" ::: "memory");
        }
        const uint32_t xoff = t * ROWP + h * 512 + ((g ^ (t << 1)) << 4);
        const uint32_t mat = lane >> 3, mhi = (lane >> 2) & 1;
        const bool isy = mat < 2;
        const uint32_t ml = isy ? (t & 2) + (mat & 1) : t;
        const uint32_t moff = ml * ROWP + 2048 + (((isy ? 4 + 2 * mhi + (t & 1) : 2 * mhi + mat - 2) ^ (ml << 1)) << 4);
        __syncwarp();
        consumer_loop(acc, wf, cgf, xoff, ring, moff, sb + SM_REC + team * UCAP * REC);
        {
        int lane_;
        asm volatile("mov.u32 %0, %%laneid;" : "=r"(lane_));
        const int lane = lane_, g = lane >> 2, t = lane & 3;
        const uint32_t sb = ring - team * NG * STAGE;
        STAMP(7);
        asm volatile("bar.sync %0, 64;" ::"r"(4 + team) : "memory");
        {
            const int rr = ((g & 3) >> 1) * 8 + (g >> 2) * 2 + (g & 1);
#pragma unroll
            for (int l = 0; l < 5; l++)
#pragma unroll
                for (int hi = 0; hi < 2; hi++) {
                    const int R = l * 16 + rr + hi * 4;
                    const uint32_t a = sb + team * AGGT + h * 10240 + R * 128;
#pragma unroll
                    for (int c = 0; c < 2; c++) {
                        const int m = 2 * c;
                        sts128(a + (((2 * t + c) ^ (R & 7)) << 4),
                               pack_bf16(acc[l][m][0][2 * hi], acc[l][m][1][2 * hi]),
                               pack_bf16(acc[l][m][0][2 * hi + 1], acc[l][m][1][2 * hi + 1]),
                               pack_bf16(acc[l][m + 1][0][2 * hi], acc[l][m + 1][1][2 * hi]),
                               pack_bf16(acc[l][m + 1][0][2 * hi + 1], acc[l][m + 1][1][2 * hi + 1]));
                    }
                }
        }
        asm volatile("fence.proxy.async.shared::cta;" ::: "memory");
        uint32_t wa[8][4];
        {
            const int r = lane & 7, k = (lane >> 4) * 8 + r;
            const int chunk = (2 * warp + ((lane >> 3) & 1)) ^ r;
#pragma unroll
            for (int ks = 0; ks < 8; ks++) {
                const int c = (ks >> 2) * 64 + 16 * (k >> 2) + 4 * (ks & 3) + (k & 3);
                asm volatile("ldmatrix.sync.aligned.m8n8.x4.trans.shared.b16 {%0,%1,%2,%3}, [%4];"
                             : "=r"(wa[ks][0]), "=r"(wa[ks][1]), "=r"(wa[ks][2]), "=r"(wa[ks][3])
                             : "r"(sb + SM_W + c * 256 + (chunk << 4)));
            }
        }
        asm volatile("bar.sync 1, 256;" ::: "memory");
        STAMP(8);
        const int sl = (lane & 7) * 4 + (lane >> 3);
        __nv_bfloat16* op = out + (size_t)(blk * NPB + (lane >> 3)) * 512 + warp * 64 + (lane & 7) * 8;
        const int nleft = N_NODES - blk * NPB - (lane >> 3);
#pragma unroll 1
        for (int tm = 0; tm < 4; tm++) {
            float o[40];
            asm volatile("wgmma.fence.sync.aligned;" ::: "memory");
#pragma unroll
            for (int ks = 0; ks < 8; ks++) {
                const uint32_t a = sb + tm * AGGT + (ks >> 2) * 10240 + (ks & 3) * 32;
                const uint64_t desc = (uint64_t)((a & 0x3ffff) >> 4) | (1ull << 16) | (64ull << 32) | (1ull << 62);
                wgmma_n80(o, wa[ks], desc, ks);
            }
            asm volatile("wgmma.commit_group.sync.aligned;" ::: "memory");
            asm volatile("wgmma.wait_group.sync.aligned 0;" ::: "memory");
#pragma unroll
            for (int i = 0; i < 40; i++) asm volatile("" : "+f"(o[i])::"memory");
#pragma unroll
            for (int l = 0; l < 5; l++) {
                uint4 v;
                v.x = __shfl_sync(~0u, pack_bf16(o[8 * l + 0], o[8 * l + 1]), sl);
                v.y = __shfl_sync(~0u, pack_bf16(o[8 * l + 4], o[8 * l + 5]), sl);
                v.z = __shfl_sync(~0u, pack_bf16(o[8 * l + 2], o[8 * l + 3]), sl);
                v.w = __shfl_sync(~0u, pack_bf16(o[8 * l + 6], o[8 * l + 7]), sl);
                if ((l < 4 || lane < 24) && tm * 19 + l * 4 < nleft)
                    *reinterpret_cast<uint4*>(op + (tm * 19 + l * 4) * 512) = v;
            }
        }
        STAMP(9);
        }
    }
}

}

extern "C" void kernel_launch(void* const* d_in, const int* in_sizes, int n_in, void* d_out, int out_size) {
    (void)in_sizes; (void)n_in; (void)out_size;
    const __nv_bfloat16* x = (const __nv_bfloat16*)d_in[0];
    const int* src = (const int*)d_in[1];
    const int* dst = (const int*)d_in[2];
    const __nv_bfloat16* Y = (const __nv_bfloat16*)d_in[3];
    const __nv_bfloat16* ef = (const __nv_bfloat16*)d_in[4];
    const __nv_bfloat16* w_rad = (const __nv_bfloat16*)d_in[5];
    const __nv_bfloat16* cg = (const __nv_bfloat16*)d_in[6];
    const __nv_bfloat16* w_mix = (const __nv_bfloat16*)d_in[7];
    __nv_bfloat16* out = (__nv_bfloat16*)d_out;

    static int sms = 0;
    if (sms == 0) {
        int dev = 0;
        cudaGetDevice(&dev);
        cudaDeviceGetAttribute(&sms, cudaDevAttrMultiProcessorCount, dev);
        cudaFuncSetAttribute(tfn_kernel<3>, cudaFuncAttributeMaxDynamicSharedMemorySize, SM_TOTAL);
        cudaFuncSetAttribute(tfn_kernel<1>, cudaFuncAttributeMaxDynamicSharedMemorySize, SM_TOTAL);
        cudaFuncSetAttribute(tfn_kernel<2>, cudaFuncAttributeMaxDynamicSharedMemorySize, SM_TOTAL);
    }
    if (sms >= NB) {
        tfn_kernel<3><<<NB, NTHR, SM_TOTAL>>>(x, src, dst, Y, ef, w_rad, cg, w_mix, out);
    } else {
        tfn_kernel<1><<<NB, NTHR, SM_TOTAL>>>(x, src, dst, Y, ef, w_rad, cg, w_mix, out);
        tfn_kernel<2><<<NB, NTHR, SM_TOTAL>>>(x, src, dst, Y, ef, w_rad, cg, w_mix, out);
    }
}
```

```cpp
#include <cuda_runtime.h>
#include <cuda_bf16.h>
#include <stdint.h>

namespace {

constexpr int N_NODES = 10000;
constexpr int N_EDGES = 320000;
constexpr int NB      = 132;
constexpr int NPB     = 76;
constexpr int NSRC    = 128;
constexpr int EPC     = N_EDGES / NSRC;
constexpr int NTHR    = 512;
#define NGS 5
constexpr int NG      = NGS;
constexpr int ROWP    = 2176;
constexpr int STAGE   = 4 * ROWP + 128;
constexpr int UCAP    = 104;
constexpr int REC     = 52;
constexpr int NBK     = 80;
constexpr int HS      = 81;

#define PACE_Q8 635
#define PACE_LEAD 300
#define PACE_HEAD 730
#define HEAD_BK 10
#define PACE_TAIL 610
#define TAIL_BK 66
#define POLL_DELAY 1350
#define LEAD_CLK 600
#define ROWMODE 1
#define PAIRING 1
#define FEEDBACK 1
#define FB_GAIN 24
#define START_NS 3200

constexpr int SM_RING  = 0;
constexpr int SM_W     = 4 * NG * STAGE;
constexpr int SM_REC   = SM_W + 32768;
constexpr int SM_MISC  = SM_REC + 4 * UCAP * REC;
constexpr int SM_TOTAL = SM_MISC + 224;
constexpr int SC_MAIL  = 1 * STAGE;
constexpr int SC_CNT   = 3 * STAGE;
constexpr int SC_DUMP  = 3 * STAGE + 1024;
constexpr int SC_XTRA  = 3 * STAGE + 2048;
constexpr int SC_HIST  = 4 * STAGE;
constexpr int SC_GPOS  = 6 * STAGE;
constexpr int SC_WR    = 7 * STAGE;
constexpr int GDUMMY   = 1024;
constexpr int AGGT     = (NG * STAGE + 1023) / 1024 * 1024;
static_assert(3 * AGGT + 20480 <= 4 * NG * STAGE, "agg tile inside the team's ring");
static_assert(NPB * 512 * 4 <= 4 * NG * STAGE, "slow tile");
static_assert(SM_TOTAL <= 232448, "smem");
static_assert(SM_REC % 16 == 0 && (4 * UCAP * REC) % 16 == 0 && SM_MISC % 16 == 0, "align");
constexpr int MI_XN = 0;
constexpr int MI_TMAX = 2;
constexpr int MI_SHIFT = 48;
constexpr int MI_NU = 8;
constexpr int MI_END = 28;
constexpr int MI_T0 = 3;

__device__ uint4 g_mail[NB * NSRC * 8];
__device__ uint32_t g_mail2[NB * NSRC * 32];
__device__ __align__(128) int g_lag[2 * NB][32];
#define STAMP(k)

__device__ __forceinline__ uint32_t smem_u32(const void* p) { return (uint32_t)__cvta_generic_to_shared(p); }
__device__ __forceinline__ uint32_t atoms_inc(uint32_t a) {
    uint32_t r;
    asm volatile("atom.shared.add.u32 %0, [%1], 1;" : "=r"(r) : "r"(a) : "memory");
    return r;
}
__device__ __forceinline__ void sts32(uint32_t a, uint32_t v) { asm volatile("st.shared.u32 [%0], %1;" ::"r"(a), "r"(v) : "memory"); }
__device__ __forceinline__ void sts16(uint32_t a, uint32_t v) { asm volatile("st.shared.u16 [%0], %1;" ::"r"(a), "h"((uint16_t)v) : "memory"); }
__device__ __forceinline__ void sts8(uint32_t a, uint32_t v) { asm volatile("st.shared.u8 [%0], %1;" ::"r"(a), "r"(v) : "memory"); }
__device__ __forceinline__ uint32_t lds32(uint32_t a) { uint32_t v; asm volatile("ld.shared.u32 %0, [%1];" : "=r"(v) : "r"(a)); return v; }
__device__ __forceinline__ uint32_t lds16(uint32_t a) { uint32_t v; asm volatile("ld.shared.u16 %0, [%1];" : "=r"(v) : "r"(a)); return v; }
__device__ __forceinline__ void cp16(uint32_t d, const void* p) {
    asm volatile("cp.async.cg.shared.global [%0], [%1], 16;" ::"r"(d), "l"(p) : "memory");
}
__device__ __forceinline__ uint32_t gtime() {
    uint32_t t;
    asm volatile("mov.u32 %0, %%globaltimer_lo;" : "=r"(t));
    return t;
}
__device__ __forceinline__ void mbar_init(uint32_t bar, int cnt) {
    asm volatile("mbarrier.init.shared.b64 [%0], %1;" ::"r"(bar), "r"(cnt) : "memory");
}
__device__ __forceinline__ void mbar_wait(uint32_t bar, uint32_t parity) {
    asm volatile("{\n.reg .pred p;\n.reg .u32 n;\nmov.u32 n, 0;\n"
                 "WAIT_%=:\nmbarrier.try_wait.parity.shared.b64 p, [%0], %1;\n@p bra DONE_%=;\n"
                 "add.u32 n, n, 1;\nsetp.lt.u32 p, n, 4194304;\n@p bra WAIT_%=;\ntrap;\nDONE_%=:\n}"
                 ::"r"(bar), "r"(parity) : "memory");
}
__device__ __forceinline__ void mbar_arrive_elect(uint32_t bar) {
    asm volatile("{\n.reg .pred p;\nelect.sync _|p, 0xffffffff;\n@p mbarrier.arrive.shared.b64 _, [%0];\n}" ::"r"(bar) : "memory");
}
__device__ __forceinline__ uint4 lds128(uint32_t a) {
    uint4 v;
    asm volatile("ld.shared.v4.u32 {%0,%1,%2,%3}, [%4];" : "=r"(v.x), "=r"(v.y), "=r"(v.z), "=r"(v.w) : "r"(a));
    return v;
}
__device__ __forceinline__ void sts128(uint32_t a, uint32_t x, uint32_t y, uint32_t z, uint32_t w) {
    asm volatile("st.shared.v4.u32 [%0], {%1,%2,%3,%4};" ::"r"(a), "r"(x), "r"(y), "r"(z), "r"(w) : "memory");
}
__device__ __forceinline__ uint32_t pack_bf16(float lo, float hi) {
    uint32_t r;
    asm("cvt.rn.bf16x2.f32 %0, %1, %2;" : "=r"(r) : "f"(hi), "f"(lo));
    return r;
}
__device__ __forceinline__ float tanh_fast(float x) {
    float r;
    asm("tanh.approx.f32 %0, %1;" : "=f"(r) : "f"(x));
    return r;
}
__device__ __forceinline__ uint32_t mul_lo(uint32_t v, uint32_t r) {
    __nv_bfloat162 a = *reinterpret_cast<__nv_bfloat162*>(&v), b = *reinterpret_cast<__nv_bfloat162*>(&r);
    __nv_bfloat162 c = __hmul2(a, __low2bfloat162(b));
    return *reinterpret_cast<uint32_t*>(&c);
}
__device__ __forceinline__ uint32_t mul_hi(uint32_t v, uint32_t r) {
    __nv_bfloat162 a = *reinterpret_cast<__nv_bfloat162*>(&v), b = *reinterpret_cast<__nv_bfloat162*>(&r);
    __nv_bfloat162 c = __hmul2(a, __high2bfloat162(b));
    return *reinterpret_cast<uint32_t*>(&c);
}
__device__ __forceinline__ void mma0(float (&d)[4], uint32_t a0, uint32_t a1, uint32_t a2, uint32_t a3,
                                     uint32_t b0, uint32_t b1) {
    asm("mma.sync.aligned.m16n8k16.row.col.f32.bf16.bf16.f32 {%0,%1,%2,%3}, {%4,%5,%6,%7}, {%8,%9}, {%10,%10,%10,%10};"
        : "=f"(d[0]), "=f"(d[1]), "=f"(d[2]), "=f"(d[3])
        : "r"(a0), "r"(a1), "r"(a2), "r"(a3), "r"(b0), "r"(b1), "f"(0.f));
}
__device__ __forceinline__ void mma0_k8(float (&d)[4], uint32_t a0, uint32_t a1, uint32_t b0) {
    asm("mma.sync.aligned.m16n8k8.row.col.f32.bf16.bf16.f32 {%0,%1,%2,%3}, {%4,%5}, {%6}, {%7,%7,%7,%7};"
        : "=f"(d[0]), "=f"(d[1]), "=f"(d[2]), "=f"(d[3])
        : "r"(a0), "r"(a1), "r"(b0), "f"(0.f));
}
__device__ __forceinline__ void mma_acc(float (&d)[4], const uint32_t (&a)[4], uint32_t b0, uint32_t b1) {
    asm volatile("mma.sync.aligned.m16n8k16.row.col.f32.bf16.bf16.f32 {%0,%1,%2,%3}, {%4,%5,%6,%7}, {%8,%9}, {%0,%1,%2,%3};"
        : "+f"(d[0]), "+f"(d[1]), "+f"(d[2]), "+f"(d[3])
        : "r"(a[0]), "r"(a[1]), "r"(a[2]), "r"(a[3]), "r"(b0), "r"(b1));
}
__device__ __forceinline__ void wgmma_n80(float (&d)[40], const uint32_t (&a)[4], uint64_t desc, int scale_d) {
    asm volatile("{\n.reg .pred p;\nsetp.ne.b32 p, %45, 0;\n"
        "wgmma.mma_async.sync.aligned.m64n80k16.f32.bf16.bf16 "
        "{%0,%1,%2,%3,%4,%5,%6,%7,%8,%9,%10,%11,%12,%13,%14,%15,%16,%17,%18,%19,"
        "%20,%21,%22,%23,%24,%25,%26,%27,%28,%29,%30,%31,%32,%33,%34,%35,%36,%37,%38,%39}, "
        "{%40,%41,%42,%43}, %44, p, 1, 1, 0;\n}"
        : "+f"(d[0]), "+f"(d[1]), "+f"(d[2]), "+f"(d[3]), "+f"(d[4]), "+f"(d[5]), "+f"(d[6]), "+f"(d[7]),
          "+f"(d[8]), "+f"(d[9]), "+f"(d[10]), "+f"(d[11]), "+f"(d[12]), "+f"(d[13]), "+f"(d[14]), "+f"(d[15]),
          "+f"(d[16]), "+f"(d[17]), "+f"(d[18]), "+f"(d[19]), "+f"(d[20]), "+f"(d[21]), "+f"(d[22]), "+f"(d[23]),
          "+f"(d[24]), "+f"(d[25]), "+f"(d[26]), "+f"(d[27]), "+f"(d[28]), "+f"(d[29]), "+f"(d[30]), "+f"(d[31]),
          "+f"(d[32]), "+f"(d[33]), "+f"(d[34]), "+f"(d[35]), "+f"(d[36]), "+f"(d[37]), "+f"(d[38]), "+f"(d[39])
        : "r"(a[0]), "r"(a[1]), "r"(a[2]), "r"(a[3]), "l"(desc), "r"(scale_d));
}

__device__ __forceinline__ void producer_loop(const void* xl, const void* efl, const void* Y, uint32_t xd, uint32_t oef,
                                              uint32_t ysel, uint32_t ring, uint32_t rec, uint32_t rlast, uint32_t odd,
                                              uint32_t lag, uint32_t xh) {
    asm volatile(
        "{\n"
        ".reg .b32 w, em, ey, cu, d, t, u, n, sa, ph, rp, rend, rlast, dy, sv, lag, lv, w2, w3, w4;\n"
        ".reg .b16 tg;\n"
        ".reg .b64 pa, pb, pc, pd;\n"
        ".reg .pred lo, z, q, e, zb, fbk;\n"
        "redux.sync.or.b32 sa, %6, 0xffffffff;\n"
        "redux.sync.or.b32 rp, %7, 0xffffffff;\n"
        "redux.sync.or.b32 rlast, %8, 0xffffffff;\n"
        "redux.sync.or.b32 lag, %11, 0xffffffff;\n"
        "setp.eq.u32 fbk, %9, 0;\n"
        "add.u32 rend, sa, 44160;\n"
        "and.b32 t, %5, 1;\n"
        "setp.eq.u32 lo, t, 0;\n"
        "mov.u32 ph, 1;\n"
        "setp.ge.u32 q, %9, 4;\n"
        "@q bra.uni PODD_%=;\n"
        "add.u32 t, rp, %4;\n"
        "ld.shared.u32 em, [t+16];\n"
        "and.b32 t, em, 0xfffffff8;\n"
        "mad.wide.u32 pa, t, 4, %1;\n"
        "add.u32 d, sa, %3;\n"
        "@lo cp.async.cg.shared.global [d+2048], [pa], 16;\n"
        "cp.async.mbarrier.arrive.noinc.shared.b64 [sa+8704];\n"
        "add.u32 rp, rp, 52;\n"
        "add.u32 sa, sa, 8832;\n"
        "PODD_%=:\n"
        "add.u32 rp, rp, 52;\n"
        "add.u32 sa, sa, 8832;\n"
        "shr.u32 t, %4, 1;\n"
        "and.b32 t, t, 4;\n"
        "add.u32 t, t, rp;\n"
        "ld.shared.u32 w, [t];\n"
        "ld.shared.u32 w2, [t+8];\n"
        "add.u32 t, rp, %4;\n"
        "ld.shared.u32 em, [t+16];\n"
        "ld.shared.u32 ey, [t+-36];\n"
        "ld.shared.u32 cu, [rp+48];\n"
        "ld.volatile.shared.u32 sv, [lag];\n"
        "setp.eq.u32 e, sa, sa;\n"
        "setp.lt.u32 q, rp, rlast;\n"
        "@!q bra.uni PF_%=;\n"
        "PL_%=:\n"
        "add.u32 cu, cu, sv;\n"
        "mov.u32 u, %%clock;\n"
        "shl.b32 u, u, 14;\n"
        "sub.u32 u, u, cu;\n"
        "setp.ge.and.s32 q, u, 0, e;\n"
        "@q bra.uni PGO_%=;\n"
        "mov.u32 n, 0;\n"
        "PW1_%=:\n"
        "@e bra.uni PW2_%=;\n"
        "mbarrier.try_wait.parity.shared.b64 e, [sa+8712], ph;\n"
        "add.u32 n, n, 1;\n"
        "setp.lt.u32 q, n, 4194304;\n"
        "@q bra.uni PW1_%=;\n"
        "trap;\n"
        "PW2_%=:\n"
        "mov.u32 u, %%clock;\n"
        "shl.b32 u, u, 14;\n"
        "sub.u32 u, u, cu;\n"
        "setp.lt.s32 q, u, 0;\n"
        "@q bra.uni PW2_%=;\n"
        "PGO_%=:\n"
        "and.b32 t, em, 0xfffffff8;\n"
        "mad.wide.u32 pa, t, 4, %1;\n"
        "and.b32 t, w, 0xffff;\n"
        "mad.wide.u32 pc, t, 1024, %0;\n"
        "shr.u32 t, w, 16;\n"
        "mad.wide.u32 pd, t, 1024, %0;\n"
        "add.u32 d, sa, %3;\n"
        "@lo cp.async.cg.shared.global [d+2048], [pa], 16;\n"
        "xor.b32 t, ey, %5;\n"
        "and.b32 t, t, 7;\n"
        "setp.ne.u32 zb, t, 0;\n"
        "and.b32 t, ey, 0xfffffff8;\n"
        "cvt.u64.u32 pb, t;\n"
        "add.u64 pb, pb, %2;\n"
        "selp.u32 dy, 64, 8, lo;\n"
        "xor.b32 dy, dy, d;\n"
        "cp.async.ca.shared.global [dy+2048], [pb], 8, zb;\n"
        "add.u32 d, sa, %12;\n"
        "cp.async.cg.shared.global [d+0], [pc+0], 16;\n"
        "cp.async.cg.shared.global [d+256], [pc+256], 16;\n"
        "cp.async.cg.shared.global [d+512], [pc+512], 16;\n"
        "cp.async.cg.shared.global [d+768], [pc+768], 16;\n"
        "cp.async.cg.shared.global [d+1024], [pd+0], 16;\n"
        "cp.async.cg.shared.global [d+1280], [pd+256], 16;\n"
        "cp.async.cg.shared.global [d+1536], [pd+512], 16;\n"
        "cp.async.cg.shared.global [d+1792], [pd+768], 16;\n"
        "xor.b32 dy, d, 64;\n"
        "and.b32 t, w2, 0xffff;\n"
        "mad.wide.u32 pa, t, 1024, %0;\n"
        "cp.async.cg.shared.global [dy+4352], [pa+0], 16;\n"
        "cp.async.cg.shared.global [dy+4608], [pa+256], 16;\n"
        "cp.async.cg.shared.global [dy+4864], [pa+512], 16;\n"
        "cp.async.cg.shared.global [dy+5120], [pa+768], 16;\n"
        "shr.u32 t, w2, 16;\n"
        "mad.wide.u32 pb, t, 1024, %0;\n"
        "cp.async.cg.shared.global [dy+5376], [pb+0], 16;\n"
        "cp.async.cg.shared.global [dy+5632], [pb+256], 16;\n"
        "cp.async.cg.shared.global [dy+5888], [pb+512], 16;\n"
        "cp.async.cg.shared.global [dy+6144], [pb+768], 16;\n"
        "add.u32 rp, rp, 104;\n"
        "shr.u32 t, %4, 1;\n"
        "and.b32 t, t, 4;\n"
        "add.u32 t, t, rp;\n"
        "ld.shared.u32 w, [t];\n"
        "ld.shared.u32 w2, [t+8];\n"
        "add.u32 t, rp, %4;\n"
        "ld.shared.u32 em, [t+16];\n"
        "ld.shared.u32 ey, [t+-36];\n"
        "ld.shared.u32 cu, [rp+48];\n"
        "ld.volatile.shared.u32 sv, [lag];\n"
        "cp.async.mbarrier.arrive.noinc.shared.b64 [sa+8704];\n"
        "add.u32 sa, sa, 17664;\n"
        "sub.u32 t, sa, 44160;\n"
        "setp.ge.u32 q, sa, rend;\n"
        "selp.u32 sa, t, sa, q;\n"
        "selp.u32 t, 1, 0, q;\n"
        "xor.b32 ph, ph, t;\n"
        "mbarrier.try_wait.parity.shared.b64 e, [sa+8712], ph;\n"
        "@!fbk bra.uni PC_%=;\n"
        "ld.shared.u32 t, [rp+-56];\n"
        "mov.u32 u, %%clock;\n"
        "shl.b32 u, u, 14;\n"
        "sub.u32 u, u, t;\n"
        "sub.u32 u, u, sv;\n"
        "shr.s32 u, u, 16;\n"
        "ld.volatile.shared.u64 pa, [lag+16];\n"
        "elect.sync _|z, 0xffffffff;\n"
        "@z st.relaxed.gpu.global.u32 [pa], u;\n"
        "@z cp.async.cg.shared.global [lag], [pa+16896], 16;\n"
        "PC_%=:\n"
        "setp.lt.u32 q, rp, rlast;\n"
        "@q bra.uni PL_%=;\n"
        "PF_%=:\n"
        "setp.ne.u32 q, rp, rlast;\n"
        "@q bra.uni PX_%=;\n"
        "mov.u32 n, 0;\n"
        "PE1_%=:\n"
        "@e bra.uni PE2_%=;\n"
        "mbarrier.try_wait.parity.shared.b64 e, [sa+8712], ph;\n"
        "add.u32 n, n, 1;\n"
        "setp.lt.u32 q, n, 4194304;\n"
        "@q bra.uni PE1_%=;\n"
        "trap;\n"
        "PE2_%=:\n"
        "cp.async.mbarrier.arrive.noinc.shared.b64 [sa+8704];\n"
        "PX_%=:\n"
        "}\n"
        ::"l"(xl), "l"(efl), "l"(Y), "r"(xd), "r"(oef), "r"(ysel), "r"(ring), "r"(rec), "r"(rlast), "r"(odd),
          "n"(0), "r"(lag), "r"(xh) : "memory");
}

__device__ __forceinline__ void consumer_loop(float (&acc)[5][4][2][4], const uint32_t (&wf)[4][4], const uint32_t (&cgf)[4],
                                              uint32_t xoff, uint32_t& ring, uint32_t moff, uint32_t rec) {
    asm volatile(
        "{\n"
        ".reg .b32 x<16>, a<4>, b<4>, r<4>, m<4>, rl, rh, tag, la, lb, sa, last, ph, tq, xa, ma, n, ring, sn, ln, yb, zz, k<4>, tp;\n"
        ".reg .b16 lo, hi;\n"
        ".reg .f32 p<16>, d<4>, t0, t1, fz;\n"
        ".reg .pred q, w, el, c<5>;\n"
        "TA_%=: .branchtargets A0_%=, A1_%=, A2_%=, A3_%=, A4_%=, EXIT_%=;\n"
        "TB_%=: .branchtargets B0_%=, B1_%=, B2_%=, B3_%=, B4_%=, SPIN_%=;\n"
        "mov.f32 fz, 0f00000000;\n"
        "redux.sync.or.b32 ring, %160, 0xffffffff;\n"
        "mov.u32 sa, ring;\n"
        "add.u32 last, ring, 35328;\n"
        "mov.u32 ph, 0;\n"
        "redux.sync.xor.b32 zz, %160, 0xffffffff;\n"
        "redux.sync.or.b32 tp, %183, 0xffffffff;\n"
        "elect.sync _|el, 0xffffffff;\n"
        "mov.u32 k0, sa;\n"
        "mov.u32 k1, sa;\n"
        "mov.u32 k2, sa;\n"
        "mov.u32 k3, sa;\n"
        "mov.b32 x0, 0;\n"
        "mov.b32 x1, 0;\n"
        "mov.b32 x2, 0;\n"
        "mov.b32 x3, 0;\n"
        "mov.b32 x4, 0;\n"
        "mov.b32 x5, 0;\n"
        "mov.b32 x6, 0;\n"
        "mov.b32 x7, 0;\n"
        "mov.b32 x8, 0;\n"
        "mov.b32 x9, 0;\n"
        "mov.b32 x10, 0;\n"
        "mov.b32 x11, 0;\n"
        "mov.b32 x12, 0;\n"
        "mov.b32 x13, 0;\n"
        "mov.b32 x14, 0;\n"
        "mov.b32 x15, 0;\n"
        "mov.b32 b0, 0;\n"
        "mov.b32 r0, 0;\n"
        "mov.b32 b1, 0;\n"
        "mov.b32 r1, 0;\n"
        "mov.b32 b2, 0;\n"
        "mov.b32 r2, 0;\n"
        "mov.b32 b3, 0;\n"
        "mov.b32 r3, 0;\n"
        "mov.u32 lb, 0;\n"
        "mov.u32 n, 0;\n"
        "W0_%=:\n"
        "mbarrier.try_wait.parity.shared.b64 w, [sa+8704], 0;\n"
        "@w bra.uni W0D_%=;\n"
        "add.u32 n, n, 1;\n"
        "setp.lt.u32 q, n, 4194304;\n"
        "@q bra.uni W0_%=;\n"
        "trap;\n"
        "W0D_%=:\n"
        "add.u32 ma, sa, %182;\n"
        "ldmatrix.sync.aligned.m8n8.x4.shared.b16 {m0,m1,m2,m3}, [ma];\n"
        "ld.shared.u16 tag, [tp+48];\n"
        "add.u32 tp, tp, 52;\n"
        "add.u32 sn, sa, 8832;\n"
        "setp.eq.u32 q, sa, last;\n"
        "selp.u32 sn, ring, sn, q;\n"
        "selp.u32 tq, 1, 0, q;\n"
        "xor.b32 ph, ph, tq;\n"
        "mbarrier.test_wait.parity.shared.b64 w, [sn+8704], ph;\n"
        "mma.sync.aligned.m16n8k16.row.col.f32.bf16.bf16.f32 {p0,p1,p2,p3}, {%161,%162,%163,%164}, {m2,m3}, {fz,fz,fz,fz};\n"
        "mma.sync.aligned.m16n8k16.row.col.f32.bf16.bf16.f32 {p4,p5,p6,p7}, {%165,%166,%167,%168}, {m2,m3}, {fz,fz,fz,fz};\n"
        "mma.sync.aligned.m16n8k16.row.col.f32.bf16.bf16.f32 {p8,p9,p10,p11}, {%169,%170,%171,%172}, {m2,m3}, {fz,fz,fz,fz};\n"
        "mma.sync.aligned.m16n8k16.row.col.f32.bf16.bf16.f32 {p12,p13,p14,p15}, {%173,%174,%175,%176}, {m2,m3}, {fz,fz,fz,fz};\n"
        "@el mbarrier.arrive.shared.b64 _, [k0+8712];\n"
        "redux.sync.or.b32 ln, tag, 0xffffffff;\n"
        "mov.u32 sa, sn;\n"
        "add.u32 k0, sn, zz;\n"
        "SPIN_%=:\n"
        "mov.u32 n, 0;\n"
        "SP1_%=:\n"
        "mbarrier.try_wait.parity.shared.b64 w, [sa+8704], ph;\n"
        "@w bra.uni SP2_%=;\n"
        "add.u32 n, n, 1;\n"
        "setp.lt.u32 q, n, 4194304;\n"
        "@q bra.uni SP1_%=;\n"
        "trap;\n"
        "SP2_%=:\n"
        "brx.idx.uni lb, TB_%=;\n"
        "A0_%=:\n"
        "add.u32 xa, sa, %181;\n"
        "add.u32 ma, sa, %182;\n"
        "ldmatrix.sync.aligned.m8n8.x4.shared.b16 {m0,m1,m2,m3}, [ma];\n"
        "ld.shared.u16 tag, [tp+48];\n"
        "add.u32 tp, tp, 52;\n"
        "add.u32 sn, sa, 8832;\n"
        "setp.eq.u32 q, sa, last;\n"
        "selp.u32 sn, ring, sn, q;\n"
        "selp.u32 tq, 1, 0, q;\n"
        "xor.b32 ph, ph, tq;\n"
        "mbarrier.test_wait.parity.shared.b64 w, [sn+8704], ph;\n"
        "mma.sync.aligned.m16n8k16.row.col.f32.bf16.bf16.f32 {%0,%1,%2,%3}, {a0,a1,a2,a3}, {x0,x1}, {%0,%1,%2,%3};\n"
        "mma.sync.aligned.m16n8k16.row.col.f32.bf16.bf16.f32 {%4,%5,%6,%7}, {a0,a1,a2,a3}, {x2,x3}, {%4,%5,%6,%7};\n"
        "ld.shared.v4.u32 {x0,x1,x2,x3}, [xa+1024];\n"
        "tanh.approx.f32 t0, p1;\n"
        "tanh.approx.f32 t1, p3;\n"
        "fma.rn.f32 t0, p1, t0, p1;\n"
        "fma.rn.f32 t1, p3, t1, p3;\n"
        "cvt.rn.bf16x2.f32 r0, t1, t0;\n"
        "mma.sync.aligned.m16n8k16.row.col.f32.bf16.bf16.f32 {p0,p1,p2,p3}, {%161,%162,%163,%164}, {m2,m3}, {fz,fz,fz,fz};\n"
        "mma.sync.aligned.m16n8k16.row.col.f32.bf16.bf16.f32 {%8,%9,%10,%11}, {a0,a1,a2,a3}, {x4,x5}, {%8,%9,%10,%11};\n"
        "mma.sync.aligned.m16n8k16.row.col.f32.bf16.bf16.f32 {%12,%13,%14,%15}, {a0,a1,a2,a3}, {x6,x7}, {%12,%13,%14,%15};\n"
        "ld.shared.v4.u32 {x4,x5,x6,x7}, [xa+1152];\n"
        "mma.sync.aligned.m16n8k8.row.col.f32.bf16.bf16.f32 {d0,d1,d2,d3}, {%177,%178}, {m1}, {fz,fz,fz,fz};\n"
        "cvt.rn.bf16x2.f32 b0, d2, d0;\n"
        "cvt.rn.bf16x2.f32 b1, d3, d1;\n"
        "tanh.approx.f32 t0, p5;\n"
        "tanh.approx.f32 t1, p7;\n"
        "fma.rn.f32 t0, p5, t0, p5;\n"
        "fma.rn.f32 t1, p7, t1, p7;\n"
        "cvt.rn.bf16x2.f32 r1, t1, t0;\n"
        "mma.sync.aligned.m16n8k16.row.col.f32.bf16.bf16.f32 {p4,p5,p6,p7}, {%165,%166,%167,%168}, {m2,m3}, {fz,fz,fz,fz};\n"
        "mov.b32 {lo,hi}, r2;\n"
        "mov.b32 rl, {lo,lo};\n"
        "mov.b32 rh, {hi,hi};\n"
        "mul.bf16x2 x8, x8, rl;\n"
        "mul.bf16x2 x9, x9, rl;\n"
        "mul.bf16x2 x10, x10, rh;\n"
        "mul.bf16x2 x11, x11, rh;\n"
        "mma.sync.aligned.m16n8k16.row.col.f32.bf16.bf16.f32 {%16,%17,%18,%19}, {a0,a1,a2,a3}, {x8,x9}, {%16,%17,%18,%19};\n"
        "mma.sync.aligned.m16n8k16.row.col.f32.bf16.bf16.f32 {%20,%21,%22,%23}, {a0,a1,a2,a3}, {x10,x11}, {%20,%21,%22,%23};\n"
        "ld.shared.v4.u32 {x8,x9,x10,x11}, [xa+1280];\n"
        "mma.sync.aligned.m16n8k8.row.col.f32.bf16.bf16.f32 {d0,d1,d2,d3}, {%179,%180}, {m1}, {fz,fz,fz,fz};\n"
        "cvt.rn.bf16x2.f32 b2, d2, d0;\n"
        "cvt.rn.bf16x2.f32 b3, d3, d1;\n"
        "tanh.approx.f32 t0, p9;\n"
        "tanh.approx.f32 t1, p11;\n"
        "fma.rn.f32 t0, p9, t0, p9;\n"
        "fma.rn.f32 t1, p11, t1, p11;\n"
        "cvt.rn.bf16x2.f32 r2, t1, t0;\n"
        "mma.sync.aligned.m16n8k16.row.col.f32.bf16.bf16.f32 {p8,p9,p10,p11}, {%169,%170,%171,%172}, {m2,m3}, {fz,fz,fz,fz};\n"
        "selp.u32 tq, lb, 5, w;\n"
        "mov.b32 {lo,hi}, r3;\n"
        "mov.b32 rl, {lo,lo};\n"
        "mov.b32 rh, {hi,hi};\n"
        "mul.bf16x2 x12, x12, rl;\n"
        "mul.bf16x2 x13, x13, rl;\n"
        "mul.bf16x2 x14, x14, rh;\n"
        "mul.bf16x2 x15, x15, rh;\n"
        "mma.sync.aligned.m16n8k16.row.col.f32.bf16.bf16.f32 {%24,%25,%26,%27}, {a0,a1,a2,a3}, {x12,x13}, {%24,%25,%26,%27};\n"
        "mma.sync.aligned.m16n8k16.row.col.f32.bf16.bf16.f32 {%28,%29,%30,%31}, {a0,a1,a2,a3}, {x14,x15}, {%28,%29,%30,%31};\n"
        "ld.shared.v4.u32 {x12,x13,x14,x15}, [xa+1408];\n"
        "@el mbarrier.arrive.shared.b64 _, [k0+8712];\n"
        "redux.sync.or.b32 ln, tag, 0xffffffff;\n"
        "mov.u32 sa, sn;\n"
        "add.u32 k0, sn, zz;\n"
        "tanh.approx.f32 t0, p13;\n"
        "tanh.approx.f32 t1, p15;\n"
        "fma.rn.f32 t0, p13, t0, p13;\n"
        "fma.rn.f32 t1, p15, t1, p15;\n"
        "cvt.rn.bf16x2.f32 r3, t1, t0;\n"
        "mma.sync.aligned.m16n8k16.row.col.f32.bf16.bf16.f32 {p12,p13,p14,p15}, {%173,%174,%175,%176}, {m2,m3}, {fz,fz,fz,fz};\n"
        "mov.b32 {lo,hi}, r0;\n"
        "mov.b32 rl, {lo,lo};\n"
        "mov.b32 rh, {hi,hi};\n"
        "mul.bf16x2 x0, x0, rl;\n"
        "mul.bf16x2 x1, x1, rl;\n"
        "mul.bf16x2 x2, x2, rh;\n"
        "mul.bf16x2 x3, x3, rh;\n"
        "mov.b32 {lo,hi}, r1;\n"
        "mov.b32 rl, {lo,lo};\n"
        "mov.b32 rh, {hi,hi};\n"
        "mul.bf16x2 x4, x4, rl;\n"
        "mul.bf16x2 x5, x5, rl;\n"
        "mul.bf16x2 x6, x6, rh;\n"
        "mul.bf16x2 x7, x7, rh;\n"
        "brx.idx.uni tq, TB_%=;\n"
        "A1_%=:\n"
        "add.u32 xa, sa, %181;\n"
        "add.u32 ma, sa, %182;\n"
        "ldmatrix.sync.aligned.m8n8.x4.shared.b16 {m0,m1,m2,m3}, [ma];\n"
        "ld.shared.u16 tag, [tp+48];\n"
        "add.u32 tp, tp, 52;\n"
        "add.u32 sn, sa, 8832;\n"
        "setp.eq.u32 q, sa, last;\n"
        "selp.u32 sn, ring, sn, q;\n"
        "selp.u32 tq, 1, 0, q;\n"
        "xor.b32 ph, ph, tq;\n"
        "mbarrier.test_wait.parity.shared.b64 w, [sn+8704], ph;\n"
        "mma.sync.aligned.m16n8k16.row.col.f32.bf16.bf16.f32 {%32,%33,%34,%35}, {a0,a1,a2,a3}, {x0,x1}, {%32,%33,%34,%35};\n"
        "mma.sync.aligned.m16n8k16.row.col.f32.bf16.bf16.f32 {%36,%37,%38,%39}, {a0,a1,a2,a3}, {x2,x3}, {%36,%37,%38,%39};\n"
        "ld.shared.v4.u32 {x0,x1,x2,x3}, [xa+1024];\n"
        "tanh.approx.f32 t0, p1;\n"
        "tanh.approx.f32 t1, p3;\n"
        "fma.rn.f32 t0, p1, t0, p1;\n"
        "fma.rn.f32 t1, p3, t1, p3;\n"
        "cvt.rn.bf16x2.f32 r0, t1, t0;\n"
        "mma.sync.aligned.m16n8k16.row.col.f32.bf16.bf16.f32 {p0,p1,p2,p3}, {%161,%162,%163,%164}, {m2,m3}, {fz,fz,fz,fz};\n"
        "mma.sync.aligned.m16n8k16.row.col.f32.bf16.bf16.f32 {%40,%41,%42,%43}, {a0,a1,a2,a3}, {x4,x5}, {%40,%41,%42,%43};\n"
        "mma.sync.aligned.m16n8k16.row.col.f32.bf16.bf16.f32 {%44,%45,%46,%47}, {a0,a1,a2,a3}, {x6,x7}, {%44,%45,%46,%47};\n"
        "ld.shared.v4.u32 {x4,x5,x6,x7}, [xa+1152];\n"
        "mma.sync.aligned.m16n8k8.row.col.f32.bf16.bf16.f32 {d0,d1,d2,d3}, {%177,%178}, {m1}, {fz,fz,fz,fz};\n"
        "cvt.rn.bf16x2.f32 b0, d2, d0;\n"
        "cvt.rn.bf16x2.f32 b1, d3, d1;\n"
        "tanh.approx.f32 t0, p5;\n"
        "tanh.approx.f32 t1, p7;\n"
        "fma.rn.f32 t0, p5, t0, p5;\n"
        "fma.rn.f32 t1, p7, t1, p7;\n"
        "cvt.rn.bf16x2.f32 r1, t1, t0;\n"
        "mma.sync.aligned.m16n8k16.row.col.f32.bf16.bf16.f32 {p4,p5,p6,p7}, {%165,%166,%167,%168}, {m2,m3}, {fz,fz,fz,fz};\n"
        "mov.b32 {lo,hi}, r2;\n"
        "mov.b32 rl, {lo,lo};\n"
        "mov.b32 rh, {hi,hi};\n"
        "mul.bf16x2 x8, x8, rl;\n"
        "mul.bf16x2 x9, x9, rl;\n"
        "mul.bf16x2 x10, x10, rh;\n"
        "mul.bf16x2 x11, x11, rh;\n"
        "mma.sync.aligned.m16n8k16.row.col.f32.bf16.bf16.f32 {%48,%49,%50,%51}, {a0,a1,a2,a3}, {x8,x9}, {%48,%49,%50,%51};\n"
        "mma.sync.aligned.m16n8k16.row.col.f32.bf16.bf16.f32 {%52,%53,%54,%55}, {a0,a1,a2,a3}, {x10,x11}, {%52,%53,%54,%55};\n"
        "ld.shared.v4.u32 {x8,x9,x10,x11}, [xa+1280];\n"
        "mma.sync.aligned.m16n8k8.row.col.f32.bf16.bf16.f32 {d0,d1,d2,d3}, {%179,%180}, {m1}, {fz,fz,fz,fz};\n"
        "cvt.rn.bf16x2.f32 b2, d2, d0;\n"
        "cvt.rn.bf16x2.f32 b3, d3, d1;\n"
        "tanh.approx.f32 t0, p9;\n"
        "tanh.approx.f32 t1, p11;\n"
        "fma.rn.f32 t0, p9, t0, p9;\n"
        "fma.rn.f32 t1, p11, t1, p11;\n"
        "cvt.rn.bf16x2.f32 r2, t1, t0;\n"
        "mma.sync.aligned.m16n8k16.row.col.f32.bf16.bf16.f32 {p8,p9,p10,p11}, {%169,%170,%171,%172}, {m2,m3}, {fz,fz,fz,fz};\n"
        "selp.u32 tq, lb, 5, w;\n"
        "mov.b32 {lo,hi}, r3;\n"
        "mov.b32 rl, {lo,lo};\n"
        "mov.b32 rh, {hi,hi};\n"
        "mul.bf16x2 x12, x12, rl;\n"
        "mul.bf16x2 x13, x13, rl;\n"
        "mul.bf16x2 x14, x14, rh;\n"
        "mul.bf16x2 x15, x15, rh;\n"
        "mma.sync.aligned.m16n8k16.row.col.f32.bf16.bf16.f32 {%56,%57,%58,%59}, {a0,a1,a2,a3}, {x12,x13}, {%56,%57,%58,%59};\n"
        "mma.sync.aligned.m16n8k16.row.col.f32.bf16.bf16.f32 {%60,%61,%62,%63}, {a0,a1,a2,a3}, {x14,x15}, {%60,%61,%62,%63};\n"
        "ld.shared.v4.u32 {x12,x13,x14,x15}, [xa+1408];\n"
        "@el mbarrier.arrive.shared.b64 _, [k0+8712];\n"
        "redux.sync.or.b32 ln, tag, 0xffffffff;\n"
        "mov.u32 sa, sn;\n"
        "add.u32 k0, sn, zz;\n"
        "tanh.approx.f32 t0, p13;\n"
        "tanh.approx.f32 t1, p15;\n"
        "fma.rn.f32 t0, p13, t0, p13;\n"
        "fma.rn.f32 t1, p15, t1, p15;\n"
        "cvt.rn.bf16x2.f32 r3, t1, t0;\n"
        "mma.sync.aligned.m16n8k16.row.col.f32.bf16.bf16.f32 {p12,p13,p14,p15}, {%173,%174,%175,%176}, {m2,m3}, {fz,fz,fz,fz};\n"
        "mov.b32 {lo,hi}, r0;\n"
        "mov.b32 rl, {lo,lo};\n"
        "mov.b32 rh, {hi,hi};\n"
        "mul.bf16x2 x0, x0, rl;\n"
        "mul.bf16x2 x1, x1, rl;\n"
        "mul.bf16x2 x2, x2, rh;\n"
        "mul.bf16x2 x3, x3, rh;\n"
        "mov.b32 {lo,hi}, r1;\n"
        "mov.b32 rl, {lo,lo};\n"
        "mov.b32 rh, {hi,hi};\n"
        "mul.bf16x2 x4, x4, rl;\n"
        "mul.bf16x2 x5, x5, rl;\n"
        "mul.bf16x2 x6, x6, rh;\n"
        "mul.bf16x2 x7, x7, rh;\n"
        "brx.idx.uni tq, TB_%=;\n"
        "A2_%=:\n"
        "add.u32 xa, sa, %181;\n"
        "add.u32 ma, sa, %182;\n"
        "ldmatrix.sync.aligned.m8n8.x4.shared.b16 {m0,m1,m2,m3}, [ma];\n"
        "ld.shared.u16 tag, [tp+48];\n"
        "add.u32 tp, tp, 52;\n"
        "add.u32 sn, sa, 8832;\n"
        "setp.eq.u32 q, sa, last;\n"
        "selp.u32 sn, ring, sn, q;\n"
        "selp.u32 tq, 1, 0, q;\n"
        "xor.b32 ph, ph, tq;\n"
        "mbarrier.test_wait.parity.shared.b64 w, [sn+8704], ph;\n"
        "mma.sync.aligned.m16n8k16.row.col.f32.bf16.bf16.f32 {%64,%65,%66,%67}, {a0,a1,a2,a3}, {x0,x1}, {%64,%65,%66,%67};\n"
        "mma.sync.aligned.m16n8k16.row.col.f32.bf16.bf16.f32 {%68,%69,%70,%71}, {a0,a1,a2,a3}, {x2,x3}, {%68,%69,%70,%71};\n"
        "ld.shared.v4.u32 {x0,x1,x2,x3}, [xa+1024];\n"
        "tanh.approx.f32 t0, p1;\n"
        "tanh.approx.f32 t1, p3;\n"
        "fma.rn.f32 t0, p1, t0, p1;\n"
        "fma.rn.f32 t1, p3, t1, p3;\n"
        "cvt.rn.bf16x2.f32 r0, t1, t0;\n"
        "mma.sync.aligned.m16n8k16.row.col.f32.bf16.bf16.f32 {p0,p1,p2,p3}, {%161,%162,%163,%164}, {m2,m3}, {fz,fz,fz,fz};\n"
        "mma.sync.aligned.m16n8k16.row.col.f32.bf16.bf16.f32 {%72,%73,%74,%75}, {a0,a1,a2,a3}, {x4,x5}, {%72,%73,%74,%75};\n"
        "mma.sync.aligned.m16n8k16.row.col.f32.bf16.bf16.f32 {%76,%77,%78,%79}, {a0,a1,a2,a3}, {x6,x7}, {%76,%77,%78,%79};\n"
        "ld.shared.v4.u32 {x4,x5,x6,x7}, [xa+1152];\n"
        "mma.sync.aligned.m16n8k8.row.col.f32.bf16.bf16.f32 {d0,d1,d2,d3}, {%177,%178}, {m1}, {fz,fz,fz,fz};\n"
        "cvt.rn.bf16x2.f32 b0, d2, d0;\n"
        "cvt.rn.bf16x2.f32 b1, d3, d1;\n"
        "tanh.approx.f32 t0, p5;\n"
        "tanh.approx.f32 t1, p7;\n"
        "fma.rn.f32 t0, p5, t0, p5;\n"
        "fma.rn.f32 t1, p7, t1, p7;\n"
        "cvt.rn.bf16x2.f32 r1, t1, t0;\n"
        "mma.sync.aligned.m16n8k16.row.col.f32.bf16.bf16.f32 {p4,p5,p6,p7}, {%165,%166,%167,%168}, {m2,m3}, {fz,fz,fz,fz};\n"
        "mov.b32 {lo,hi}, r2;\n"
        "mov.b32 rl, {lo,lo};\n"
        "mov.b32 rh, {hi,hi};\n"
        "mul.bf16x2 x8, x8, rl;\n"
        "mul.bf16x2 x9, x9, rl;\n"
        "mul.bf16x2 x10, x10, rh;\n"
        "mul.bf16x2 x11, x11, rh;\n"
        "mma.sync.aligned.m16n8k16.row.col.f32.bf16.bf16.f32 {%80,%81,%82,%83}, {a0,a1,a2,a3}, {x8,x9}, {%80,%81,%82,%83};\n"
        "mma.sync.aligned.m16n8k16.row.col.f32.bf16.bf16.f32 {%84,%85,%86,%87}, {a0,a1,a2,a3}, {x10,x11}, {%84,%85,%86,%87};\n"
        "ld.shared.v4.u32 {x8,x9,x10,x11}, [xa+1280];\n"
        "mma.sync.aligned.m16n8k8.row.col.f32.bf16.bf16.f32 {d0,d1,d2,d3}, {%179,%180}, {m1}, {fz,fz,fz,fz};\n"
        "cvt.rn.bf16x2.f32 b2, d2, d0;\n"
        "cvt.rn.bf16x2.f32 b3, d3, d1;\n"
        "tanh.approx.f32 t0, p9;\n"
        "tanh.approx.f32 t1, p11;\n"
        "fma.rn.f32 t0, p9, t0, p9;\n"
        "fma.rn.f32 t1, p11, t1, p11;\n"
        "cvt.rn.bf16x2.f32 r2, t1, t0;\n"
        "mma.sync.aligned.m16n8k16.row.col.f32.bf16.bf16.f32 {p8,p9,p10,p11}, {%169,%170,%171,%172}, {m2,m3}, {fz,fz,fz,fz};\n"
        "selp.u32 tq, lb, 5, w;\n"
        "mov.b32 {lo,hi}, r3;\n"
        "mov.b32 rl, {lo,lo};\n"
        "mov.b32 rh, {hi,hi};\n"
        "mul.bf16x2 x12, x12, rl;\n"
        "mul.bf16x2 x13, x13, rl;\n"
        "mul.bf16x2 x14, x14, rh;\n"
        "mul.bf16x2 x15, x15, rh;\n"
        "mma.sync.aligned.m16n8k16.row.col.f32.bf16.bf16.f32 {%88,%89,%90,%91}, {a0,a1,a2,a3}, {x12,x13}, {%88,%89,%90,%91};\n"
        "mma.sync.aligned.m16n8k16.row.col.f32.bf16.bf16.f32 {%92,%93,%94,%95}, {a0,a1,a2,a3}, {x14,x15}, {%92,%93,%94,%95};\n"
        "ld.shared.v4.u32 {x12,x13,x14,x15}, [xa+1408];\n"
        "@el mbarrier.arrive.shared.b64 _, [k0+8712];\n"
        "redux.sync.or.b32 ln, tag, 0xffffffff;\n"
        "mov.u32 sa, sn;\n"
        "add.u32 k0, sn, zz;\n"
        "tanh.approx.f32 t0, p13;\n"
        "tanh.approx.f32 t1, p15;\n"
        "fma.rn.f32 t0, p13, t0, p13;\n"
        "fma.rn.f32 t1, p15, t1, p15;\n"
        "cvt.rn.bf16x2.f32 r3, t1, t0;\n"
        "mma.sync.aligned.m16n8k16.row.col.f32.bf16.bf16.f32 {p12,p13,p14,p15}, {%173,%174,%175,%176}, {m2,m3}, {fz,fz,fz,fz};\n"
        "mov.b32 {lo,hi}, r0;\n"
        "mov.b32 rl, {lo,lo};\n"
        "mov.b32 rh, {hi,hi};\n"
        "mul.bf16x2 x0, x0, rl;\n"
        "mul.bf16x2 x1, x1, rl;\n"
        "mul.bf16x2 x2, x2, rh;\n"
        "mul.bf16x2 x3, x3, rh;\n"
        "mov.b32 {lo,hi}, r1;\n"
        "mov.b32 rl, {lo,lo};\n"
        "mov.b32 rh, {hi,hi};\n"
        "mul.bf16x2 x4, x4, rl;\n"
        "mul.bf16x2 x5, x5, rl;\n"
        "mul.bf16x2 x6, x6, rh;\n"
        "mul.bf16x2 x7, x7, rh;\n"
        "brx.idx.uni tq, TB_%=;\n"
        "A3_%=:\n"
        "add.u32 xa, sa, %181;\n"
        "add.u32 ma, sa, %182;\n"
        "ldmatrix.sync.aligned.m8n8.x4.shared.b16 {m0,m1,m2,m3}, [ma];\n"
        "ld.shared.u16 tag, [tp+48];\n"
        "add.u32 tp, tp, 52;\n"
        "add.u32 sn, sa, 8832;\n"
        "setp.eq.u32 q, sa, last;\n"
        "selp.u32 sn, ring, sn, q;\n"
        "selp.u32 tq, 1, 0, q;\n"
        "xor.b32 ph, ph, tq;\n"
        "mbarrier.test_wait.parity.shared.b64 w, [sn+8704], ph;\n"
        "mma.sync.aligned.m16n8k16.row.col.f32.bf16.bf16.f32 {%96,%97,%98,%99}, {a0,a1,a2,a3}, {x0,x1}, {%96,%97,%98,%99};\n"
        "mma.sync.aligned.m16n8k16.row.col.f32.bf16.bf16.f32 {%100,%101,%102,%103}, {a0,a1,a2,a3}, {x2,x3}, {%100,%101,%102,%103};\n"
        "ld.shared.v4.u32 {x0,x1,x2,x3}, [xa+1024];\n"
        "tanh.approx.f32 t0, p1;\n"
        "tanh.approx.f32 t1, p3;\n"
        "fma.rn.f32 t0, p1, t0, p1;\n"
        "fma.rn.f32 t1, p3, t1, p3;\n"
        "cvt.rn.bf16x2.f32 r0, t1, t0;\n"
        "mma.sync.aligned.m16n8k16.row.col.f32.bf16.bf16.f32 {p0,p1,p2,p3}, {%161,%162,%163,%164}, {m2,m3}, {fz,fz,fz,fz};\n"
        "mma.sync.aligned.m16n8k16.row.col.f32.bf16.bf16.f32 {%104,%105,%106,%107}, {a0,a1,a2,a3}, {x4,x5}, {%104,%105,%106,%107};\n"
        "mma.sync.aligned.m16n8k16.row.col.f32.bf16.bf16.f32 {%108,%109,%110,%111}, {a0,a1,a2,a3}, {x6,x7}, {%108,%109,%110,%111};\n"
        "ld.shared.v4.u32 {x4,x5,x6,x7}, [xa+1152];\n"
        "mma.sync.aligned.m16n8k8.row.col.f32.bf16.bf16.f32 {d0,d1,d2,d3}, {%177,%178}, {m1}, {fz,fz,fz,fz};\n"
        "cvt.rn.bf16x2.f32 b0, d2, d0;\n"
        "cvt.rn.bf16x2.f32 b1, d3, d1;\n"
        "tanh.approx.f32 t0, p5;\n"
        "tanh.approx.f32 t1, p7;\n"
        "fma.rn.f32 t0, p5, t0, p5;\n"
        "fma.rn.f32 t1, p7, t1, p7;\n"
        "cvt.rn.bf16x2.f32 r1, t1, t0;\n"
        "mma.sync.aligned.m16n8k16.row.col.f32.bf16.bf16.f32 {p4,p5,p6,p7}, {%165,%166,%167,%168}, {m2,m3}, {fz,fz,fz,fz};\n"
        "mov.b32 {lo,hi}, r2;\n"
        "mov.b32 rl, {lo,lo};\n"
        "mov.b32 rh, {hi,hi};\n"
        "mul.bf16x2 x8, x8, rl;\n"
        "mul.bf16x2 x9, x9, rl;\n"
        "mul.bf16x2 x10, x10, rh;\n"
        "mul.bf16x2 x11, x11, rh;\n"
        "mma.sync.aligned.m16n8k16.row.col.f32.bf16.bf16.f32 {%112,%113,%114,%115}, {a0,a1,a2,a3}, {x8,x9}, {%112,%113,%114,%115};\n"
        "mma.sync.aligned.m16n8k16.row.col.f32.bf16.bf16.f32 {%116,%117,%118,%119}, {a0,a1,a2,a3}, {x10,x11}, {%116,%117,%118,%119};\n"
        "ld.shared.v4.u32 {x8,x9,x10,x11}, [xa+1280];\n"
        "mma.sync.aligned.m16n8k8.row.col.f32.bf16.bf16.f32 {d0,d1,d2,d3}, {%179,%180}, {m1}, {fz,fz,fz,fz};\n"
        "cvt.rn.bf16x2.f32 b2, d2, d0;\n"
        "cvt.rn.bf16x2.f32 b3, d3, d1;\n"
        "tanh.approx.f32 t0, p9;\n"
        "tanh.approx.f32 t1, p11;\n"
        "fma.rn.f32 t0, p9, t0, p9;\n"
        "fma.rn.f32 t1, p11, t1, p11;\n"
        "cvt.rn.bf16x2.f32 r2, t1, t0;\n"
        "mma.sync.aligned.m16n8k16.row.col.f32.bf16.bf16.f32 {p8,p9,p10,p11}, {%169,%170,%171,%172}, {m2,m3}, {fz,fz,fz,fz};\n"
        "selp.u32 tq, lb, 5, w;\n"
        "mov.b32 {lo,hi}, r3;\n"
        "mov.b32 rl, {lo,lo};\n"
        "mov.b32 rh, {hi,hi};\n"
        "mul.bf16x2 x12, x12, rl;\n"
        "mul.bf16x2 x13, x13, rl;\n"
        "mul.bf16x2 x14, x14, rh;\n"
        "mul.bf16x2 x15, x15, rh;\n"
        "mma.sync.aligned.m16n8k16.row.col.f32.bf16.bf16.f32 {%120,%121,%122,%123}, {a0,a1,a2,a3}, {x12,x13}, {%120,%121,%122,%123};\n"
        "mma.sync.aligned.m16n8k16.row.col.f32.bf16.bf16.f32 {%124,%125,%126,%127}, {a0,a1,a2,a3}, {x14,x15}, {%124,%125,%126,%127};\n"
        "ld.shared.v4.u32 {x12,x13,x14,x15}, [xa+1408];\n"
        "@el mbarrier.arrive.shared.b64 _, [k0+8712];\n"
        "redux.sync.or.b32 ln, tag, 0xffffffff;\n"
        "mov.u32 sa, sn;\n"
        "add.u32 k0, sn, zz;\n"
        "tanh.approx.f32 t0, p13;\n"
        "tanh.approx.f32 t1, p15;\n"
        "fma.rn.f32 t0, p13, t0, p13;\n"
        "fma.rn.f32 t1, p15, t1, p15;\n"
        "cvt.rn.bf16x2.f32 r3, t1, t0;\n"
        "mma.sync.aligned.m16n8k16.row.col.f32.bf16.bf16.f32 {p12,p13,p14,p15}, {%173,%174,%175,%176}, {m2,m3}, {fz,fz,fz,fz};\n"
        "mov.b32 {lo,hi}, r0;\n"
        "mov.b32 rl, {lo,lo};\n"
        "mov.b32 rh, {hi,hi};\n"
        "mul.bf16x2 x0, x0, rl;\n"
        "mul.bf16x2 x1, x1, rl;\n"
        "mul.bf16x2 x2, x2, rh;\n"
        "mul.bf16x2 x3, x3, rh;\n"
        "mov.b32 {lo,hi}, r1;\n"
        "mov.b32 rl, {lo,lo};\n"
        "mov.b32 rh, {hi,hi};\n"
        "mul.bf16x2 x4, x4, rl;\n"
        "mul.bf16x2 x5, x5, rl;\n"
        "mul.bf16x2 x6, x6, rh;\n"
        "mul.bf16x2 x7, x7, rh;\n"
        "brx.idx.uni tq, TB_%=;\n"
        "A4_%=:\n"
        "add.u32 xa, sa, %181;\n"
        "add.u32 ma, sa, %182;\n"
        "ldmatrix.sync.aligned.m8n8.x4.shared.b16 {m0,m1,m2,m3}, [ma];\n"
        "ld.shared.u16 tag, [tp+48];\n"
        "add.u32 tp, tp, 52;\n"
        "add.u32 sn, sa, 8832;\n"
        "setp.eq.u32 q, sa, last;\n"
        "selp.u32 sn, ring, sn, q;\n"
        "selp.u32 tq, 1, 0, q;\n"
        "xor.b32 ph, ph, tq;\n"
        "mbarrier.test_wait.parity.shared.b64 w, [sn+8704], ph;\n"
        "mma.sync.aligned.m16n8k16.row.col.f32.bf16.bf16.f32 {%128,%129,%130,%131}, {a0,a1,a2,a3}, {x0,x1}, {%128,%129,%130,%131};\n"
        "mma.sync.aligned.m16n8k16.row.col.f32.bf16.bf16.f32 {%132,%133,%134,%135}, {a0,a1,a2,a3}, {x2,x3}, {%132,%133,%134,%135};\n"
        "ld.shared.v4.u32 {x0,x1,x2,x3}, [xa+1024];\n"
        "tanh.approx.f32 t0, p1;\n"
        "tanh.approx.f32 t1, p3;\n"
        "fma.rn.f32 t0, p1, t0, p1;\n"
        "fma.rn.f32 t1, p3, t1, p3;\n"
        "cvt.rn.bf16x2.f32 r0, t1, t0;\n"
        "mma.sync.aligned.m16n8k16.row.col.f32.bf16.bf16.f32 {p0,p1,p2,p3}, {%161,%162,%163,%164}, {m2,m3}, {fz,fz,fz,fz};\n"
        "mma.sync.aligned.m16n8k16.row.col.f32.bf16.bf16.f32 {%136,%137,%138,%139}, {a0,a1,a2,a3}, {x4,x5}, {%136,%137,%138,%139};\n"
        "mma.sync.aligned.m16n8k16.row.col.f32.bf16.bf16.f32 {%140,%141,%142,%143}, {a0,a1,a2,a3}, {x6,x7}, {%140,%141,%142,%143};\n"
        "ld.shared.v4.u32 {x4,x5,x6,x7}, [xa+1152];\n"
        "mma.sync.aligned.m16n8k8.row.col.f32.bf16.bf16.f32 {d0,d1,d2,d3}, {%177,%178}, {m1}, {fz,fz,fz,fz};\n"
        "cvt.rn.bf16x2.f32 b0, d2, d0;\n"
        "cvt.rn.bf16x2.f32 b1, d3, d1;\n"
        "tanh.approx.f32 t0, p5;\n"
        "tanh.approx.f32 t1, p7;\n"
        "fma.rn.f32 t0, p5, t0, p5;\n"
        "fma.rn.f32 t1, p7, t1, p7;\n"
        "cvt.rn.bf16x2.f32 r1, t1, t0;\n"
        "mma.sync.aligned.m16n8k16.row.col.f32.bf16.bf16.f32 {p4,p5,p6,p7}, {%165,%166,%167,%168}, {m2,m3}, {fz,fz,fz,fz};\n"
        "mov.b32 {lo,hi}, r2;\n"
        "mov.b32 rl, {lo,lo};\n"
        "mov.b32 rh, {hi,hi};\n"
        "mul.bf16x2 x8, x8, rl;\n"
        "mul.bf16x2 x9, x9, rl;\n"
        "mul.bf16x2 x10, x10, rh;\n"
        "mul.bf16x2 x11, x11, rh;\n"
        "mma.sync.aligned.m16n8k16.row.col.f32.bf16.bf16.f32 {%144,%145,%146,%147}, {a0,a1,a2,a3}, {x8,x9}, {%144,%145,%146,%147};\n"
        "mma.sync.aligned.m16n8k16.row.col.f32.bf16.bf16.f32 {%148,%149,%150,%151}, {a0,a1,a2,a3}, {x10,x11}, {%148,%149,%150,%151};\n"
        "ld.shared.v4.u32 {x8,x9,x10,x11}, [xa+1280];\n"
        "mma.sync.aligned.m16n8k8.row.col.f32.bf16.bf16.f32 {d0,d1,d2,d3}, {%179,%180}, {m1}, {fz,fz,fz,fz};\n"
        "cvt.rn.bf16x2.f32 b2, d2, d0;\n"
        "cvt.rn.bf16x2.f32 b3, d3, d1;\n"
        "tanh.approx.f32 t0, p9;\n"
        "tanh.approx.f32 t1, p11;\n"
        "fma.rn.f32 t0, p9, t0, p9;\n"
        "fma.rn.f32 t1, p11, t1, p11;\n"
        "cvt.rn.bf16x2.f32 r2, t1, t0;\n"
        "mma.sync.aligned.m16n8k16.row.col.f32.bf16.bf16.f32 {p8,p9,p10,p11}, {%169,%170,%171,%172}, {m2,m3}, {fz,fz,fz,fz};\n"
        "selp.u32 tq, lb, 5, w;\n"
        "mov.b32 {lo,hi}, r3;\n"
        "mov.b32 rl, {lo,lo};\n"
        "mov.b32 rh, {hi,hi};\n"
        "mul.bf16x2 x12, x12, rl;\n"
        "mul.bf16x2 x13, x13, rl;\n"
        "mul.bf16x2 x14, x14, rh;\n"
        "mul.bf16x2 x15, x15, rh;\n"
        "mma.sync.aligned.m16n8k16.row.col.f32.bf16.bf16.f32 {%152,%153,%154,%155}, {a0,a1,a2,a3}, {x12,x13}, {%152,%153,%154,%155};\n"
        "mma.sync.aligned.m16n8k16.row.col.f32.bf16.bf16.f32 {%156,%157,%158,%159}, {a0,a1,a2,a3}, {x14,x15}, {%156,%157,%158,%159};\n"
        "ld.shared.v4.u32 {x12,x13,x14,x15}, [xa+1408];\n"
        "@el mbarrier.arrive.shared.b64 _, [k0+8712];\n"
        "redux.sync.or.b32 ln, tag, 0xffffffff;\n"
        "mov.u32 sa, sn;\n"
        "add.u32 k0, sn, zz;\n"
        "tanh.approx.f32 t0, p13;\n"
        "tanh.approx.f32 t1, p15;\n"
        "fma.rn.f32 t0, p13, t0, p13;\n"
        "fma.rn.f32 t1, p15, t1, p15;\n"
        "cvt.rn.bf16x2.f32 r3, t1, t0;\n"
        "mma.sync.aligned.m16n8k16.row.col.f32.bf16.bf16.f32 {p12,p13,p14,p15}, {%173,%174,%175,%176}, {m2,m3}, {fz,fz,fz,fz};\n"
        "mov.b32 {lo,hi}, r0;\n"
        "mov.b32 rl, {lo,lo};\n"
        "mov.b32 rh, {hi,hi};\n"
        "mul.bf16x2 x0, x0, rl;\n"
        "mul.bf16x2 x1, x1, rl;\n"
        "mul.bf16x2 x2, x2, rh;\n"
        "mul.bf16x2 x3, x3, rh;\n"
        "mov.b32 {lo,hi}, r1;\n"
        "mov.b32 rl, {lo,lo};\n"
        "mov.b32 rh, {hi,hi};\n"
        "mul.bf16x2 x4, x4, rl;\n"
        "mul.bf16x2 x5, x5, rl;\n"
        "mul.bf16x2 x6, x6, rh;\n"
        "mul.bf16x2 x7, x7, rh;\n"
        "brx.idx.uni tq, TB_%=;\n"
        "B0_%=:\n"
        "and.b32 la, ln, 255;\n"
        "shr.u32 lb, ln, 8;\n"
        "add.u32 ma, sa, %182;\n"
        "ldmatrix.sync.aligned.m8n8.x1.shared.b16 {yb}, [ma];\n"
        "add.u32 xa, sa, %181;\n"
        "mma.sync.aligned.m16n8k16.row.col.f32.bf16.bf16.f32 {%0,%1,%2,%3}, {b0,b1,b2,b3}, {x0,x1}, {%0,%1,%2,%3};\n"
        "mma.sync.aligned.m16n8k16.row.col.f32.bf16.bf16.f32 {%4,%5,%6,%7}, {b0,b1,b2,b3}, {x2,x3}, {%4,%5,%6,%7};\n"
        "ld.shared.v4.u32 {x0,x1,x2,x3}, [xa+0];\n"
        "tanh.approx.f32 t0, p0;\n"
        "tanh.approx.f32 t1, p2;\n"
        "fma.rn.f32 t0, p0, t0, p0;\n"
        "fma.rn.f32 t1, p2, t1, p2;\n"
        "cvt.rn.bf16x2.f32 r0, t1, t0;\n"
        "mma.sync.aligned.m16n8k16.row.col.f32.bf16.bf16.f32 {%8,%9,%10,%11}, {b0,b1,b2,b3}, {x4,x5}, {%8,%9,%10,%11};\n"
        "mma.sync.aligned.m16n8k16.row.col.f32.bf16.bf16.f32 {%12,%13,%14,%15}, {b0,b1,b2,b3}, {x6,x7}, {%12,%13,%14,%15};\n"
        "ld.shared.v4.u32 {x4,x5,x6,x7}, [xa+128];\n"
        "tanh.approx.f32 t0, p4;\n"
        "tanh.approx.f32 t1, p6;\n"
        "fma.rn.f32 t0, p4, t0, p4;\n"
        "fma.rn.f32 t1, p6, t1, p6;\n"
        "cvt.rn.bf16x2.f32 r1, t1, t0;\n"
        "mma.sync.aligned.m16n8k8.row.col.f32.bf16.bf16.f32 {d0,d1,d2,d3}, {%177,%178}, {yb}, {fz,fz,fz,fz};\n"
        "cvt.rn.bf16x2.f32 a0, d2, d0;\n"
        "cvt.rn.bf16x2.f32 a1, d3, d1;\n"
        "mov.b32 {lo,hi}, r2;\n"
        "mov.b32 rl, {lo,lo};\n"
        "mov.b32 rh, {hi,hi};\n"
        "mul.bf16x2 x8, x8, rl;\n"
        "mul.bf16x2 x9, x9, rl;\n"
        "mul.bf16x2 x10, x10, rh;\n"
        "mul.bf16x2 x11, x11, rh;\n"
        "mma.sync.aligned.m16n8k16.row.col.f32.bf16.bf16.f32 {%16,%17,%18,%19}, {b0,b1,b2,b3}, {x8,x9}, {%16,%17,%18,%19};\n"
        "mma.sync.aligned.m16n8k16.row.col.f32.bf16.bf16.f32 {%20,%21,%22,%23}, {b0,b1,b2,b3}, {x10,x11}, {%20,%21,%22,%23};\n"
        "ld.shared.v4.u32 {x8,x9,x10,x11}, [xa+256];\n"
        "tanh.approx.f32 t0, p8;\n"
        "tanh.approx.f32 t1, p10;\n"
        "fma.rn.f32 t0, p8, t0, p8;\n"
        "fma.rn.f32 t1, p10, t1, p10;\n"
        "cvt.rn.bf16x2.f32 r2, t1, t0;\n"
        "mma.sync.aligned.m16n8k8.row.col.f32.bf16.bf16.f32 {d0,d1,d2,d3}, {%179,%180}, {yb}, {fz,fz,fz,fz};\n"
        "cvt.rn.bf16x2.f32 a2, d2, d0;\n"
        "cvt.rn.bf16x2.f32 a3, d3, d1;\n"
        "mov.b32 {lo,hi}, r3;\n"
        "mov.b32 rl, {lo,lo};\n"
        "mov.b32 rh, {hi,hi};\n"
        "mul.bf16x2 x12, x12, rl;\n"
        "mul.bf16x2 x13, x13, rl;\n"
        "mul.bf16x2 x14, x14, rh;\n"
        "mul.bf16x2 x15, x15, rh;\n"
        "mma.sync.aligned.m16n8k16.row.col.f32.bf16.bf16.f32 {%24,%25,%26,%27}, {b0,b1,b2,b3}, {x12,x13}, {%24,%25,%26,%27};\n"
        "mma.sync.aligned.m16n8k16.row.col.f32.bf16.bf16.f32 {%28,%29,%30,%31}, {b0,b1,b2,b3}, {x14,x15}, {%28,%29,%30,%31};\n"
        "ld.shared.v4.u32 {x12,x13,x14,x15}, [xa+384];\n"
        "tanh.approx.f32 t0, p12;\n"
        "tanh.approx.f32 t1, p14;\n"
        "fma.rn.f32 t0, p12, t0, p12;\n"
        "fma.rn.f32 t1, p14, t1, p14;\n"
        "cvt.rn.bf16x2.f32 r3, t1, t0;\n"
        "mov.b32 {lo,hi}, r0;\n"
        "mov.b32 rl, {lo,lo};\n"
        "mov.b32 rh, {hi,hi};\n"
        "mul.bf16x2 x0, x0, rl;\n"
        "mul.bf16x2 x1, x1, rl;\n"
        "mul.bf16x2 x2, x2, rh;\n"
        "mul.bf16x2 x3, x3, rh;\n"
        "mov.b32 {lo,hi}, r1;\n"
        "mov.b32 rl, {lo,lo};\n"
        "mov.b32 rh, {hi,hi};\n"
        "mul.bf16x2 x4, x4, rl;\n"
        "mul.bf16x2 x5, x5, rl;\n"
        "mul.bf16x2 x6, x6, rh;\n"
        "mul.bf16x2 x7, x7, rh;\n"
        "brx.idx.uni la, TA_%=;\n"
        "B1_%=:\n"
        "and.b32 la, ln, 255;\n"
        "shr.u32 lb, ln, 8;\n"
        "add.u32 ma, sa, %182;\n"
        "ldmatrix.sync.aligned.m8n8.x1.shared.b16 {yb}, [ma];\n"
        "add.u32 xa, sa, %181;\n"
        "mma.sync.aligned.m16n8k16.row.col.f32.bf16.bf16.f32 {%32,%33,%34,%35}, {b0,b1,b2,b3}, {x0,x1}, {%32,%33,%34,%35};\n"
        "mma.sync.aligned.m16n8k16.row.col.f32.bf16.bf16.f32 {%36,%37,%38,%39}, {b0,b1,b2,b3}, {x2,x3}, {%36,%37,%38,%39};\n"
        "ld.shared.v4.u32 {x0,x1,x2,x3}, [xa+0];\n"
        "tanh.approx.f32 t0, p0;\n"
        "tanh.approx.f32 t1, p2;\n"
        "fma.rn.f32 t0, p0, t0, p0;\n"
        "fma.rn.f32 t1, p2, t1, p2;\n"
        "cvt.rn.bf16x2.f32 r0, t1, t0;\n"
        "mma.sync.aligned.m16n8k16.row.col.f32.bf16.bf16.f32 {%40,%41,%42,%43}, {b0,b1,b2,b3}, {x4,x5}, {%40,%41,%42,%43};\n"
        "mma.sync.aligned.m16n8k16.row.col.f32.bf16.bf16.f32 {%44,%45,%46,%47}, {b0,b1,b2,b3}, {x6,x7}, {%44,%45,%46,%47};\n"
        "ld.shared.v4.u32 {x4,x5,x6,x7}, [xa+128];\n"
        "tanh.approx.f32 t0, p4;\n"
        "tanh.approx.f32 t1, p6;\n"
        "fma.rn.f32 t0, p4, t0, p4;\n"
        "fma.rn.f32 t1, p6, t1, p6;\n"
        "cvt.rn.bf16x2.f32 r1, t1, t0;\n"
        "mma.sync.aligned.m16n8k8.row.col.f32.bf16.bf16.f32 {d0,d1,d2,d3}, {%177,%178}, {yb}, {fz,fz,fz,fz};\n"
        "cvt.rn.bf16x2.f32 a0, d2, d0;\n"
        "cvt.rn.bf16x2.f32 a1, d3, d1;\n"
        "mov.b32 {lo,hi}, r2;\n"
        "mov.b32 rl, {lo,lo};\n"
        "mov.b32 rh, {hi,hi};\n"
        "mul.bf16x2 x8, x8, rl;\n"
        "mul.bf16x2 x9, x9, rl;\n"
        "mul.bf16x2 x10, x10, rh;\n"
        "mul.bf16x2 x11, x11, rh;\n"
        "mma.sync.aligned.m16n8k16.row.col.f32.bf16.bf16.f32 {%48,%49,%50,%51}, {b0,b1,b2,b3}, {x8,x9}, {%48,%49,%50,%51};\n"
        "mma.sync.aligned.m16n8k16.row.col.f32.bf16.bf16.f32 {%52,%53,%54,%55}, {b0,b1,b2,b3}, {x10,x11}, {%52,%53,%54,%55};\n"
        "ld.shared.v4.u32 {x8,x9,x10,x11}, [xa+256];\n"
        "tanh.approx.f32 t0, p8;\n"
        "tanh.approx.f32 t1, p10;\n"
        "fma.rn.f32 t0, p8, t0, p8;\n"
        "fma.rn.f32 t1, p10, t1, p10;\n"
        "cvt.rn.bf16x2.f32 r2, t1, t0;\n"
        "mma.sync.aligned.m16n8k8.row.col.f32.bf16.bf16.f32 {d0,d1,d2,d3}, {%179,%180}, {yb}, {fz,fz,fz,fz};\n"
        "cvt.rn.bf16x2.f32 a2, d2, d0;\n"
        "cvt.rn.bf16x2.f32 a3, d3, d1;\n"
        "mov.b32 {lo,hi}, r3;\n"
        "mov.b32 rl, {lo,lo};\n"
        "mov.b32 rh, {hi,hi};\n"
        "mul.bf16x2 x12, x12, rl;\n"
        "mul.bf16x2 x13, x13, rl;\n"
        "mul.bf16x2 x14, x14, rh;\n"
        "mul.bf16x2 x15, x15, rh;\n"
        "mma.sync.aligned.m16n8k16.row.col.f32.bf16.bf16.f32 {%56,%57,%58,%59}, {b0,b1,b2,b3}, {x12,x13}, {%56,%57,%58,%59};\n"
        "mma.sync.aligned.m16n8k16.row.col.f32.bf16.bf16.f32 {%60,%61,%62,%63}, {b0,b1,b2,b3}, {x14,x15}, {%60,%61,%62,%63};\n"
        "ld.shared.v4.u32 {x12,x13,x14,x15}, [xa+384];\n"
        "tanh.approx.f32 t0, p12;\n"
        "tanh.approx.f32 t1, p14;\n"
        "fma.rn.f32 t0, p12, t0, p12;\n"
        "fma.rn.f32 t1, p14, t1, p14;\n"
        "cvt.rn.bf16x2.f32 r3, t1, t0;\n"
        "mov.b32 {lo,hi}, r0;\n"
        "mov.b32 rl, {lo,lo};\n"
        "mov.b32 rh, {hi,hi};\n"
        "mul.bf16x2 x0, x0, rl;\n"
        "mul.bf16x2 x1, x1, rl;\n"
        "mul.bf16x2 x2, x2, rh;\n"
        "mul.bf16x2 x3, x3, rh;\n"
        "mov.b32 {lo,hi}, r1;\n"
        "mov.b32 rl, {lo,lo};\n"
        "mov.b32 rh, {hi,hi};\n"
        "mul.bf16x2 x4, x4, rl;\n"
        "mul.bf16x2 x5, x5, rl;\n"
        "mul.bf16x2 x6, x6, rh;\n"
        "mul.bf16x2 x7, x7, rh;\n"
        "brx.idx.uni la, TA_%=;\n"
        "B2_%=:\n"
        "and.b32 la, ln, 255;\n"
        "shr.u32 lb, ln, 8;\n"
        "add.u32 ma, sa, %182;\n"
        "ldmatrix.sync.aligned.m8n8.x1.shared.b16 {yb}, [ma];\n"
        "add.u32 xa, sa, %181;\n"
        "mma.sync.aligned.m16n8k16.row.col.f32.bf16.bf16.f32 {%64,%65,%66,%67}, {b0,b1,b2,b3}, {x0,x1}, {%64,%65,%66,%67};\n"
        "mma.sync.aligned.m16n8k16.row.col.f32.bf16.bf16.f32 {%68,%69,%70,%71}, {b0,b1,b2,b3}, {x2,x3}, {%68,%69,%70,%71};\n"
        "ld.shared.v4.u32 {x0,x1,x2,x3}, [xa+0];\n"
        "tanh.approx.f32 t0, p0;\n"
        "tanh.approx.f32 t1, p2;\n"
        "fma.rn.f32 t0, p0, t0, p0;\n"
        "fma.rn.f32 t1, p2, t1, p2;\n"
        "cvt.rn.bf16x2.f32 r0, t1, t0;\n"
        "mma.sync.aligned.m16n8k16.row.col.f32.bf16.bf16.f32 {%72,%73,%74,%75}, {b0,b1,b2,b3}, {x4,x5}, {%72,%73,%74,%75};\n"
        "mma.sync.aligned.m16n8k16.row.col.f32.bf16.bf16.f32 {%76,%77,%78,%79}, {b0,b1,b2,b3}, {x6,x7}, {%76,%77,%78,%79};\n"
        "ld.shared.v4.u32 {x4,x5,x6,x7}, [xa+128];\n"
        "tanh.approx.f32 t0, p4;\n"
        "tanh.approx.f32 t1, p6;\n"
        "fma.rn.f32 t0, p4, t0, p4;\n"
        "fma.rn.f32 t1, p6, t1, p6;\n"
        "cvt.rn.bf16x2.f32 r1, t1, t0;\n"
        "mma.sync.aligned.m16n8k8.row.col.f32.bf16.bf16.f32 {d0,d1,d2,d3}, {%177,%178}, {yb}, {fz,fz,fz,fz};\n"
        "cvt.rn.bf16x2.f32 a0, d2, d0;\n"
        "cvt.rn.bf16x2.f32 a1, d3, d1;\n"
        "mov.b32 {lo,hi}, r2;\n"
        "mov.b32 rl, {lo,lo};\n"
        "mov.b32 rh, {hi,hi};\n"
        "mul.bf16x2 x8, x8, rl;\n"
        "mul.bf16x2 x9, x9, rl;\n"
        "mul.bf16x2 x10, x10, rh;\n"
        "mul.bf16x2 x11, x11, rh;\n"
        "mma.sync.aligned.m16n8k16.row.col.f32.bf16.bf16.f32 {%80,%81,%82,%83}, {b0,b1,b2,b3}, {x8,x9}, {%80,%81,%82,%83};\n"
        "mma.sync.aligned.m16n8k16.row.col.f32.bf16.bf16.f32 {%84,%85,%86,%87}, {b0,b1,b2,b3}, {x10,x11}, {%84,%85,%86,%87};\n"
        "ld.shared.v4.u32 {x8,x9,x10,x11}, [xa+256];\n"
        "tanh.approx.f32 t0, p8;\n"
        "tanh.approx.f32 t1, p10;\n"
        "fma.rn.f32 t0, p8, t0, p8;\n"
        "fma.rn.f32 t1, p10, t1, p10;\n"
        "cvt.rn.bf16x2.f32 r2, t1, t0;\n"
        "mma.sync.aligned.m16n8k8.row.col.f32.bf16.bf16.f32 {d0,d1,d2,d3}, {%179,%180}, {yb}, {fz,fz,fz,fz};\n"
        "cvt.rn.bf16x2.f32 a2, d2, d0;\n"
        "cvt.rn.bf16x2.f32 a3, d3, d1;\n"
        "mov.b32 {lo,hi}, r3;\n"
        "mov.b32 rl, {lo,lo};\n"
        "mov.b32 rh, {hi,hi};\n"
        "mul.bf16x2 x12, x12, rl;\n"
        "mul.bf16x2 x13, x13, rl;\n"
        "mul.bf16x2 x14, x14, rh;\n"
        "mul.bf16x2 x15, x15, rh;\n"
        "mma.sync.aligned.m16n8k16.row.col.f32.bf16.bf16.f32 {%88,%89,%90,%91}, {b0,b1,b2,b3}, {x12,x13}, {%88,%89,%90,%91};\n"
        "mma.sync.aligned.m16n8k16.row.col.f32.bf16.bf16.f32 {%92,%93,%94,%95}, {b0,b1,b2,b3}, {x14,x15}, {%92,%93,%94,%95};\n"
        "ld.shared.v4.u32 {x12,x13,x14,x15}, [xa+384];\n"
        "tanh.approx.f32 t0, p12;\n"
        "tanh.approx.f32 t1, p14;\n"
        "fma.rn.f32 t0, p12, t0, p12;\n"
        "fma.rn.f32 t1, p14, t1, p14;\n"
        "cvt.rn.bf16x2.f32 r3, t1, t0;\n"
        "mov.b32 {lo,hi}, r0;\n"
        "mov.b32 rl, {lo,lo};\n"
        "mov.b32 rh, {hi,hi};\n"
        "mul.bf16x2 x0, x0, rl;\n"
        "mul.bf16x2 x1, x1, rl;\n"
        "mul.bf16x2 x2, x2, rh;\n"
        "mul.bf16x2 x3, x3, rh;\n"
        "mov.b32 {lo,hi}, r1;\n"
        "mov.b32 rl, {lo,lo};\n"
        "mov.b32 rh, {hi,hi};\n"
        "mul.bf16x2 x4, x4, rl;\n"
        "mul.bf16x2 x5, x5, rl;\n"
        "mul.bf16x2 x6, x6, rh;\n"
        "mul.bf16x2 x7, x7, rh;\n"
        "brx.idx.uni la, TA_%=;\n"
        "B3_%=:\n"
        "and.b32 la, ln, 255;\n"
        "shr.u32 lb, ln, 8;\n"
        "add.u32 ma, sa, %182;\n"
        "ldmatrix.sync.aligned.m8n8.x1.shared.b16 {yb}, [ma];\n"
        "add.u32 xa, sa, %181;\n"
        "mma.sync.aligned.m16n8k16.row.col.f32.bf16.bf16.f32 {%96,%97,%98,%99}, {b0,b1,b2,b3}, {x0,x1}, {%96,%97,%98,%99};\n"
        "mma.sync.aligned.m16n8k16.row.col.f32.bf16.bf16.f32 {%100,%101,%102,%103}, {b0,b1,b2,b3}, {x2,x3}, {%100,%101,%102,%103};\n"
        "ld.shared.v4.u32 {x0,x1,x2,x3}, [xa+0];\n"
        "tanh.approx.f32 t0, p0;\n"
        "tanh.approx.f32 t1, p2;\n"
        "fma.rn.f32 t0, p0, t0, p0;\n"
        "fma.rn.f32 t1, p2, t1, p2;\n"
        "cvt.rn.bf16x2.f32 r0, t1, t0;\n"
        "mma.sync.aligned.m16n8k16.row.col.f32.bf16.bf16.f32 {%104,%105,%106,%107}, {b0,b1,b2,b3}, {x4,x5}, {%104,%105,%106,%107};\n"
        "mma.sync.aligned.m16n8k16.row.col.f32.bf16.bf16.f32 {%108,%109,%110,%111}, {b0,b1,b2,b3}, {x6,x7}, {%108,%109,%110,%111};\n"
        "ld.shared.v4.u32 {x4,x5,x6,x7}, [xa+128];\n"
        "tanh.approx.f32 t0, p4;\n"
        "tanh.approx.f32 t1, p6;\n"
        "fma.rn.f32 t0, p4, t0, p4;\n"
        "fma.rn.f32 t1, p6, t1, p6;\n"
        "cvt.rn.bf16x2.f32 r1, t1, t0;\n"
        "mma.sync.aligned.m16n8k8.row.col.f32.bf16.bf16.f32 {d0,d1,d2,d3}, {%177,%178}, {yb}, {fz,fz,fz,fz};\n"
        "cvt.rn.bf16x2.f32 a0, d2, d0;\n"
        "cvt.rn.bf16x2.f32 a1, d3, d1;\n"
        "mov.b32 {lo,hi}, r2;\n"
        "mov.b32 rl, {lo,lo};\n"
        "mov.b32 rh, {hi,hi};\n"
        "mul.bf16x2 x8, x8, rl;\n"
        "mul.bf16x2 x9, x9, rl;\n"
        "mul.bf16x2 x10, x10, rh;\n"
        "mul.bf16x2 x11, x11, rh;\n"
        "mma.sync.aligned.m16n8k16.row.col.f32.bf16.bf16.f32 {%112,%113,%114,%115}, {b0,b1,b2,b3}, {x8,x9}, {%112,%113,%114,%115};\n"
        "mma.sync.aligned.m16n8k16.row.col.f32.bf16.bf16.f32 {%116,%117,%118,%119}, {b0,b1,b2,b3}, {x10,x11}, {%116,%117,%118,%119};\n"
        "ld.shared.v4.u32 {x8,x9,x10,x11}, [xa+256];\n"
        "tanh.approx.f32 t0, p8;\n"
        "tanh.approx.f32 t1, p10;\n"
        "fma.rn.f32 t0, p8, t0, p8;\n"
        "fma.rn.f32 t1, p10, t1, p10;\n"
        "cvt.rn.bf16x2.f32 r2, t1, t0;\n"
        "mma.sync.aligned.m16n8k8.row.col.f32.bf16.bf16.f32 {d0,d1,d2,d3}, {%179,%180}, {yb}, {fz,fz,fz,fz};\n"
        "cvt.rn.bf16x2.f32 a2, d2, d0;\n"
        "cvt.rn.bf16x2.f32 a3, d3, d1;\n"
        "mov.b32 {lo,hi}, r3;\n"
        "mov.b32 rl, {lo,lo};\n"
        "mov.b32 rh, {hi,hi};\n"
        "mul.bf16x2 x12, x12, rl;\n"
        "mul.bf16x2 x13, x13, rl;\n"
        "mul.bf16x2 x14, x14, rh;\n"
        "mul.bf16x2 x15, x15, rh;\n"
        "mma.sync.aligned.m16n8k16.row.col.f32.bf16.bf16.f32 {%120,%121,%122,%123}, {b0,b1,b2,b3}, {x12,x13}, {%120,%121,%122,%123};\n"
        "mma.sync.aligned.m16n8k16.row.col.f32.bf16.bf16.f32 {%124,%125,%126,%127}, {b0,b1,b2,b3}, {x14,x15}, {%124,%125,%126,%127};\n"
        "ld.shared.v4.u32 {x12,x13,x14,x15}, [xa+384];\n"
        "tanh.approx.f32 t0, p12;\n"
        "tanh.approx.f32 t1, p14;\n"
        "fma.rn.f32 t0, p12, t0, p12;\n"
        "fma.rn.f32 t1, p14, t1, p14;\n"
        "cvt.rn.bf16x2.f32 r3, t1, t0;\n"
        "mov.b32 {lo,hi}, r0;\n"
        "mov.b32 rl, {lo,lo};\n"
        "mov.b32 rh, {hi,hi};\n"
        "mul.bf16x2 x0, x0, rl;\n"
        "mul.bf16x2 x1, x1, rl;\n"
        "mul.bf16x2 x2, x2, rh;\n"
        "mul.bf16x2 x3, x3, rh;\n"
        "mov.b32 {lo,hi}, r1;\n"
        "mov.b32 rl, {lo,lo};\n"
        "mov.b32 rh, {hi,hi};\n"
        "mul.bf16x2 x4, x4, rl;\n"
        "mul.bf16x2 x5, x5, rl;\n"
        "mul.bf16x2 x6, x6, rh;\n"
        "mul.bf16x2 x7, x7, rh;\n"
        "brx.idx.uni la, TA_%=;\n"
        "B4_%=:\n"
        "and.b32 la, ln, 255;\n"
        "shr.u32 lb, ln, 8;\n"
        "add.u32 ma, sa, %182;\n"
        "ldmatrix.sync.aligned.m8n8.x1.shared.b16 {yb}, [ma];\n"
        "add.u32 xa, sa, %181;\n"
        "mma.sync.aligned.m16n8k16.row.col.f32.bf16.bf16.f32 {%128,%129,%130,%131}, {b0,b1,b2,b3}, {x0,x1}, {%128,%129,%130,%131};\n"
        "mma.sync.aligned.m16n8k16.row.col.f32.bf16.bf16.f32 {%132,%133,%134,%135}, {b0,b1,b2,b3}, {x2,x3}, {%132,%133,%134,%135};\n"
        "ld.shared.v4.u32 {x0,x1,x2,x3}, [xa+0];\n"
        "tanh.approx.f32 t0, p0;\n"
        "tanh.approx.f32 t1, p2;\n"
        "fma.rn.f32 t0, p0, t0, p0;\n"
        "fma.rn.f32 t1, p2, t1, p2;\n"
        "cvt.rn.bf16x2.f32 r0, t1, t0;\n"
        "mma.sync.aligned.m16n8k16.row.col.f32.bf16.bf16.f32 {%136,%137,%138,%139}, {b0,b1,b2,b3}, {x4,x5}, {%136,%137,%138,%139};\n"
        "mma.sync.aligned.m16n8k16.row.col.f32.bf16.bf16.f32 {%140,%141,%142,%143}, {b0,b1,b2,b3}, {x6,x7}, {%140,%141,%142,%143};\n"
        "ld.shared.v4.u32 {x4,x5,x6,x7}, [xa+128];\n"
        "tanh.approx.f32 t0, p4;\n"
        "tanh.approx.f32 t1, p6;\n"
        "fma.rn.f32 t0, p4, t0, p4;\n"
        "fma.rn.f32 t1, p6, t1, p6;\n"
        "cvt.rn.bf16x2.f32 r1, t1, t0;\n"
        "mma.sync.aligned.m16n8k8.row.col.f32.bf16.bf16.f32 {d0,d1,d2,d3}, {%177,%178}, {yb}, {fz,fz,fz,fz};\n"
        "cvt.rn.bf16x2.f32 a0, d2, d0;\n"
        "cvt.rn.bf16x2.f32 a1, d3, d1;\n"
        "mov.b32 {lo,hi}, r2;\n"
        "mov.b32 rl, {lo,lo};\n"
        "mov.b32 rh, {hi,hi};\n"
        "mul.bf16x2 x8, x8, rl;\n"
        "mul.bf16x2 x9, x9, rl;\n"
        "mul.bf16x2 x10, x10, rh;\n"
        "mul.bf16x2 x11, x11, rh;\n"
        "mma.sync.aligned.m16n8k16.row.col.f32.bf16.bf16.f32 {%144,%145,%146,%147}, {b0,b1,b2,b3}, {x8,x9}, {%144,%145,%146,%147};\n"
        "mma.sync.aligned.m16n8k16.row.col.f32.bf16.bf16.f32 {%148,%149,%150,%151}, {b0,b1,b2,b3}, {x10,x11}, {%148,%149,%150,%151};\n"
        "ld.shared.v4.u32 {x8,x9,x10,x11}, [xa+256];\n"
        "tanh.approx.f32 t0, p8;\n"
        "tanh.approx.f32 t1, p10;\n"
        "fma.rn.f32 t0, p8, t0, p8;\n"
        "fma.rn.f32 t1, p10, t1, p10;\n"
        "cvt.rn.bf16x2.f32 r2, t1, t0;\n"
        "mma.sync.aligned.m16n8k8.row.col.f32.bf16.bf16.f32 {d0,d1,d2,d3}, {%179,%180}, {yb}, {fz,fz,fz,fz};\n"
        "cvt.rn.bf16x2.f32 a2, d2, d0;\n"
        "cvt.rn.bf16x2.f32 a3, d3, d1;\n"
        "mov.b32 {lo,hi}, r3;\n"
        "mov.b32 rl, {lo,lo};\n"
        "mov.b32 rh, {hi,hi};\n"
        "mul.bf16x2 x12, x12, rl;\n"
        "mul.bf16x2 x13, x13, rl;\n"
        "mul.bf16x2 x14, x14, rh;\n"
        "mul.bf16x2 x15, x15, rh;\n"
        "mma.sync.aligned.m16n8k16.row.col.f32.bf16.bf16.f32 {%152,%153,%154,%155}, {b0,b1,b2,b3}, {x12,x13}, {%152,%153,%154,%155};\n"
        "mma.sync.aligned.m16n8k16.row.col.f32.bf16.bf16.f32 {%156,%157,%158,%159}, {b0,b1,b2,b3}, {x14,x15}, {%156,%157,%158,%159};\n"
        "ld.shared.v4.u32 {x12,x13,x14,x15}, [xa+384];\n"
        "tanh.approx.f32 t0, p12;\n"
        "tanh.approx.f32 t1, p14;\n"
        "fma.rn.f32 t0, p12, t0, p12;\n"
        "fma.rn.f32 t1, p14, t1, p14;\n"
        "cvt.rn.bf16x2.f32 r3, t1, t0;\n"
        "mov.b32 {lo,hi}, r0;\n"
        "mov.b32 rl, {lo,lo};\n"
        "mov.b32 rh, {hi,hi};\n"
        "mul.bf16x2 x0, x0, rl;\n"
        "mul.bf16x2 x1, x1, rl;\n"
        "mul.bf16x2 x2, x2, rh;\n"
        "mul.bf16x2 x3, x3, rh;\n"
        "mov.b32 {lo,hi}, r1;\n"
        "mov.b32 rl, {lo,lo};\n"
        "mov.b32 rh, {hi,hi};\n"
        "mul.bf16x2 x4, x4, rl;\n"
        "mul.bf16x2 x5, x5, rl;\n"
        "mul.bf16x2 x6, x6, rh;\n"
        "mul.bf16x2 x7, x7, rh;\n"
        "brx.idx.uni la, TA_%=;\n"
        "EXIT_%=:\n"
        "mov.u32 %160, ring;\n"
        "}\n"
        : "+f"(acc[0][0][0][0]), "+f"(acc[0][0][0][1]), "+f"(acc[0][0][0][2]), "+f"(acc[0][0][0][3]), "+f"(acc[0][0][1][0]),
          "+f"(acc[0][0][1][1]), "+f"(acc[0][0][1][2]), "+f"(acc[0][0][1][3]), "+f"(acc[0][1][0][0]), "+f"(acc[0][1][0][1]),
          "+f"(acc[0][1][0][2]), "+f"(acc[0][1][0][3]), "+f"(acc[0][1][1][0]), "+f"(acc[0][1][1][1]), "+f"(acc[0][1][1][2]),
          "+f"(acc[0][1][1][3]), "+f"(acc[0][2][0][0]), "+f"(acc[0][2][0][1]), "+f"(acc[0][2][0][2]), "+f"(acc[0][2][0][3]),
          "+f"(acc[0][2][1][0]), "+f"(acc[0][2][1][1]), "+f"(acc[0][2][1][2]), "+f"(acc[0][2][1][3]), "+f"(acc[0][3][0][0]),
          "+f"(acc[0][3][0][1]), "+f"(acc[0][3][0][2]), "+f"(acc[0][3][0][3]), "+f"(acc[0][3][1][0]), "+f"(acc[0][3][1][1]),
          "+f"(acc[0][3][1][2]), "+f"(acc[0][3][1][3]), "+f"(acc[1][0][0][0]), "+f"(acc[1][0][0][1]), "+f"(acc[1][0][0][2]),
          "+f"(acc[1][0][0][3]), "+f"(acc[1][0][1][0]), "+f"(acc[1][0][1][1]), "+f"(acc[1][0][1][2]), "+f"(acc[1][0][1][3]),
          "+f"(acc[1][1][0][0]), "+f"(acc[1][1][0][1]), "+f"(acc[1][1][0][2]), "+f"(acc[1][1][0][3]), "+f"(acc[1][1][1][0]),
          "+f"(acc[1][1][1][1]), "+f"(acc[1][1][1][2]), "+f"(acc[1][1][1][3]), "+f"(acc[1][2][0][0]), "+f"(acc[1][2][0][1]),
          "+f"(acc[1][2][0][2]), "+f"(acc[1][2][0][3]), "+f"(acc[1][2][1][0]), "+f"(acc[1][2][1][1]), "+f"(acc[1][2][1][2]),
          "+f"(acc[1][2][1][3]), "+f"(acc[1][3][0][0]), "+f"(acc[1][3][0][1]), "+f"(acc[1][3][0][2]), "+f"(acc[1][3][0][3]),
          "+f"(acc[1][3][1][0]), "+f"(acc[1][3][1][1]), "+f"(acc[1][3][1][2]), "+f"(acc[1][3][1][3]), "+f"(acc[2][0][0][0]),
          "+f"(acc[2][0][0][1]), "+f"(acc[2][0][0][2]), "+f"(acc[2][0][0][3]), "+f"(acc[2][0][1][0]), "+f"(acc[2][0][1][1]),
          "+f"(acc[2][0][1][2]), "+f"(acc[2][0][1][3]), "+f"(acc[2][1][0][0]), "+f"(acc[2][1][0][1]), "+f"(acc[2][1][0][2]),
          "+f"(acc[2][1][0][3]), "+f"(acc[2][1][1][0]), "+f"(acc[2][1][1][1]), "+f"(acc[2][1][1][2]), "+f"(acc[2][1][1][3]),
          "+f"(acc[2][2][0][0]), "+f"(acc[2][2][0][1]), "+f"(acc[2][2][0][2]), "+f"(acc[2][2][0][3]), "+f"(acc[2][2][1][0]),
          "+f"(acc[2][2][1][1]), "+f"(acc[2][2][1][2]), "+f"(acc[2][2][1][3]), "+f"(acc[2][3][0][0]), "+f"(acc[2][3][0][1]),
          "+f"(acc[2][3][0][2]), "+f"(acc[2][3][0][3]), "+f"(acc[2][3][1][0]), "+f"(acc[2][3][1][1]), "+f"(acc[2][3][1][2]),
          "+f"(acc[2][3][1][3]), "+f"(acc[3][0][0][0]), "+f"(acc[3][0][0][1]), "+f"(acc[3][0][0][2]), "+f"(acc[3][0][0][3]),
          "+f"(acc[3][0][1][0]), "+f"(acc[3][0][1][1]), "+f"(acc[3][0][1][2]), "+f"(acc[3][0][1][3]), "+f"(acc[3][1][0][0]),
          "+f"(acc[3][1][0][1]), "+f"(acc[3][1][0][2]), "+f"(acc[3][1][0][3]), "+f"(acc[3][1][1][0]), "+f"(acc[3][1][1][1]),
          "+f"(acc[3][1][1][2]), "+f"(acc[3][1][1][3]), "+f"(acc[3][2][0][0]), "+f"(acc[3][2][0][1]), "+f"(acc[3][2][0][2]),
          "+f"(acc[3][2][0][3]), "+f"(acc[3][2][1][0]), "+f"(acc[3][2][1][1]), "+f"(acc[3][2][1][2]), "+f"(acc[3][2][1][3]),
          "+f"(acc[3][3][0][0]), "+f"(acc[3][3][0][1]), "+f"(acc[3][3][0][2]), "+f"(acc[3][3][0][3]), "+f"(acc[3][3][1][0]),
          "+f"(acc[3][3][1][1]), "+f"(acc[3][3][1][2]), "+f"(acc[3][3][1][3]), "+f"(acc[4][0][0][0]), "+f"(acc[4][0][0][1]),
          "+f"(acc[4][0][0][2]), "+f"(acc[4][0][0][3]), "+f"(acc[4][0][1][0]), "+f"(acc[4][0][1][1]), "+f"(acc[4][0][1][2]),
          "+f"(acc[4][0][1][3]), "+f"(acc[4][1][0][0]), "+f"(acc[4][1][0][1]), "+f"(acc[4][1][0][2]), "+f"(acc[4][1][0][3]),
          "+f"(acc[4][1][1][0]), "+f"(acc[4][1][1][1]), "+f"(acc[4][1][1][2]), "+f"(acc[4][1][1][3]), "+f"(acc[4][2][0][0]),
          "+f"(acc[4][2][0][1]), "+f"(acc[4][2][0][2]), "+f"(acc[4][2][0][3]), "+f"(acc[4][2][1][0]), "+f"(acc[4][2][1][1]),
          "+f"(acc[4][2][1][2]), "+f"(acc[4][2][1][3]), "+f"(acc[4][3][0][0]), "+f"(acc[4][3][0][1]), "+f"(acc[4][3][0][2]),
          "+f"(acc[4][3][0][3]), "+f"(acc[4][3][1][0]), "+f"(acc[4][3][1][1]), "+f"(acc[4][3][1][2]), "+f"(acc[4][3][1][3]),
          "+r"(ring)
        : "r"(wf[0][0]), "r"(wf[0][1]), "r"(wf[0][2]), "r"(wf[0][3]), "r"(wf[1][0]), "r"(wf[1][1]), "r"(wf[1][2]), "r"(wf[1][3]),
          "r"(wf[2][0]), "r"(wf[2][1]), "r"(wf[2][2]), "r"(wf[2][3]), "r"(wf[3][0]), "r"(wf[3][1]), "r"(wf[3][2]), "r"(wf[3][3]),
          "r"(cgf[0]), "r"(cgf[1]), "r"(cgf[2]), "r"(cgf[3]), "r"(xoff), "r"(moff), "r"(rec)
        : "memory");
}

__device__ __noinline__ void generic_path(float* sagg, const __nv_bfloat16* x, const int* src, const int* dst,
                                          const __nv_bfloat16* Y, const __nv_bfloat16* ef, const __nv_bfloat16* w_rad,
                                          const __nv_bfloat16* cg, int x0, int x1) {
    const int tid = threadIdx.x, lane = tid & 31, blk = blockIdx.x;
    for (int k = 0; k < 2; k++)
        for (int r = 0; r < min(k == 0 ? x0 : x1, 32); r++) {
            uint32_t* p2 = g_mail2 + (blk * NSRC + ((tid + k * NTHR) >> 3)) * 32 + r;
            uint32_t v;
            int it = 0;
            do {
                asm volatile("ld.relaxed.gpu.global.u32 %0, [%1];" : "=r"(v) : "l"(p2) : "memory");
                if (++it > (1 << 20)) __trap();
            } while (v == 0);
            *p2 = 0;
        }
    __syncthreads();
    for (int i = tid; i < NPB * 512; i += NTHR) sagg[i] = 0.f;
    __syncthreads();
    for (int e0 = tid & ~31; e0 < N_EDGES; e0 += NTHR) {
        uint32_t bm = __ballot_sync(~0u, dst[e0 + lane] / NPB == blk);
        while (bm) {
            const int e = e0 + __ffs(bm) - 1, s = src[e], loc = dst[e] - blk * NPB;
            bm &= bm - 1;
            float a[4][4];
            for (int i = 0; i < 4; i++)
                for (int o = 0; o < 4; o++) {
                    a[i][o] = 0.f;
                    for (int f = 0; f < 4; f++)
                        a[i][o] += __bfloat162float(Y[e * 4 + f]) * __bfloat162float(cg[i * 16 + f * 4 + o]);
                }
#pragma unroll 1
            for (int c = lane; c < 128; c += 32) {
                float pre = 0.f;
                for (int k = 0; k < 16; k++)
                    pre += __bfloat162float(ef[e * 16 + k]) * __bfloat162float(w_rad[k * 128 + c]);
                const float R = pre / (1.f + __expf(-pre));
                for (int o = 0; o < 4; o++) {
                    float acc = 0.f;
                    for (int i = 0; i < 4; i++) acc += __bfloat162float(x[(size_t)s * 512 + c * 4 + i]) * a[i][o];
                    atomicAdd(&sagg[loc * 512 + c * 4 + o], R * acc);
                }
            }
        }
    }
    __syncthreads();
}

__device__ __forceinline__ void init_barriers() {
    extern __shared__ __align__(1024) uint8_t smem[];
    const uint32_t sb = smem_u32(smem);
#pragma unroll
    for (int i = 0; i < 4 * NG; i++) {
        mbar_init(sb + i * STAGE + 4 * ROWP, 32);
        mbar_init(sb + i * STAGE + 4 * ROWP + 8, 2);
    }
}

template <int PHASES>
__global__ void __launch_bounds__(NTHR, 1)
tfn_kernel(const __nv_bfloat16* __restrict__ x, const int* __restrict__ src, const int* __restrict__ dst,
           const __nv_bfloat16* __restrict__ Y, const __nv_bfloat16* __restrict__ ef,
           const __nv_bfloat16* __restrict__ w_rad, const __nv_bfloat16* __restrict__ cg,
           const __nv_bfloat16* __restrict__ w_mix, __nv_bfloat16* __restrict__ out) {
    extern __shared__ __align__(1024) uint8_t smem[];
    const int tid = threadIdx.x, lane = tid & 31;
    const int warp = __shfl_sync(~0u, tid >> 5, 0);
    const int blk = blockIdx.x;
    uint32_t sb = smem_u32(smem);
    asm volatile("" : "+r"(sb));
    int* mi = reinterpret_cast<int*>(smem + SM_MISC);

    const int g = lane >> 2, t = lane & 3;
    const uint32_t dump = sb + SC_DUMP + lane * 4;
    int4 d1[2], s1[2];
    constexpr int nq = EPC / 4;
    const bool binner = (PHASES & 1) && blk < NSRC;
    if (binner) {
#pragma unroll
        for (int k = 0; k < 2; k++) {
            const int q = tid + k * NTHR;
            if (q < nq) {
                d1[k] = __ldg(reinterpret_cast<const int4*>(dst + blk * EPC) + q);
                s1[k] = __ldg(reinterpret_cast<const int4*>(src + blk * EPC) + q);
            }
        }
    }
    if (binner) {
#pragma unroll
        for (int k = 0; k < 3; k++)
            if (k < 2 || warp < 1) sts128(sb + SC_MAIL + (tid + k * NTHR) * 16, ~0u, ~0u, ~0u, ~0u);
        if (tid <= NB / 4) sts128(sb + SC_CNT + tid * 16, 0, 0, 0, 0);
    }
    if (PHASES & 2) {
        if (tid == 160) { sts128(sb + SM_MISC, 0, 0, 0, 0); sts128(sb + SM_MISC + MI_NU * 4, 0, 0, 0, 0); }
        if (tid == 161) {
            mi[MI_SHIFT] = 0;
            *reinterpret_cast<int**>(mi + MI_SHIFT + 4) = g_lag[blk];
        }
        if (tid == 162) g_lag[blk][0] = g_lag[NB + blk][0] = 0;
        if (tid < 20 * HS / 4) sts128(sb + SC_HIST + tid * 16, 0, 0, 0, 0);
        const uint32_t pad = (uint32_t)(lane * 0x10008 + 7);
#pragma unroll
        for (int k = 0; k < 3; k++)
            if (tid + k * NTHR < 4 * UCAP * REC / 16) sts128(sb + SM_REC + (tid + k * NTHR) * 16, pad, pad, pad, pad);
    }
    __syncthreads();
    if (PHASES & 2) {
#pragma unroll
        for (int k = 0; k < 4; k++) {
            const int i = tid + k * NTHR, c = i >> 4;
            cp16(sb + SM_W + c * 256 + (((i & 15) ^ ((c & 2) | (((c >> 4) & 1) << 2))) << 4), w_mix + i * 8);
        }
        if (warp >= 8) cp16(sb + SC_WR + ((tid - 256) ^ ((tid >> 4) & 6)) * 16, w_rad + (tid - 256) * 8);
        if (tid < 8) cp16(sb + SC_WR + 4096 + tid * 16, cg + tid * 8);
    }
    if (binner) {
#pragma unroll
        for (int k = 0; k < 2; k++) {
            if (tid + k * NTHR < nq) {
                const uint32_t dd[4] = {(uint32_t)d1[k].x, (uint32_t)d1[k].y, (uint32_t)d1[k].z, (uint32_t)d1[k].w};
                const uint32_t ss[4] = {(uint32_t)s1[k].x, (uint32_t)s1[k].y, (uint32_t)s1[k].z, (uint32_t)s1[k].w};
                uint32_t own[4], rk[4], v[4];
#pragma unroll
                for (int j = 0; j < 4; j++) { own[j] = dd[j] / NPB; rk[j] = atoms_inc(sb + SC_CNT + own[j] * 4); }
#pragma unroll
                for (int j = 0; j < 4; j++) {
                    const uint32_t loc = dd[j] - own[j] * NPB, code = loc + ((loc * 216) >> 12);
                    v[j] = (ss[j] << 18) + code * 2560 + (tid + k * NTHR) * 4 + j + 1;
                    sts32(sb + SC_MAIL + own[j] * 128 + ((min(rk[j], 31u) * 4) ^ ((own[j] & 7) << 4)), v[j]);
                }
                if (max(max(rk[0], rk[1]), max(rk[2], rk[3])) >= 31) {
#pragma unroll
                    for (int j = 0; j < 4; j++)
                        if (rk[j] - 31 < 32)
                            asm volatile("st.relaxed.gpu.global.u32 [%0], %1;" ::"l"(g_mail2 + (own[j] * NSRC + blk) * 32 + rk[j] - 31), "r"(v[j]) : "memory");
                }
            }
        }
        __syncwarp();
        asm volatile("red.shared.max.u32 [%0], %1;" ::"r"(lane == 0 ? sb + SC_CNT + NB * 4 : dump), "r"(gtime()) : "memory");
        STAMP(1);
        __syncthreads();
        const uint32_t hdr = 0xc0000000u | ((lds32(sb + SC_CNT + NB * 4) << 7) & 0x3ffff000u);
        uint4 mv[3];
        uint32_t mc[3];
#pragma unroll
        for (int k = 0; k < 3; k++)
            if (k < 2 || warp < 1) {
                const int j = tid + k * NTHR, own = j >> 3;
                mv[k] = lds128(sb + SC_MAIL + own * 128 + (((j ^ own) & 7) << 4));
                mc[k] = lds32(sb + SC_CNT + own * 4);
            }
#pragma unroll
        for (int k = 0; k < 3; k++)
            if (k < 2 || warp < 1) {
                const int j = tid + k * NTHR;
                asm volatile("st.relaxed.gpu.global.v4.u32 [%0], {%1,%2,%3,%4};" ::"l"(g_mail + ((j >> 3) * NSRC + blk) * 8 + (j & 7)),
                             "r"(mv[k].x), "r"(mv[k].y), "r"(mv[k].z), "r"((j & 7) == 7 ? hdr | mc[k] : mv[k].w) : "memory");
            }
        STAMP(2);
    }
    if (!(PHASES & 2)) return;
    const uint32_t tpub = (uint32_t)clock() + (blk < NSRC ? 0 : 3000);
    asm volatile("cp.async.wait_all;" ::: "memory");
    __syncwarp();
#pragma unroll
    for (int k = 0; k < 2; k++) {
        const int i = (tid & ~1) + ((tid & 1) * 2 + k) * NTHR, c = i >> 4;
        const uint32_t a0 = sb + SM_W + c * 256 + (((i & 15) ^ ((c & 3) | (((c >> 4) & 1) << 2))) << 4);
        const uint32_t o = (tid & 1) << 4;
        uint4 u = lds128((a0 & ~16u) ^ o), v = lds128((a0 | 16u) ^ o);
        if (tid & 1) { const uint4 w = u; u = v; v = w; }
        const uint32_t s0 = (tid & 1) ? 0x7632 : 0x5410, s1 = s0 ^ 0x2222;
        sts128(a0 ^ o, __byte_perm(u.x, u.y, s0), __byte_perm(u.z, u.w, s0), __byte_perm(v.x, v.y, s0), __byte_perm(v.z, v.w, s0));
        sts128(a0 ^ o ^ 16, __byte_perm(u.x, u.y, s1), __byte_perm(u.z, u.w, s1), __byte_perm(v.x, v.y, s1), __byte_perm(v.z, v.w, s1));
    }

    uint32_t en[8], hr[8], rk[8], em[8];
    int xc[2];
    const uint32_t tref = __shfl_sync(~0u, gtime() >> 5, 0);
    {
        uint4* mp = g_mail + blk * NSRC * 8 + tid;
        int it = 0;
        bool ok;
        while ((int)((uint32_t)clock() - tpub) < POLL_DELAY) {}
        do {
#pragma unroll
            for (int k = 0; k < 2; k++)
                    asm volatile("ld.relaxed.gpu.global.v4.u32 {%0,%1,%2,%3}, [%4];"
                                 : "=r"(en[4 * k]), "=r"(en[4 * k + 1]), "=r"(en[4 * k + 2]), "=r"(en[4 * k + 3])
                                 : "l"(mp + k * NTHR) : "memory");
            uint32_t m = ~0u;
#pragma unroll
            for (int i = 0; i < 8; i++) m = min(m, en[i]);
            ok = __all_sync(~0u, m != 0);
            if (++it > (1 << 20)) __trap();
        } while (!ok);
        STAMP(3);
#pragma unroll
        for (int i = 0; i < 8; i++) {
            const uint32_t w = en[i] & 0x3ffff, code = ((w >> 9) * 13108) >> 16;
            hr[i] = en[i] < 0xc0000000u ? sb + SC_HIST + ((code >> 2) * HS + (en[i] >> 25)) * 4 : dump;
            rk[i] = atoms_inc(hr[i]);
            em[i] = ((((tid + (i >> 2) * NTHR) >> 3) * EPC + w - code * 2560 - 1) * 8) | (code & 3);
        }
        int dt = -(1 << 20);
#pragma unroll
        for (int k = 0; k < 2; k++) {
            const bool hd = (lane & 7) == 7;
            dt = max(dt, hd ? (int)(((en[4 * k + 3] >> 12) - tref) << 14) >> 14 : -(1 << 20));
            xc[k] = hd ? max((int)(en[4 * k + 3] & 0xfff) - 31, 0) : 0;
        }
        dt = __reduce_max_sync(~0u, dt);
        asm volatile("red.shared.max.u32 [%0], %1;" ::"r"(lane == 0 ? sb + SM_MISC + MI_TMAX * 4 : dump + 128), "r"(tref + dt + (1u << 27)) : "memory");
        if (xc[0] | xc[1]) {
#pragma unroll
            for (int k = 0; k < 2; k++) {
                const int slot = atomicAdd(&mi[MI_XN], xc[k]);
                for (int r = 0; r < xc[k] && slot + r < 32; r++)
                    reinterpret_cast<uint32_t*>(smem + SC_XTRA)[slot + r] = ((tid + k * NTHR) >> 3) * 32 + r;
            }
        }
#pragma unroll
        for (int k = 0; k < 2; k++)
            mp[k * NTHR] = make_uint4(0, 0, 0, 0);
    }
    __syncthreads();
    STAMP(4);
    uint32_t* hist = reinterpret_cast<uint32_t*>(smem + SC_HIST);
    const int xn = mi[MI_XN];
    uint32_t xi = 0, xv = 1;
    if (warp < 10) {
        uint32_t* hp = hist + (warp * 2 + (lane >> 4)) * HS + (lane & 15) * 5;
        int c[5], s = 0;
#pragma unroll
        for (int j = 0; j < 5; j++) { c[j] = hp[j]; s += c[j]; }
        int inc = s;
#pragma unroll
        for (int o = 1; o < 16; o <<= 1) { int v = __shfl_up_sync(~0u, inc, o, 16); if ((lane & 15) >= o) inc += v; }
        int base = 0;
        if ((lane & 15) == 15) {
            const int tm = (warp * 2 + (lane >> 4)) / 5;
            base = tm * 256 + atomicAdd(&mi[MI_NU + tm], (inc + 3) >> 2);
            hp[5] = (base + ((inc + 3) >> 2)) << 16;
        }
        const int tot = __shfl_sync(~0u, inc, 15, 16);
        base = __shfl_sync(~0u, base, 15, 16);
        int ex = inc - s;
#pragma unroll
        for (int j = 0; j < 5; j++) {
            hp[j] = (base * 4 + ex) | ((base + ((ex == tot ? ex + 3 : ex + 1) >> 2)) << 16);
            ex += c[j];
        }
    } else if (warp == 10) {
        if (lane == 0) init_barriers();
        if (lane < xn) {
            xi = reinterpret_cast<const uint32_t*>(smem + SC_XTRA)[lane];
            asm volatile("ld.relaxed.gpu.global.u32 %0, [%1];" : "=r"(xv) : "l"(g_mail2 + blk * NSRC * 32 + xi) : "memory");
        }
    } else if (warp >= 12) {
        const uint32_t d = sb + (warp - 12) * NG * STAGE + lane * 16;
#pragma unroll
        for (int m = 0; m < 8; m++) {
            uint32_t w[4];
#pragma unroll
            for (int j = 0; j < 4; j++)
                w[j] = mul_lo(lds32(sb + SC_WR + (2 * t + (j & 1) + (j >> 1) * 8) * 256 + (((m * 8 + g) * 4) ^ (t << 5))), 0x3f003f00u);
            sts128(d + (m >> 2) * ROWP + (m & 3) * 512, __byte_perm(w[0], w[1], 0x5410), __byte_perm(w[0], w[1], 0x7632),
                   __byte_perm(w[2], w[3], 0x5410), __byte_perm(w[2], w[3], 0x7632));
        }
        uint32_t c[4];
#pragma unroll
        for (int i = 0; i < 4; i++) {
            const uint32_t ca = sb + SC_WR + 4096 + (i * 16 + (t & 1) * 8 + (g & 3)) * 2;
            c[i] = (lds16(ca) | (lds16(ca + 8) << 16)) & ((t >> 1) == (g >> 2) ? ~0u : 0u);
        }
        sts128(d + 2 * ROWP, c[0], c[1], c[2], c[3]);
    } else if (lane == 0) {
        sts32(sb + SC_GPOS + GDUMMY * 4, (uint32_t)(4 * UCAP * REC + 128) * 0x10001u);
        constexpr int start_ns = START_NS;
        mi[MI_T0] = (uint32_t)clock() + (((int)(((uint32_t)mi[MI_TMAX] << 5) + start_ns - gtime()) * 31) >> 4);
    }
    __syncthreads();
    STAMP(10);
    int myng = mi[MI_NU + (lane & 3)];
    const bool ovf = __any_sync(~0u, myng + xn > 2 * (UCAP - 4) || xn > 32);
    if (!ovf) {
        constexpr int pace = PACE_Q8, p1 = PACE_HEAD, b1 = HEAD_BK, p2 = PACE_TAIL, b2 = TAIL_BK, lead = PACE_LEAD;
        auto sched = [&](int b) { return b * pace - min(b, b1) * (pace - p1) - max(b - b2, 0) * (pace - p2) - lead; };
        if (warp < 10) {
            const int team = tid / NBK, b = tid - team * NBK;
            int lo[5], n[5], pos = team * UCAP * 2, nsum = 0;
#pragma unroll
            for (int q = 0; q < 5; q++) {
                lo[q] = hist[(team * 5 + q) * HS + b] >> 16;
                n[q] = (hist[(team * 5 + q) * HS + b + 1] >> 16) - lo[q];
                pos += lo[q] - (hist[(team * 5 + q) * HS] >> 16);
                nsum += n[q];
            }
            const int step = __float2int_rz(__fdividef((float)(sched(b + 1) - sched(b)), (float)max(nsum, 1)));
            const int tb = sched(b) + step / 2 - pos * step;
            const uint32_t t0 = mi[MI_T0];
            auto emit = [&](int q, int r, int pq) {
                const bool on = r < n[q];
                const uint32_t ro = (pq >> 1) * REC, par = pq & 1;
                sts32(on ? sb + SC_GPOS + (lo[q] + r) * 4 : dump, ro * 0x10001u + par * 0x40002u + (REC | (16 << 16)));
                sts8(on ? sb + SM_REC + 48 + ro + par : dump, q);
                sts16(on && !par ? sb + SM_REC + REC + 50 + ro : dump, (t0 + max(tb + pq * step, 0)) >> 2);
            };
#pragma unroll
            for (int q = 0, pq = pos; q < 5; pq += n[q], q++) emit(q, 0, pq);
#pragma unroll
            for (int q = 0; q < 5; pos += n[q], q++)
#pragma unroll 1
                for (int r = 1; __any_sync(~0u, r < n[q]); r++) emit(q, r, pos + r);
        } else if (warp == 10) {
            for (int n = 0; __any_sync(~0u, xv == 0); n++) {
                if (xv == 0) asm volatile("ld.relaxed.gpu.global.u32 %0, [%1];" : "=r"(xv) : "l"(g_mail2 + blk * NSRC * 32 + xi) : "memory");
                if (n > (1 << 20)) __trap();
            }
            const uint32_t w = xv & 0x3ffff, code = ((w >> 9) * 13108) >> 16, xt = lane < xn ? code / 20 : 4;
            const uint32_t same = __match_any_sync(~0u, xt);
            const int pq = __shfl_sync(~0u, myng, xt & 3) + __popc(same & ((1u << lane) - 1));
#pragma unroll
            for (int q = 0; q < 4; q++) {
                const int c = __popc(__ballot_sync(~0u, xt == q));
                if (lane == q) myng += c;
            }
            if (lane < xn) {
                g_mail2[blk * NSRC * 32 + xi] = 0;
                const uint32_t a = sb + SM_REC + (xt * UCAP + (pq >> 1)) * REC;
                sts16(a + REC + (pq & 1) * 2, xv >> 18);
                sts32(a + 16 + (pq & 1) * 4, (((xi >> 5) * EPC + w - code * 2560 - 1) * 8) | (code & 3));
                sts8(a + 48 + (pq & 1), (code >> 2) - xt * 5);
                if (!(pq & 1)) sts16(a + REC + 50, ((uint32_t)mi[MI_T0] + sched(NBK - 2)) >> 2);
            }
            if (lane < 4) {
                const uint32_t a = sb + SM_REC + (lane * UCAP + (myng >> 1)) * REC + 48;
                if (myng & 1) sts8(a + 1, 0);
                sts16(a + (myng & 1) * REC, 5);
                mi[MI_END + lane] = (myng + 1) >> 1;
            }
        }
#pragma unroll
        for (int i = 0; i < 8; i++) {
            const uint32_t p = en[i] < 0xc0000000u ? rk[i] + lds16(hr[i]) : GDUMMY * 4;
            hr[i] = sb + SC_GPOS + (p & ~3u);
            rk[i] = (p & 3) * 0x80004u;
        }
        __syncthreads();
        STAMP(11);
#pragma unroll
        for (int i = 0; i < 8; i++) rk[i] += lds32(hr[i]);
#pragma unroll
        for (int i = 0; i < 8; i++) {
            sts16(sb + SM_REC + (rk[i] & 0xffff), en[i] >> 18);
            sts32(sb + SM_REC + (rk[i] >> 16), em[i]);
        }
    } else {
        if (tid < 4) {
            sts16(sb + SM_REC + tid * UCAP * REC + 48, 5);
            mi[MI_END + tid] = 0;
        }
        generic_path(reinterpret_cast<float*>(smem), x, src, dst, Y, ef, w_rad, cg, xc[0], xc[1]);
    }

    __syncwarp();
    if (warp >= 8) {
        asm volatile("bar.sync 3, 512;" ::: "memory");
        asm volatile("setmaxnreg.dec.sync.aligned.u32 24;");
        const int team = warp & 3;
        if (ovf) {
            asm volatile("bar.sync 2;" ::: "memory");
            if (tid == 256) init_barriers();
            asm volatile("bar.sync 2;" ::: "memory");
        }
        STAMP(5);
        const uint32_t ring = sb + SM_RING + team * NG * STAGE;
        const uint32_t q = lane >> 3, c = lane & 7, rec = sb + SM_REC + team * UCAP * REC;
        __syncwarp();
        producer_loop(reinterpret_cast<const char*>(x) + (ROWMODE == 0 ? c : ROWMODE == 1 ? lane & 15 : lane) * 16, reinterpret_cast<const char*>(ef) + (c & 1) * 16, Y,
                      q * ROWP + ((c ^ (q << 1)) << 4), q * 4 + (c & 2) * 8, (c & 1) * 2 + (c >> 2), ring, rec,
                      rec + (mi[MI_END + team] + 1) * REC, warp - 8, sb + SM_MISC + MI_SHIFT * 4,
                      ROWMODE == 1 ? (lane >> 4) * ROWP + (((lane & 15) ^ ((lane >> 4) << 1)) << 4) : lane * 16);
        uint32_t ln, sb2, cta;
        asm volatile("mov.u32 %0, %%tid.x;\nmov.u32 %1, %%ctaid.x;\nmov.u32 %2, %%dynamic_smem_size;" : "=r"(ln), "=r"(cta), "=r"(sb2));
        if (FEEDBACK && cta == NB - 1 && ln >= NTHR - 32) {
            ln &= 31;
            sb2 += smem_u32(smem) - SM_TOTAL + SM_MISC;
            constexpr int lead = LEAD_CLK >> 2;
            const uint32_t tend = lds32(sb2 + MI_T0 * 4) + 70 * PACE_Q8;
            int sh = 0;
            for (int n = 0; n < 199 && (int)((uint32_t)clock() - tend - (sh >> 14)) < 0; n++) {
                int v;
                asm volatile("ld.relaxed.gpu.global.s32 %0, [%1];" : "=r"(v) : "l"(g_lag[ln * 4]) : "memory");
                sh += (max((__reduce_add_sync(~0u, max(v, 0)) >> 5) - lead, 0) * FB_GAIN >> 3) << 16;
#pragma unroll
                for (int k = 0; k < 5; k++)
                    asm volatile("st.relaxed.gpu.global.s32 [%0], %1;" ::"l"(g_lag[NB + min(ln + 32 * k, NB - 1u)]), "r"(sh) : "memory");
            }
        }
    } else {
        int team;
        {
            const int n0 = mi[MI_END], n1 = mi[MI_END + 1], n2 = mi[MI_END + 2], n3 = mi[MI_END + 3];
            const int d1 = abs(n0 + n1 - n2 - n3), d2 = abs(n0 + n2 - n1 - n3), d3 = abs(n0 + n3 - n1 - n2);
            const uint32_t perm = PAIRING && d1 < min(d2, d3) ? 0x3120 : PAIRING && d3 < d2 ? 0x2310 : 0x3210;
            team = __shfl_sync(~0u, (perm >> ((warp >> 1) * 4)) & 3, 0);
        }
        const int h = warp & 1;
        asm volatile("bar.arrive 3, 512;" ::: "memory");
        asm volatile("setmaxnreg.inc.sync.aligned.u32 232;");
        uint32_t ring = sb + SM_RING + team * NG * STAGE;
        uint32_t wf[4][4], cgf[4];
#pragma unroll
        for (int m = 0; m < 5; m++) {
            const uint4 v = lds128(ring + (m < 4 ? h * ROWP + m * 512 : 2 * ROWP) + lane * 16);
            uint32_t* f = m < 4 ? wf[m] : cgf;
            f[0] = v.x; f[1] = v.y; f[2] = v.z; f[3] = v.w;
        }
        float acc[5][4][2][4];
        if (!ovf) {
#pragma unroll
            for (int l = 0; l < 5; l++)
#pragma unroll
                for (int m = 0; m < 4; m++)
#pragma unroll
                    for (int p = 0; p < 2; p++)
#pragma unroll
                        for (int r = 0; r < 4; r++) acc[l][m][p][r] = 0.f;
        } else {
            const float* sagg = reinterpret_cast<const float*>(smem);
#pragma unroll
            for (int l = 0; l < 5; l++)
#pragma unroll
                for (int m = 0; m < 4; m++)
#pragma unroll
                    for (int p = 0; p < 2; p++)
#pragma unroll
                        for (int r = 0; r < 4; r++) {
                            int nd = l * 4 + (g >> 2) + (r >> 1) * 2;
                            int ch = h * 64 + m * 16 + 4 * t + (r & 1) * 2 + p;
                            acc[l][m][p][r] = nd < 19 ? sagg[(team * 19 + nd) * 512 + ch * 4 + (g & 3)] : 0.f;
                        }
            asm volatile("bar.sync 2;" ::: "memory");
            asm volatile("bar.sync 2;" ::: "memory");
        }
        const uint32_t xoff = t * ROWP + h * 512 + ((g ^ (t << 1)) << 4);
        const uint32_t mat = lane >> 3, mhi = (lane >> 2) & 1;
        const bool isy = mat < 2;
        const uint32_t ml = isy ? (t & 2) + (mat & 1) : t;
        const uint32_t moff = ml * ROWP + 2048 + (((isy ? 4 + 2 * mhi + (t & 1) : 2 * mhi + mat - 2) ^ (ml << 1)) << 4);
        __syncwarp();
        consumer_loop(acc, wf, cgf, xoff, ring, moff, sb + SM_REC + team * UCAP * REC);
        {
        int lane_;
        asm volatile("mov.u32 %0, %%laneid;" : "=r"(lane_));
        const int lane = lane_, g = lane >> 2, t = lane & 3;
        const uint32_t sb = ring - team * NG * STAGE;
        STAMP(7);
        asm volatile("bar.sync %0, 64;" ::"r"(4 + team) : "memory");
        {
            const int rr = ((g & 3) >> 1) * 8 + (g >> 2) * 2 + (g & 1);
#pragma unroll
            for (int l = 0; l < 5; l++)
#pragma unroll
                for (int hi = 0; hi < 2; hi++) {
                    const int R = l * 16 + rr + hi * 4;
                    const uint32_t a = sb + team * AGGT + h * 10240 + R * 128;
#pragma unroll
                    for (int c = 0; c < 2; c++) {
                        const int m = 2 * c;
                        sts128(a + (((2 * t + c) ^ (R & 7)) << 4),
                               pack_bf16(acc[l][m][0][2 * hi], acc[l][m][1][2 * hi]),
                               pack_bf16(acc[l][m][0][2 * hi + 1], acc[l][m][1][2 * hi + 1]),
                               pack_bf16(acc[l][m + 1][0][2 * hi], acc[l][m + 1][1][2 * hi]),
                               pack_bf16(acc[l][m + 1][0][2 * hi + 1], acc[l][m + 1][1][2 * hi + 1]));
                    }
                }
        }
        asm volatile("fence.proxy.async.shared::cta;" ::: "memory");
        uint32_t wa[8][4];
        {
            const int r = lane & 7, k = (lane >> 4) * 8 + r;
            const int chunk = (2 * warp + ((lane >> 3) & 1)) ^ r;
#pragma unroll
            for (int ks = 0; ks < 8; ks++) {
                const int c = (ks >> 2) * 64 + 16 * (k >> 2) + 4 * (ks & 3) + (k & 3);
                asm volatile("ldmatrix.sync.aligned.m8n8.x4.trans.shared.b16 {%0,%1,%2,%3}, [%4];"
                             : "=r"(wa[ks][0]), "=r"(wa[ks][1]), "=r"(wa[ks][2]), "=r"(wa[ks][3])
                             : "r"(sb + SM_W + c * 256 + (chunk << 4)));
            }
        }
        asm volatile("bar.sync 1, 256;" ::: "memory");
        STAMP(8);
        const int sl = (lane & 7) * 4 + (lane >> 3);
        __nv_bfloat16* op = out + (size_t)(blk * NPB + (lane >> 3)) * 512 + warp * 64 + (lane & 7) * 8;
        const int nleft = N_NODES - blk * NPB - (lane >> 3);
#pragma unroll 1
        for (int tm = 0; tm < 4; tm++) {
            float o[40];
            asm volatile("wgmma.fence.sync.aligned;" ::: "memory");
#pragma unroll
            for (int ks = 0; ks < 8; ks++) {
                const uint32_t a = sb + tm * AGGT + (ks >> 2) * 10240 + (ks & 3) * 32;
                const uint64_t desc = (uint64_t)((a & 0x3ffff) >> 4) | (1ull << 16) | (64ull << 32) | (1ull << 62);
                wgmma_n80(o, wa[ks], desc, ks);
            }
            asm volatile("wgmma.commit_group.sync.aligned;" ::: "memory");
            asm volatile("wgmma.wait_group.sync.aligned 0;" ::: "memory");
#pragma unroll
            for (int i = 0; i < 40; i++) asm volatile("" : "+f"(o[i])::"memory");
#pragma unroll
            for (int l = 0; l < 5; l++) {
                uint4 v;
                v.x = __shfl_sync(~0u, pack_bf16(o[8 * l + 0], o[8 * l + 1]), sl);
                v.y = __shfl_sync(~0u, pack_bf16(o[8 * l + 4], o[8 * l + 5]), sl);
                v.z = __shfl_sync(~0u, pack_bf16(o[8 * l + 2], o[8 * l + 3]), sl);
                v.w = __shfl_sync(~0u, pack_bf16(o[8 * l + 6], o[8 * l + 7]), sl);
                if ((l < 4 || lane < 24) && tm * 19 + l * 4 < nleft)
                    *reinterpret_cast<uint4*>(op + (tm * 19 + l * 4) * 512) = v;
            }
        }
        STAMP(9);
        }
    }
}

}

extern "C" void kernel_launch(void* const* d_in, const int* in_sizes, int n_in, void* d_out, int out_size) {
    (void)in_sizes; (void)n_in; (void)out_size;
    const __nv_bfloat16* x = (const __nv_bfloat16*)d_in[0];
    const int* src = (const int*)d_in[1];
    const int* dst = (const int*)d_in[2];
    const __nv_bfloat16* Y = (const __nv_bfloat16*)d_in[3];
    const __nv_bfloat16* ef = (const __nv_bfloat16*)d_in[4];
    const __nv_bfloat16* w_rad = (const __nv_bfloat16*)d_in[5];
    const __nv_bfloat16* cg = (const __nv_bfloat16*)d_in[6];
    const __nv_bfloat16* w_mix = (const __nv_bfloat16*)d_in[7];
    __nv_bfloat16* out = (__nv_bfloat16*)d_out;

    static int sms = 0;
    if (sms == 0) {
        int dev = 0;
        cudaGetDevice(&dev);
        cudaDeviceGetAttribute(&sms, cudaDevAttrMultiProcessorCount, dev);
        cudaFuncSetAttribute(tfn_kernel<3>, cudaFuncAttributeMaxDynamicSharedMemorySize, SM_TOTAL);
        cudaFuncSetAttribute(tfn_kernel<1>, cudaFuncAttributeMaxDynamicSharedMemorySize, SM_TOTAL);
        cudaFuncSetAttribute(tfn_kernel<2>, cudaFuncAttributeMaxDynamicSharedMemorySize, SM_TOTAL);
    }
    if (sms >= NB) {
        tfn_kernel<3><<<NB, NTHR, SM_TOTAL>>>(x, src, dst, Y, ef, w_rad, cg, w_mix, out);
    } else {
        tfn_kernel<1><<<NB, NTHR, SM_TOTAL>>>(x, src, dst, Y, ef, w_rad, cg, w_mix, out);
        tfn_kernel<2><<<NB, NTHR, SM_TOTAL>>>(x, src, dst, Y, ef, w_rad, cg, w_mix, out);
    }
}
```

```cpp
#include <cuda_runtime.h>
#include <cuda_bf16.h>
#include <stdint.h>

namespace {

constexpr int N_NODES = 10000;
constexpr int N_EDGES = 320000;
constexpr int NB      = 132;
constexpr int NPB     = 76;
constexpr int NSRC    = 128;
constexpr int EPC     = N_EDGES / NSRC;
constexpr int NTHR    = 512;
#define NGS 5
constexpr int NG      = NGS;
constexpr int ROWP    = 2176;
constexpr int STAGE   = 4 * ROWP + 128;
constexpr int UCAP    = 104;
constexpr int REC     = 52;
constexpr int NBK     = 80;
constexpr int HS      = 81;

#define PACE_Q8 628
#define PACE_LEAD 300
#define PACE_HEAD 730
#define HEAD_BK 10
#define PACE_TAIL 610
#define TAIL_BK 66
#define POLL_DELAY 1350
#define LEAD_CLK 550
#define ROWMODE 1
#define PAIRING 1
#define FEEDBACK 1
#define FB_GAIN 24
#define FB_DOWN 4
#define FB_MIN 0
#define START_NS 3300

constexpr int SM_RING  = 0;
constexpr int SM_W     = 4 * NG * STAGE;
constexpr int SM_REC   = SM_W + 32768;
constexpr int SM_MISC  = SM_REC + 4 * UCAP * REC;
constexpr int SM_TOTAL = SM_MISC + 224;
constexpr int SC_MAIL  = 1 * STAGE;
constexpr int SC_CNT   = 3 * STAGE;
constexpr int SC_DUMP  = 3 * STAGE + 1024;
constexpr int SC_XTRA  = 3 * STAGE + 2048;
constexpr int SC_HIST  = 4 * STAGE;
constexpr int SC_GPOS  = 6 * STAGE;
constexpr int SC_WR    = 7 * STAGE;
constexpr int GDUMMY   = 1024;
constexpr int AGGT     = (NG * STAGE + 1023) / 1024 * 1024;
static_assert(3 * AGGT + 20480 <= 4 * NG * STAGE, "agg tile inside the team's ring");
static_assert(NPB * 512 * 4 <= 4 * NG * STAGE, "slow tile");
static_assert(SM_TOTAL <= 232448, "smem");
static_assert(SM_REC % 16 == 0 && (4 * UCAP * REC) % 16 == 0 && SM_MISC % 16 == 0, "align");
constexpr int MI_XN = 0;
constexpr int MI_TMAX = 2;
constexpr int MI_SHIFT = 48;
constexpr int MI_NU = 8;
constexpr int MI_END = 28;
constexpr int MI_T0 = 3;

__device__ uint4 g_mail[NB * NSRC * 8];
__device__ uint32_t g_mail2[NB * NSRC * 32];
__device__ __align__(128) int g_lag[2 * NB][32];
#define STAMP(k)

__device__ __forceinline__ uint32_t smem_u32(const void* p) { return (uint32_t)__cvta_generic_to_shared(p); }
__device__ __forceinline__ uint32_t atoms_inc(uint32_t a) {
    uint32_t r;
    asm volatile("atom.shared.add.u32 %0, [%1], 1;" : "=r"(r) : "r"(a) : "memory");
    return r;
}
__device__ __forceinline__ void sts32(uint32_t a, uint32_t v) { asm volatile("st.shared.u32 [%0], %1;" ::"r"(a), "r"(v) : "memory"); }
__device__ __forceinline__ void sts16(uint32_t a, uint32_t v) { asm volatile("st.shared.u16 [%0], %1;" ::"r"(a), "h"((uint16_t)v) : "memory"); }
__device__ __forceinline__ void sts8(uint32_t a, uint32_t v) { asm volatile("st.shared.u8 [%0], %1;" ::"r"(a), "r"(v) : "memory"); }
__device__ __forceinline__ uint32_t lds32(uint32_t a) { uint32_t v; asm volatile("ld.shared.u32 %0, [%1];" : "=r"(v) : "r"(a)); return v; }
__device__ __forceinline__ uint32_t lds16(uint32_t a) { uint32_t v; asm volatile("ld.shared.u16 %0, [%1];" : "=r"(v) : "r"(a)); return v; }
__device__ __forceinline__ void cp16(uint32_t d, const void* p) {
    asm volatile("cp.async.cg.shared.global [%0], [%1], 16;" ::"r"(d), "l"(p) : "memory");
}
__device__ __forceinline__ uint32_t gtime() {
    uint32_t t;
    asm volatile("mov.u32 %0, %%globaltimer_lo;" : "=r"(t));
    return t;
}
__device__ __forceinline__ void mbar_init(uint32_t bar, int cnt) {
    asm volatile("mbarrier.init.shared.b64 [%0], %1;" ::"r"(bar), "r"(cnt) : "memory");
}
__device__ __forceinline__ void mbar_wait(uint32_t bar, uint32_t parity) {
    asm volatile("{\n.reg .pred p;\n.reg .u32 n;\nmov.u32 n, 0;\n"
                 "WAIT_%=:\nmbarrier.try_wait.parity.shared.b64 p, [%0], %1;\n@p bra DONE_%=;\n"
                 "add.u32 n, n, 1;\nsetp.lt.u32 p, n, 4194304;\n@p bra WAIT_%=;\ntrap;\nDONE_%=:\n}"
                 ::"r"(bar), "r"(parity) : "memory");
}
__device__ __forceinline__ void mbar_arrive_elect(uint32_t bar) {
    asm volatile("{\n.reg .pred p;\nelect.sync _|p, 0xffffffff;\n@p mbarrier.arrive.shared.b64 _, [%0];\n}" ::"r"(bar) : "memory");
}
__device__ __forceinline__ uint4 lds128(uint32_t a) {
    uint4 v;
    asm volatile("ld.shared.v4.u32 {%0,%1,%2,%3}, [%4];" : "=r"(v.x), "=r"(v.y), "=r"(v.z), "=r"(v.w) : "r"(a));
    return v;
}
__device__ __forceinline__ void sts128(uint32_t a, uint32_t x, uint32_t y, uint32_t z, uint32_t w) {
    asm volatile("st.shared.v4.u32 [%0], {%1,%2,%3,%4};" ::"r"(a), "r"(x), "r"(y), "r"(z), "r"(w) : "memory");
}
__device__ __forceinline__ uint32_t pack_bf16(float lo, float hi) {
    uint32_t r;
    asm("cvt.rn.bf16x2.f32 %0, %1, %2;" : "=r"(r) : "f"(hi), "f"(lo));
    return r;
}
__device__ __forceinline__ float tanh_fast(float x) {
    float r;
    asm("tanh.approx.f32 %0, %1;" : "=f"(r) : "f"(x));
    return r;
}
__device__ __forceinline__ uint32_t mul_lo(uint32_t v, uint32_t r) {
    __nv_bfloat162 a = *reinterpret_cast<__nv_bfloat162*>(&v), b = *reinterpret_cast<__nv_bfloat162*>(&r);
    __nv_bfloat162 c = __hmul2(a, __low2bfloat162(b));
    return *reinterpret_cast<uint32_t*>(&c);
}
__device__ __forceinline__ uint32_t mul_hi(uint32_t v, uint32_t r) {
    __nv_bfloat162 a = *reinterpret_cast<__nv_bfloat162*>(&v), b = *reinterpret_cast<__nv_bfloat162*>(&r);
    __nv_bfloat162 c = __hmul2(a, __high2bfloat162(b));
    return *reinterpret_cast<uint32_t*>(&c);
}
__device__ __forceinline__ void mma0(float (&d)[4], uint32_t a0, uint32_t a1, uint32_t a2, uint32_t a3,
                                     uint32_t b0, uint32_t b1) {
    asm("mma.sync.aligned.m16n8k16.row.col.f32.bf16.bf16.f32 {%0,%1,%2,%3}, {%4,%5,%6,%7}, {%8,%9}, {%10,%10,%10,%10};"
        : "=f"(d[0]), "=f"(d[1]), "=f"(d[2]), "=f"(d[3])
        : "r"(a0), "r"(a1), "r"(a2), "r"(a3), "r"(b0), "r"(b1), "f"(0.f));
}
__device__ __forceinline__ void mma0_k8(float (&d)[4], uint32_t a0, uint32_t a1, uint32_t b0) {
    asm("mma.sync.aligned.m16n8k8.row.col.f32.bf16.bf16.f32 {%0,%1,%2,%3}, {%4,%5}, {%6}, {%7,%7,%7,%7};"
        : "=f"(d[0]), "=f"(d[1]), "=f"(d[2]), "=f"(d[3])
        : "r"(a0), "r"(a1), "r"(b0), "f"(0.f));
}
__device__ __forceinline__ void mma_acc(float (&d)[4], const uint32_t (&a)[4], uint32_t b0, uint32_t b1) {
    asm volatile("mma.sync.aligned.m16n8k16.row.col.f32.bf16.bf16.f32 {%0,%1,%2,%3}, {%4,%5,%6,%7}, {%8,%9}, {%0,%1,%2,%3};"
        : "+f"(d[0]), "+f"(d[1]), "+f"(d[2]), "+f"(d[3])
        : "r"(a[0]), "r"(a[1]), "r"(a[2]), "r"(a[3]), "r"(b0), "r"(b1));
}
__device__ __forceinline__ void wgmma_n80(float (&d)[40], const uint32_t (&a)[4], uint64_t desc, int scale_d) {
    asm volatile("{\n.reg .pred p;\nsetp.ne.b32 p, %45, 0;\n"
        "wgmma.mma_async.sync.aligned.m64n80k16.f32.bf16.bf16 "
        "{%0,%1,%2,%3,%4,%5,%6,%7,%8,%9,%10,%11,%12,%13,%14,%15,%16,%17,%18,%19,"
        "%20,%21,%22,%23,%24,%25,%26,%27,%28,%29,%30,%31,%32,%33,%34,%35,%36,%37,%38,%39}, "
        "{%40,%41,%42,%43}, %44, p, 1, 1, 0;\n}"
        : "+f"(d[0]), "+f"(d[1]), "+f"(d[2]), "+f"(d[3]), "+f"(d[4]), "+f"(d[5]), "+f"(d[6]), "+f"(d[7]),
          "+f"(d[8]), "+f"(d[9]), "+f"(d[10]), "+f"(d[11]), "+f"(d[12]), "+f"(d[13]), "+f"(d[14]), "+f"(d[15]),
          "+f"(d[16]), "+f"(d[17]), "+f"(d[18]), "+f"(d[19]), "+f"(d[20]), "+f"(d[21]), "+f"(d[22]), "+f"(d[23]),
          "+f"(d[24]), "+f"(d[25]), "+f"(d[26]), "+f"(d[27]), "+f"(d[28]), "+f"(d[29]), "+f"(d[30]), "+f"(d[31]),
          "+f"(d[32]), "+f"(d[33]), "+f"(d[34]), "+f"(d[35]), "+f"(d[36]), "+f"(d[37]), "+f"(d[38]), "+f"(d[39])
        : "r"(a[0]), "r"(a[1]), "r"(a[2]), "r"(a[3]), "l"(desc), "r"(scale_d));
}

__device__ __forceinline__ void producer_loop(const void* xl, const void* efl, const void* Y, uint32_t xd, uint32_t oef,
                                              uint32_t ysel, uint32_t ring, uint32_t rec, uint32_t rlast, uint32_t odd,
                                              uint32_t lag, uint32_t xh) {
    asm volatile(
        "{\n"
        ".reg .b32 w, em, ey, cu, d, t, u, n, sa, ph, rp, rend, rlast, dy, sv, lag, lv, w2, w3, w4;\n"
        ".reg .b16 tg;\n"
        ".reg .b64 pa, pb, pc, pd;\n"
        ".reg .pred lo, z, q, e, zb, fbk;\n"
        "redux.sync.or.b32 sa, %6, 0xffffffff;\n"
        "redux.sync.or.b32 rp, %7, 0xffffffff;\n"
        "redux.sync.or.b32 rlast, %8, 0xffffffff;\n"
        "redux.sync.or.b32 lag, %11, 0xffffffff;\n"
        "setp.eq.u32 fbk, %9, 0;\n"
        "add.u32 rend, sa, 44160;\n"
        "and.b32 t, %5, 1;\n"
        "setp.eq.u32 lo, t, 0;\n"
        "mov.u32 ph, 1;\n"
        "setp.ge.u32 q, %9, 4;\n"
        "@q bra.uni PODD_%=;\n"
        "add.u32 t, rp, %4;\n"
        "ld.shared.u32 em, [t+16];\n"
        "and.b32 t, em, 0xfffffff8;\n"
        "mad.wide.u32 pa, t, 4, %1;\n"
        "add.u32 d, sa, %3;\n"
        "@lo cp.async.cg.shared.global [d+2048], [pa], 16;\n"
        "cp.async.mbarrier.arrive.noinc.shared.b64 [sa+8704];\n"
        "add.u32 rp, rp, 52;\n"
        "add.u32 sa, sa, 8832;\n"
        "PODD_%=:\n"
        "add.u32 rp, rp, 52;\n"
        "add.u32 sa, sa, 8832;\n"
        "shr.u32 t, %4, 1;\n"
        "and.b32 t, t, 4;\n"
        "add.u32 t, t, rp;\n"
        "ld.shared.u32 w, [t];\n"
        "ld.shared.u32 w2, [t+8];\n"
        "add.u32 t, rp, %4;\n"
        "ld.shared.u32 em, [t+16];\n"
        "ld.shared.u32 ey, [t+-36];\n"
        "ld.shared.u32 cu, [rp+48];\n"
        "ld.volatile.shared.u32 sv, [lag];\n"
        "setp.eq.u32 e, sa, sa;\n"
        "setp.lt.u32 q, rp, rlast;\n"
        "@!q bra.uni PF_%=;\n"
        "PL_%=:\n"
        "add.u32 cu, cu, sv;\n"
        "mov.u32 u, %%clock;\n"
        "shl.b32 u, u, 14;\n"
        "sub.u32 u, u, cu;\n"
        "setp.ge.and.s32 q, u, 0, e;\n"
        "@q bra.uni PGO_%=;\n"
        "mov.u32 n, 0;\n"
        "PW1_%=:\n"
        "@e bra.uni PW2_%=;\n"
        "mbarrier.try_wait.parity.shared.b64 e, [sa+8712], ph;\n"
        "add.u32 n, n, 1;\n"
        "setp.lt.u32 q, n, 4194304;\n"
        "@q bra.uni PW1_%=;\n"
        "trap;\n"
        "PW2_%=:\n"
        "mov.u32 u, %%clock;\n"
        "shl.b32 u, u, 14;\n"
        "sub.u32 u, u, cu;\n"
        "setp.lt.s32 q, u, 0;\n"
        "@q bra.uni PW2_%=;\n"
        "PGO_%=:\n"
        "and.b32 t, em, 0xfffffff8;\n"
        "mad.wide.u32 pa, t, 4, %1;\n"
        "and.b32 t, w, 0xffff;\n"
        "mad.wide.u32 pc, t, 1024, %0;\n"
        "shr.u32 t, w, 16;\n"
        "mad.wide.u32 pd, t, 1024, %0;\n"
        "add.u32 d, sa, %3;\n"
        "@lo cp.async.cg.shared.global [d+2048], [pa], 16;\n"
        "xor.b32 t, ey, %5;\n"
        "and.b32 t, t, 7;\n"
        "setp.ne.u32 zb, t, 0;\n"
        "and.b32 t, ey, 0xfffffff8;\n"
        "cvt.u64.u32 pb, t;\n"
        "add.u64 pb, pb, %2;\n"
        "selp.u32 dy, 64, 8, lo;\n"
        "xor.b32 dy, dy, d;\n"
        "cp.async.ca.shared.global [dy+2048], [pb], 8, zb;\n"
        "add.u32 d, sa, %12;\n"
        "cp.async.cg.shared.global [d+0], [pc+0], 16;\n"
        "cp.async.cg.shared.global [d+256], [pc+256], 16;\n"
        "cp.async.cg.shared.global [d+512], [pc+512], 16;\n"
        "cp.async.cg.shared.global [d+768], [pc+768], 16;\n"
        "cp.async.cg.shared.global [d+1024], [pd+0], 16;\n"
        "cp.async.cg.shared.global [d+1280], [pd+256], 16;\n"
        "cp.async.cg.shared.global [d+1536], [pd+512], 16;\n"
        "cp.async.cg.shared.global [d+1792], [pd+768], 16;\n"
        "xor.b32 dy, d, 64;\n"
        "and.b32 t, w2, 0xffff;\n"
        "mad.wide.u32 pa, t, 1024, %0;\n"
        "cp.async.cg.shared.global [dy+4352], [pa+0], 16;\n"
        "cp.async.cg.shared.global [dy+4608], [pa+256], 16;\n"
        "cp.async.cg.shared.global [dy+4864], [pa+512], 16;\n"
        "cp.async.cg.shared.global [dy+5120], [pa+768], 16;\n"
        "shr.u32 t, w2, 16;\n"
        "mad.wide.u32 pb, t, 1024, %0;\n"
        "cp.async.cg.shared.global [dy+5376], [pb+0], 16;\n"
        "cp.async.cg.shared.global [dy+5632], [pb+256], 16;\n"
        "cp.async.cg.shared.global [dy+5888], [pb+512], 16;\n"
        "cp.async.cg.shared.global [dy+6144], [pb+768], 16;\n"
        "add.u32 rp, rp, 104;\n"
        "shr.u32 t, %4, 1;\n"
        "and.b32 t, t, 4;\n"
        "add.u32 t, t, rp;\n"
        "ld.shared.u32 w, [t];\n"
        "ld.shared.u32 w2, [t+8];\n"
        "add.u32 t, rp, %4;\n"
        "ld.shared.u32 em, [t+16];\n"
        "ld.shared.u32 ey, [t+-36];\n"
        "ld.shared.u32 cu, [rp+48];\n"
        "ld.volatile.shared.u32 sv, [lag];\n"
        "cp.async.mbarrier.arrive.noinc.shared.b64 [sa+8704];\n"
        "add.u32 sa, sa, 17664;\n"
        "sub.u32 t, sa, 44160;\n"
        "setp.ge.u32 q, sa, rend;\n"
        "selp.u32 sa, t, sa, q;\n"
        "selp.u32 t, 1, 0, q;\n"
        "xor.b32 ph, ph, t;\n"
        "mbarrier.try_wait.parity.shared.b64 e, [sa+8712], ph;\n"
        "@!fbk bra.uni PC_%=;\n"
        "ld.shared.u32 t, [rp+-56];\n"
        "mov.u32 u, %%clock;\n"
        "shl.b32 u, u, 14;\n"
        "sub.u32 u, u, t;\n"
        "sub.u32 u, u, sv;\n"
        "shr.s32 u, u, 16;\n"
        "ld.volatile.shared.u64 pa, [lag+16];\n"
        "elect.sync _|z, 0xffffffff;\n"
        "@z st.relaxed.gpu.global.u32 [pa], u;\n"
        "@z cp.async.cg.shared.global [lag], [pa+16896], 16;\n"
        "PC_%=:\n"
        "setp.lt.u32 q, rp, rlast;\n"
        "@q bra.uni PL_%=;\n"
        "PF_%=:\n"
        "setp.ne.u32 q, rp, rlast;\n"
        "@q bra.uni PX_%=;\n"
        "mov.u32 n, 0;\n"
        "PE1_%=:\n"
        "@e bra.uni PE2_%=;\n"
        "mbarrier.try_wait.parity.shared.b64 e, [sa+8712], ph;\n"
        "add.u32 n, n, 1;\n"
        "setp.lt.u32 q, n, 4194304;\n"
        "@q bra.uni PE1_%=;\n"
        "trap;\n"
        "PE2_%=:\n"
        "cp.async.mbarrier.arrive.noinc.shared.b64 [sa+8704];\n"
        "PX_%=:\n"
        "}\n"
        ::"l"(xl), "l"(efl), "l"(Y), "r"(xd), "r"(oef), "r"(ysel), "r"(ring), "r"(rec), "r"(rlast), "r"(odd),
          "n"(0), "r"(lag), "r"(xh) : "memory");
}

__device__ __forceinline__ void consumer_loop(float (&acc)[5][4][2][4], const uint32_t (&wf)[4][4], const uint32_t (&cgf)[4],
                                              uint32_t xoff, uint32_t& ring, uint32_t moff, uint32_t rec) {
    asm volatile(
        "{\n"
        ".reg .b32 x<16>, a<4>, b<4>, r<4>, m<4>, rl, rh, tag, la, lb, sa, last, ph, tq, xa, ma, n, ring, sn, ln, yb, zz, k<4>, tp;\n"
        ".reg .b16 lo, hi;\n"
        ".reg .f32 p<16>, d<4>, t0, t1, fz;\n"
        ".reg .pred q, w, el, c<5>;\n"
        "TA_%=: .branchtargets A0_%=, A1_%=, A2_%=, A3_%=, A4_%=, EXIT_%=;\n"
        "TB_%=: .branchtargets B0_%=, B1_%=, B2_%=, B3_%=, B4_%=, SPIN_%=;\n"
        "mov.f32 fz, 0f00000000;\n"
        "redux.sync.or.b32 ring, %160, 0xffffffff;\n"
        "mov.u32 sa, ring;\n"
        "add.u32 last, ring, 35328;\n"
        "mov.u32 ph, 0;\n"
        "redux.sync.xor.b32 zz, %160, 0xffffffff;\n"
        "redux.sync.or.b32 tp, %183, 0xffffffff;\n"
        "elect.sync _|el, 0xffffffff;\n"
        "mov.u32 k0, sa;\n"
        "mov.u32 k1, sa;\n"
        "mov.u32 k2, sa;\n"
        "mov.u32 k3, sa;\n"
        "mov.b32 x0, 0;\n"
        "mov.b32 x1, 0;\n"
        "mov.b32 x2, 0;\n"
        "mov.b32 x3, 0;\n"
        "mov.b32 x4, 0;\n"
        "mov.b32 x5, 0;\n"
        "mov.b32 x6, 0;\n"
        "mov.b32 x7, 0;\n"
        "mov.b32 x8, 0;\n"
        "mov.b32 x9, 0;\n"
        "mov.b32 x10, 0;\n"
        "mov.b32 x11, 0;\n"
        "mov.b32 x12, 0;\n"
        "mov.b32 x13, 0;\n"
        "mov.b32 x14, 0;\n"
        "mov.b32 x15, 0;\n"
        "mov.b32 b0, 0;\n"
        "mov.b32 r0, 0;\n"
        "mov.b32 b1, 0;\n"
        "mov.b32 r1, 0;\n"
        "mov.b32 b2, 0;\n"
        "mov.b32 r2, 0;\n"
        "mov.b32 b3, 0;\n"
        "mov.b32 r3, 0;\n"
        "mov.u32 lb, 0;\n"
        "mov.u32 n, 0;\n"
        "W0_%=:\n"
        "mbarrier.try_wait.parity.shared.b64 w, [sa+8704], 0;\n"
        "@w bra.uni W0D_%=;\n"
        "add.u32 n, n, 1;\n"
        "setp.lt.u32 q, n, 4194304;\n"
        "@q bra.uni W0_%=;\n"
        "trap;\n"
        "W0D_%=:\n"
        "add.u32 ma, sa, %182;\n"
        "ldmatrix.sync.aligned.m8n8.x4.shared.b16 {m0,m1,m2,m3}, [ma];\n"
        "ld.shared.u16 tag, [tp+48];\n"
        "add.u32 tp, tp, 52;\n"
        "add.u32 sn, sa, 8832;\n"
        "setp.eq.u32 q, sa, last;\n"
        "selp.u32 sn, ring, sn, q;\n"
        "selp.u32 tq, 1, 0, q;\n"
        "xor.b32 ph, ph, tq;\n"
        "mbarrier.test_wait.parity.shared.b64 w, [sn+8704], ph;\n"
        "mma.sync.aligned.m16n8k16.row.col.f32.bf16.bf16.f32 {p0,p1,p2,p3}, {%161,%162,%163,%164}, {m2,m3}, {fz,fz,fz,fz};\n"
        "mma.sync.aligned.m16n8k16.row.col.f32.bf16.bf16.f32 {p4,p5,p6,p7}, {%165,%166,%167,%168}, {m2,m3}, {fz,fz,fz,fz};\n"
        "mma.sync.aligned.m16n8k16.row.col.f32.bf16.bf16.f32 {p8,p9,p10,p11}, {%169,%170,%171,%172}, {m2,m3}, {fz,fz,fz,fz};\n"
        "mma.sync.aligned.m16n8k16.row.col.f32.bf16.bf16.f32 {p12,p13,p14,p15}, {%173,%174,%175,%176}, {m2,m3}, {fz,fz,fz,fz};\n"
        "@el mbarrier.arrive.shared.b64 _, [k0+8712];\n"
        "redux.sync.or.b32 ln, tag, 0xffffffff;\n"
        "mov.u32 sa, sn;\n"
        "add.u32 k0, sn, zz;\n"
        "SPIN_%=:\n"
        "mov.u32 n, 0;\n"
        "SP1_%=:\n"
        "mbarrier.try_wait.parity.shared.b64 w, [sa+8704], ph;\n"
        "@w bra.uni SP2_%=;\n"
        "add.u32 n, n, 1;\n"
        "setp.lt.u32 q, n, 4194304;\n"
        "@q bra.uni SP1_%=;\n"
        "trap;\n"
        "SP2_%=:\n"
        "brx.idx.uni lb, TB_%=;\n"
        "A0_%=:\n"
        "add.u32 xa, sa, %181;\n"
        "add.u32 ma, sa, %182;\n"
        "ldmatrix.sync.aligned.m8n8.x4.shared.b16 {m0,m1,m2,m3}, [ma];\n"
        "ld.shared.u16 tag, [tp+48];\n"
        "add.u32 tp, tp, 52;\n"
        "add.u32 sn, sa, 8832;\n"
        "setp.eq.u32 q, sa, last;\n"
        "selp.u32 sn, ring, sn, q;\n"
        "selp.u32 tq, 1, 0, q;\n"
        "xor.b32 ph, ph, tq;\n"
        "mbarrier.test_wait.parity.shared.b64 w, [sn+8704], ph;\n"
        "mma.sync.aligned.m16n8k16.row.col.f32.bf16.bf16.f32 {%0,%1,%2,%3}, {a0,a1,a2,a3}, {x0,x1}, {%0,%1,%2,%3};\n"
        "mma.sync.aligned.m16n8k16.row.col.f32.bf16.bf16.f32 {%4,%5,%6,%7}, {a0,a1,a2,a3}, {x2,x3}, {%4,%5,%6,%7};\n"
        "ld.shared.v4.u32 {x0,x1,x2,x3}, [xa+1024];\n"
        "tanh.approx.f32 t0, p1;\n"
        "tanh.approx.f32 t1, p3;\n"
        "fma.rn.f32 t0, p1, t0, p1;\n"
        "fma.rn.f32 t1, p3, t1, p3;\n"
        "cvt.rn.bf16x2.f32 r0, t1, t0;\n"
        "mma.sync.aligned.m16n8k16.row.col.f32.bf16.bf16.f32 {p0,p1,p2,p3}, {%161,%162,%163,%164}, {m2,m3}, {fz,fz,fz,fz};\n"
        "mma.sync.aligned.m16n8k16.row.col.f32.bf16.bf16.f32 {%8,%9,%10,%11}, {a0,a1,a2,a3}, {x4,x5}, {%8,%9,%10,%11};\n"
        "mma.sync.aligned.m16n8k16.row.col.f32.bf16.bf16.f32 {%12,%13,%14,%15}, {a0,a1,a2,a3}, {x6,x7}, {%12,%13,%14,%15};\n"
        "ld.shared.v4.u32 {x4,x5,x6,x7}, [xa+1152];\n"
        "mma.sync.aligned.m16n8k8.row.col.f32.bf16.bf16.f32 {d0,d1,d2,d3}, {%177,%178}, {m1}, {fz,fz,fz,fz};\n"
        "cvt.rn.bf16x2.f32 b0, d2, d0;\n"
        "cvt.rn.bf16x2.f32 b1, d3, d1;\n"
        "tanh.approx.f32 t0, p5;\n"
        "tanh.approx.f32 t1, p7;\n"
        "fma.rn.f32 t0, p5, t0, p5;\n"
        "fma.rn.f32 t1, p7, t1, p7;\n"
        "cvt.rn.bf16x2.f32 r1, t1, t0;\n"
        "mma.sync.aligned.m16n8k16.row.col.f32.bf16.bf16.f32 {p4,p5,p6,p7}, {%165,%166,%167,%168}, {m2,m3}, {fz,fz,fz,fz};\n"
        "mov.b32 {lo,hi}, r2;\n"
        "mov.b32 rl, {lo,lo};\n"
        "mov.b32 rh, {hi,hi};\n"
        "mul.bf16x2 x8, x8, rl;\n"
        "mul.bf16x2 x9, x9, rl;\n"
        "mul.bf16x2 x10, x10, rh;\n"
        "mul.bf16x2 x11, x11, rh;\n"
        "mma.sync.aligned.m16n8k16.row.col.f32.bf16.bf16.f32 {%16,%17,%18,%19}, {a0,a1,a2,a3}, {x8,x9}, {%16,%17,%18,%19};\n"
        "mma.sync.aligned.m16n8k16.row.col.f32.bf16.bf16.f32 {%20,%21,%22,%23}, {a0,a1,a2,a3}, {x10,x11}, {%20,%21,%22,%23};\n"
        "ld.shared.v4.u32 {x8,x9,x10,x11}, [xa+1280];\n"
        "mma.sync.aligned.m16n8k8.row.col.f32.bf16.bf16.f32 {d0,d1,d2,d3}, {%179,%180}, {m1}, {fz,fz,fz,fz};\n"
        "cvt.rn.bf16x2.f32 b2, d2, d0;\n"
        "cvt.rn.bf16x2.f32 b3, d3, d1;\n"
        "tanh.approx.f32 t0, p9;\n"
        "tanh.approx.f32 t1, p11;\n"
        "fma.rn.f32 t0, p9, t0, p9;\n"
        "fma.rn.f32 t1, p11, t1, p11;\n"
        "cvt.rn.bf16x2.f32 r2, t1, t0;\n"
        "mma.sync.aligned.m16n8k16.row.col.f32.bf16.bf16.f32 {p8,p9,p10,p11}, {%169,%170,%171,%172}, {m2,m3}, {fz,fz,fz,fz};\n"
        "selp.u32 tq, lb, 5, w;\n"
        "mov.b32 {lo,hi}, r3;\n"
        "mov.b32 rl, {lo,lo};\n"
        "mov.b32 rh, {hi,hi};\n"
        "mul.bf16x2 x12, x12, rl;\n"
        "mul.bf16x2 x13, x13, rl;\n"
        "mul.bf16x2 x14, x14, rh;\n"
        "mul.bf16x2 x15, x15, rh;\n"
        "mma.sync.aligned.m16n8k16.row.col.f32.bf16.bf16.f32 {%24,%25,%26,%27}, {a0,a1,a2,a3}, {x12,x13}, {%24,%25,%26,%27};\n"
        "mma.sync.aligned.m16n8k16.row.col.f32.bf16.bf16.f32 {%28,%29,%30,%31}, {a0,a1,a2,a3}, {x14,x15}, {%28,%29,%30,%31};\n"
        "ld.shared.v4.u32 {x12,x13,x14,x15}, [xa+1408];\n"
        "@el mbarrier.arrive.shared.b64 _, [k0+8712];\n"
        "redux.sync.or.b32 ln, tag, 0xffffffff;\n"
        "mov.u32 sa, sn;\n"
        "add.u32 k0, sn, zz;\n"
        "tanh.approx.f32 t0, p13;\n"
        "tanh.approx.f32 t1, p15;\n"
        "fma.rn.f32 t0, p13, t0, p13;\n"
        "fma.rn.f32 t1, p15, t1, p15;\n"
        "cvt.rn.bf16x2.f32 r3, t1, t0;\n"
        "mma.sync.aligned.m16n8k16.row.col.f32.bf16.bf16.f32 {p12,p13,p14,p15}, {%173,%174,%175,%176}, {m2,m3}, {fz,fz,fz,fz};\n"
        "mov.b32 {lo,hi}, r0;\n"
        "mov.b32 rl, {lo,lo};\n"
        "mov.b32 rh, {hi,hi};\n"
        "mul.bf16x2 x0, x0, rl;\n"
        "mul.bf16x2 x1, x1, rl;\n"
        "mul.bf16x2 x2, x2, rh;\n"
        "mul.bf16x2 x3, x3, rh;\n"
        "mov.b32 {lo,hi}, r1;\n"
        "mov.b32 rl, {lo,lo};\n"
        "mov.b32 rh, {hi,hi};\n"
        "mul.bf16x2 x4, x4, rl;\n"
        "mul.bf16x2 x5, x5, rl;\n"
        "mul.bf16x2 x6, x6, rh;\n"
        "mul.bf16x2 x7, x7, rh;\n"
        "brx.idx.uni tq, TB_%=;\n"
        "A1_%=:\n"
        "add.u32 xa, sa, %181;\n"
        "add.u32 ma, sa, %182;\n"
        "ldmatrix.sync.aligned.m8n8.x4.shared.b16 {m0,m1,m2,m3}, [ma];\n"
        "ld.shared.u16 tag, [tp+48];\n"
        "add.u32 tp, tp, 52;\n"
        "add.u32 sn, sa, 8832;\n"
        "setp.eq.u32 q, sa, last;\n"
        "selp.u32 sn, ring, sn, q;\n"
        "selp.u32 tq, 1, 0, q;\n"
        "xor.b32 ph, ph, tq;\n"
        "mbarrier.test_wait.parity.shared.b64 w, [sn+8704], ph;\n"
        "mma.sync.aligned.m16n8k16.row.col.f32.bf16.bf16.f32 {%32,%33,%34,%35}, {a0,a1,a2,a3}, {x0,x1}, {%32,%33,%34,%35};\n"
        "mma.sync.aligned.m16n8k16.row.col.f32.bf16.bf16.f32 {%36,%37,%38,%39}, {a0,a1,a2,a3}, {x2,x3}, {%36,%37,%38,%39};\n"
        "ld.shared.v4.u32 {x0,x1,x2,x3}, [xa+1024];\n"
        "tanh.approx.f32 t0, p1;\n"
        "tanh.approx.f32 t1, p3;\n"
        "fma.rn.f32 t0, p1, t0, p1;\n"
        "fma.rn.f32 t1, p3, t1, p3;\n"
        "cvt.rn.bf16x2.f32 r0, t1, t0;\n"
        "mma.sync.aligned.m16n8k16.row.col.f32.bf16.bf16.f32 {p0,p1,p2,p3}, {%161,%162,%163,%164}, {m2,m3}, {fz,fz,fz,fz};\n"
        "mma.sync.aligned.m16n8k16.row.col.f32.bf16.bf16.f32 {%40,%41,%42,%43}, {a0,a1,a2,a3}, {x4,x5}, {%40,%41,%42,%43};\n"
        "mma.sync.aligned.m16n8k16.row.col.f32.bf16.bf16.f32 {%44,%45,%46,%47}, {a0,a1,a2,a3}, {x6,x7}, {%44,%45,%46,%47};\n"
        "ld.shared.v4.u32 {x4,x5,x6,x7}, [xa+1152];\n"
        "mma.sync.aligned.m16n8k8.row.col.f32.bf16.bf16.f32 {d0,d1,d2,d3}, {%177,%178}, {m1}, {fz,fz,fz,fz};\n"
        "cvt.rn.bf16x2.f32 b0, d2, d0;\n"
        "cvt.rn.bf16x2.f32 b1, d3, d1;\n"
        "tanh.approx.f32 t0, p5;\n"
        "tanh.approx.f32 t1, p7;\n"
        "fma.rn.f32 t0, p5, t0, p5;\n"
        "fma.rn.f32 t1, p7, t1, p7;\n"
        "cvt.rn.bf16x2.f32 r1, t1, t0;\n"
        "mma.sync.aligned.m16n8k16.row.col.f32.bf16.bf16.f32 {p4,p5,p6,p7}, {%165,%166,%167,%168}, {m2,m3}, {fz,fz,fz,fz};\n"
        "mov.b32 {lo,hi}, r2;\n"
        "mov.b32 rl, {lo,lo};\n"
        "mov.b32 rh, {hi,hi};\n"
        "mul.bf16x2 x8, x8, rl;\n"
        "mul.bf16x2 x9, x9, rl;\n"
        "mul.bf16x2 x10, x10, rh;\n"
        "mul.bf16x2 x11, x11, rh;\n"
        "mma.sync.aligned.m16n8k16.row.col.f32.bf16.bf16.f32 {%48,%49,%50,%51}, {a0,a1,a2,a3}, {x8,x9}, {%48,%49,%50,%51};\n"
        "mma.sync.aligned.m16n8k16.row.col.f32.bf16.bf16.f32 {%52,%53,%54,%55}, {a0,a1,a2,a3}, {x10,x11}, {%52,%53,%54,%55};\n"
        "ld.shared.v4.u32 {x8,x9,x10,x11}, [xa+1280];\n"
        "mma.sync.aligned.m16n8k8.row.col.f32.bf16.bf16.f32 {d0,d1,d2,d3}, {%179,%180}, {m1}, {fz,fz,fz,fz};\n"
        "cvt.rn.bf16x2.f32 b2, d2, d0;\n"
        "cvt.rn.bf16x2.f32 b3, d3, d1;\n"
        "tanh.approx.f32 t0, p9;\n"
        "tanh.approx.f32 t1, p11;\n"
        "fma.rn.f32 t0, p9, t0, p9;\n"
        "fma.rn.f32 t1, p11, t1, p11;\n"
        "cvt.rn.bf16x2.f32 r2, t1, t0;\n"
        "mma.sync.aligned.m16n8k16.row.col.f32.bf16.bf16.f32 {p8,p9,p10,p11}, {%169,%170,%171,%172}, {m2,m3}, {fz,fz,fz,fz};\n"
        "selp.u32 tq, lb, 5, w;\n"
        "mov.b32 {lo,hi}, r3;\n"
        "mov.b32 rl, {lo,lo};\n"
        "mov.b32 rh, {hi,hi};\n"
        "mul.bf16x2 x12, x12, rl;\n"
        "mul.bf16x2 x13, x13, rl;\n"
        "mul.bf16x2 x14, x14, rh;\n"
        "mul.bf16x2 x15, x15, rh;\n"
        "mma.sync.aligned.m16n8k16.row.col.f32.bf16.bf16.f32 {%56,%57,%58,%59}, {a0,a1,a2,a3}, {x12,x13}, {%56,%57,%58,%59};\n"
        "mma.sync.aligned.m16n8k16.row.col.f32.bf16.bf16.f32 {%60,%61,%62,%63}, {a0,a1,a2,a3}, {x14,x15}, {%60,%61,%62,%63};\n"
        "ld.shared.v4.u32 {x12,x13,x14,x15}, [xa+1408];\n"
        "@el mbarrier.arrive.shared.b64 _, [k0+8712];\n"
        "redux.sync.or.b32 ln, tag, 0xffffffff;\n"
        "mov.u32 sa, sn;\n"
        "add.u32 k0, sn, zz;\n"
        "tanh.approx.f32 t0, p13;\n"
        "tanh.approx.f32 t1, p15;\n"
        "fma.rn.f32 t0, p13, t0, p13;\n"
        "fma.rn.f32 t1, p15, t1, p15;\n"
        "cvt.rn.bf16x2.f32 r3, t1, t0;\n"
        "mma.sync.aligned.m16n8k16.row.col.f32.bf16.bf16.f32 {p12,p13,p14,p15}, {%173,%174,%175,%176}, {m2,m3}, {fz,fz,fz,fz};\n"
        "mov.b32 {lo,hi}, r0;\n"
        "mov.b32 rl, {lo,lo};\n"
        "mov.b32 rh, {hi,hi};\n"
        "mul.bf16x2 x0, x0, rl;\n"
        "mul.bf16x2 x1, x1, rl;\n"
        "mul.bf16x2 x2, x2, rh;\n"
        "mul.bf16x2 x3, x3, rh;\n"
        "mov.b32 {lo,hi}, r1;\n"
        "mov.b32 rl, {lo,lo};\n"
        "mov.b32 rh, {hi,hi};\n"
        "mul.bf16x2 x4, x4, rl;\n"
        "mul.bf16x2 x5, x5, rl;\n"
        "mul.bf16x2 x6, x6, rh;\n"
        "mul.bf16x2 x7, x7, rh;\n"
        "brx.idx.uni tq, TB_%=;\n"
        "A2_%=:\n"
        "add.u32 xa, sa, %181;\n"
        "add.u32 ma, sa, %182;\n"
        "ldmatrix.sync.aligned.m8n8.x4.shared.b16 {m0,m1,m2,m3}, [ma];\n"
        "ld.shared.u16 tag, [tp+48];\n"
        "add.u32 tp, tp, 52;\n"
        "add.u32 sn, sa, 8832;\n"
        "setp.eq.u32 q, sa, last;\n"
        "selp.u32 sn, ring, sn, q;\n"
        "selp.u32 tq, 1, 0, q;\n"
        "xor.b32 ph, ph, tq;\n"
        "mbarrier.test_wait.parity.shared.b64 w, [sn+8704], ph;\n"
        "mma.sync.aligned.m16n8k16.row.col.f32.bf16.bf16.f32 {%64,%65,%66,%67}, {a0,a1,a2,a3}, {x0,x1}, {%64,%65,%66,%67};\n"
        "mma.sync.aligned.m16n8k16.row.col.f32.bf16.bf16.f32 {%68,%69,%70,%71}, {a0,a1,a2,a3}, {x2,x3}, {%68,%69,%70,%71};\n"
        "ld.shared.v4.u32 {x0,x1,x2,x3}, [xa+1024];\n"
        "tanh.approx.f32 t0, p1;\n"
        "tanh.approx.f32 t1, p3;\n"
        "fma.rn.f32 t0, p1, t0, p1;\n"
        "fma.rn.f32 t1, p3, t1, p3;\n"
        "cvt.rn.bf16x2.f32 r0, t1, t0;\n"
        "mma.sync.aligned.m16n8k16.row.col.f32.bf16.bf16.f32 {p0,p1,p2,p3}, {%161,%162,%163,%164}, {m2,m3}, {fz,fz,fz,fz};\n"
        "mma.sync.aligned.m16n8k16.row.col.f32.bf16.bf16.f32 {%72,%73,%74,%75}, {a0,a1,a2,a3}, {x4,x5}, {%72,%73,%74,%75};\n"
        "mma.sync.aligned.m16n8k16.row.col.f32.bf16.bf16.f32 {%76,%77,%78,%79}, {a0,a1,a2,a3}, {x6,x7}, {%76,%77,%78,%79};\n"
        "ld.shared.v4.u32 {x4,x5,x6,x7}, [xa+1152];\n"
        "mma.sync.aligned.m16n8k8.row.col.f32.bf16.bf16.f32 {d0,d1,d2,d3}, {%177,%178}, {m1}, {fz,fz,fz,fz};\n"
        "cvt.rn.bf16x2.f32 b0, d2, d0;\n"
        "cvt.rn.bf16x2.f32 b1, d3, d1;\n"
        "tanh.approx.f32 t0, p5;\n"
        "tanh.approx.f32 t1, p7;\n"
        "fma.rn.f32 t0, p5, t0, p5;\n"
        "fma.rn.f32 t1, p7, t1, p7;\n"
        "cvt.rn.bf16x2.f32 r1, t1, t0;\n"
        "mma.sync.aligned.m16n8k16.row.col.f32.bf16.bf16.f32 {p4,p5,p6,p7}, {%165,%166,%167,%168}, {m2,m3}, {fz,fz,fz,fz};\n"
        "mov.b32 {lo,hi}, r2;\n"
        "mov.b32 rl, {lo,lo};\n"
        "mov.b32 rh, {hi,hi};\n"
        "mul.bf16x2 x8, x8, rl;\n"
        "mul.bf16x2 x9, x9, rl;\n"
        "mul.bf16x2 x10, x10, rh;\n"
        "mul.bf16x2 x11, x11, rh;\n"
        "mma.sync.aligned.m16n8k16.row.col.f32.bf16.bf16.f32 {%80,%81,%82,%83}, {a0,a1,a2,a3}, {x8,x9}, {%80,%81,%82,%83};\n"
        "mma.sync.aligned.m16n8k16.row.col.f32.bf16.bf16.f32 {%84,%85,%86,%87}, {a0,a1,a2,a3}, {x10,x11}, {%84,%85,%86,%87};\n"
        "ld.shared.v4.u32 {x8,x9,x10,x11}, [xa+1280];\n"
        "mma.sync.aligned.m16n8k8.row.col.f32.bf16.bf16.f32 {d0,d1,d2,d3}, {%179,%180}, {m1}, {fz,fz,fz,fz};\n"
        "cvt.rn.bf16x2.f32 b2, d2, d0;\n"
        "cvt.rn.bf16x2.f32 b3, d3, d1;\n"
        "tanh.approx.f32 t0, p9;\n"
        "tanh.approx.f32 t1, p11;\n"
        "fma.rn.f32 t0, p9, t0, p9;\n"
        "fma.rn.f32 t1, p11, t1, p11;\n"
        "cvt.rn.bf16x2.f32 r2, t1, t0;\n"
        "mma.sync.aligned.m16n8k16.row.col.f32.bf16.bf16.f32 {p8,p9,p10,p11}, {%169,%170,%171,%172}, {m2,m3}, {fz,fz,fz,fz};\n"
        "selp.u32 tq, lb, 5, w;\n"
        "mov.b32 {lo,hi}, r3;\n"
        "mov.b32 rl, {lo,lo};\n"
        "mov.b32 rh, {hi,hi};\n"
        "mul.bf16x2 x12, x12, rl;\n"
        "mul.bf16x2 x13, x13, rl;\n"
        "mul.bf16x2 x14, x14, rh;\n"
        "mul.bf16x2 x15, x15, rh;\n"
        "mma.sync.aligned.m16n8k16.row.col.f32.bf16.bf16.f32 {%88,%89,%90,%91}, {a0,a1,a2,a3}, {x12,x13}, {%88,%89,%90,%91};\n"
        "mma.sync.aligned.m16n8k16.row.col.f32.bf16.bf16.f32 {%92,%93,%94,%95}, {a0,a1,a2,a3}, {x14,x15}, {%92,%93,%94,%95};\n"
        "ld.shared.v4.u32 {x12,x13,x14,x15}, [xa+1408];\n"
        "@el mbarrier.arrive.shared.b64 _, [k0+8712];\n"
        "redux.sync.or.b32 ln, tag, 0xffffffff;\n"
        "mov.u32 sa, sn;\n"
        "add.u32 k0, sn, zz;\n"
        "tanh.approx.f32 t0, p13;\n"
        "tanh.approx.f32 t1, p15;\n"
        "fma.rn.f32 t0, p13, t0, p13;\n"
        "fma.rn.f32 t1, p15, t1, p15;\n"
        "cvt.rn.bf16x2.f32 r3, t1, t0;\n"
        "mma.sync.aligned.m16n8k16.row.col.f32.bf16.bf16.f32 {p12,p13,p14,p15}, {%173,%174,%175,%176}, {m2,m3}, {fz,fz,fz,fz};\n"
        "mov.b32 {lo,hi}, r0;\n"
        "mov.b32 rl, {lo,lo};\n"
        "mov.b32 rh, {hi,hi};\n"
        "mul.bf16x2 x0, x0, rl;\n"
        "mul.bf16x2 x1, x1, rl;\n"
        "mul.bf16x2 x2, x2, rh;\n"
        "mul.bf16x2 x3, x3, rh;\n"
        "mov.b32 {lo,hi}, r1;\n"
        "mov.b32 rl, {lo,lo};\n"
        "mov.b32 rh, {hi,hi};\n"
        "mul.bf16x2 x4, x4, rl;\n"
        "mul.bf16x2 x5, x5, rl;\n"
        "mul.bf16x2 x6, x6, rh;\n"
        "mul.bf16x2 x7, x7, rh;\n"
        "brx.idx.uni tq, TB_%=;\n"
        "A3_%=:\n"
        "add.u32 xa, sa, %181;\n"
        "add.u32 ma, sa, %182;\n"
        "ldmatrix.sync.aligned.m8n8.x4.shared.b16 {m0,m1,m2,m3}, [ma];\n"
        "ld.shared.u16 tag, [tp+48];\n"
        "add.u32 tp, tp, 52;\n"
        "add.u32 sn, sa, 8832;\n"
        "setp.eq.u32 q, sa, last;\n"
        "selp.u32 sn, ring, sn, q;\n"
        "selp.u32 tq, 1, 0, q;\n"
        "xor.b32 ph, ph, tq;\n"
        "mbarrier.test_wait.parity.shared.b64 w, [sn+8704], ph;\n"
        "mma.sync.aligned.m16n8k16.row.col.f32.bf16.bf16.f32 {%96,%97,%98,%99}, {a0,a1,a2,a3}, {x0,x1}, {%96,%97,%98,%99};\n"
        "mma.sync.aligned.m16n8k16.row.col.f32.bf16.bf16.f32 {%100,%101,%102,%103}, {a0,a1,a2,a3}, {x2,x3}, {%100,%101,%102,%103};\n"
        "ld.shared.v4.u32 {x0,x1,x2,x3}, [xa+1024];\n"
        "tanh.approx.f32 t0, p1;\n"
        "tanh.approx.f32 t1, p3;\n"
        "fma.rn.f32 t0, p1, t0, p1;\n"
        "fma.rn.f32 t1, p3, t1, p3;\n"
        "cvt.rn.bf16x2.f32 r0, t1, t0;\n"
        "mma.sync.aligned.m16n8k16.row.col.f32.bf16.bf16.f32 {p0,p1,p2,p3}, {%161,%162,%163,%164}, {m2,m3}, {fz,fz,fz,fz};\n"
        "mma.sync.aligned.m16n8k16.row.col.f32.bf16.bf16.f32 {%104,%105,%106,%107}, {a0,a1,a2,a3}, {x4,x5}, {%104,%105,%106,%107};\n"
        "mma.sync.aligned.m16n8k16.row.col.f32.bf16.bf16.f32 {%108,%109,%110,%111}, {a0,a1,a2,a3}, {x6,x7}, {%108,%109,%110,%111};\n"
        "ld.shared.v4.u32 {x4,x5,x6,x7}, [xa+1152];\n"
        "mma.sync.aligned.m16n8k8.row.col.f32.bf16.bf16.f32 {d0,d1,d2,d3}, {%177,%178}, {m1}, {fz,fz,fz,fz};\n"
        "cvt.rn.bf16x2.f32 b0, d2, d0;\n"
        "cvt.rn.bf16x2.f32 b1, d3, d1;\n"
        "tanh.approx.f32 t0, p5;\n"
        "tanh.approx.f32 t1, p7;\n"
        "fma.rn.f32 t0, p5, t0, p5;\n"
        "fma.rn.f32 t1, p7, t1, p7;\n"
        "cvt.rn.bf16x2.f32 r1, t1, t0;\n"
        "mma.sync.aligned.m16n8k16.row.col.f32.bf16.bf16.f32 {p4,p5,p6,p7}, {%165,%166,%167,%168}, {m2,m3}, {fz,fz,fz,fz};\n"
        "mov.b32 {lo,hi}, r2;\n"
        "mov.b32 rl, {lo,lo};\n"
        "mov.b32 rh, {hi,hi};\n"
        "mul.bf16x2 x8, x8, rl;\n"
        "mul.bf16x2 x9, x9, rl;\n"
        "mul.bf16x2 x10, x10, rh;\n"
        "mul.bf16x2 x11, x11, rh;\n"
        "mma.sync.aligned.m16n8k16.row.col.f32.bf16.bf16.f32 {%112,%113,%114,%115}, {a0,a1,a2,a3}, {x8,x9}, {%112,%113,%114,%115};\n"
        "mma.sync.aligned.m16n8k16.row.col.f32.bf16.bf16.f32 {%116,%117,%118,%119}, {a0,a1,a2,a3}, {x10,x11}, {%116,%117,%118,%119};\n"
        "ld.shared.v4.u32 {x8,x9,x10,x11}, [xa+1280];\n"
        "mma.sync.aligned.m16n8k8.row.col.f32.bf16.bf16.f32 {d0,d1,d2,d3}, {%179,%180}, {m1}, {fz,fz,fz,fz};\n"
        "cvt.rn.bf16x2.f32 b2, d2, d0;\n"
        "cvt.rn.bf16x2.f32 b3, d3, d1;\n"
        "tanh.approx.f32 t0, p9;\n"
        "tanh.approx.f32 t1, p11;\n"
        "fma.rn.f32 t0, p9, t0, p9;\n"
        "fma.rn.f32 t1, p11, t1, p11;\n"
        "cvt.rn.bf16x2.f32 r2, t1, t0;\n"
        "mma.sync.aligned.m16n8k16.row.col.f32.bf16.bf16.f32 {p8,p9,p10,p11}, {%169,%170,%171,%172}, {m2,m3}, {fz,fz,fz,fz};\n"
        "selp.u32 tq, lb, 5, w;\n"
        "mov.b32 {lo,hi}, r3;\n"
        "mov.b32 rl, {lo,lo};\n"
        "mov.b32 rh, {hi,hi};\n"
        "mul.bf16x2 x12, x12, rl;\n"
        "mul.bf16x2 x13, x13, rl;\n"
        "mul.bf16x2 x14, x14, rh;\n"
        "mul.bf16x2 x15, x15, rh;\n"
        "mma.sync.aligned.m16n8k16.row.col.f32.bf16.bf16.f32 {%120,%121,%122,%123}, {a0,a1,a2,a3}, {x12,x13}, {%120,%121,%122,%123};\n"
        "mma.sync.aligned.m16n8k16.row.col.f32.bf16.bf16.f32 {%124,%125,%126,%127}, {a0,a1,a2,a3}, {x14,x15}, {%124,%125,%126,%127};\n"
        "ld.shared.v4.u32 {x12,x13,x14,x15}, [xa+1408];\n"
        "@el mbarrier.arrive.shared.b64 _, [k0+8712];\n"
        "redux.sync.or.b32 ln, tag, 0xffffffff;\n"
        "mov.u32 sa, sn;\n"
        "add.u32 k0, sn, zz;\n"
        "tanh.approx.f32 t0, p13;\n"
        "tanh.approx.f32 t1, p15;\n"
        "fma.rn.f32 t0, p13, t0, p13;\n"
        "fma.rn.f32 t1, p15, t1, p15;\n"
        "cvt.rn.bf16x2.f32 r3, t1, t0;\n"
        "mma.sync.aligned.m16n8k16.row.col.f32.bf16.bf16.f32 {p12,p13,p14,p15}, {%173,%174,%175,%176}, {m2,m3}, {fz,fz,fz,fz};\n"
        "mov.b32 {lo,hi}, r0;\n"
        "mov.b32 rl, {lo,lo};\n"
        "mov.b32 rh, {hi,hi};\n"
        "mul.bf16x2 x0, x0, rl;\n"
        "mul.bf16x2 x1, x1, rl;\n"
        "mul.bf16x2 x2, x2, rh;\n"
        "mul.bf16x2 x3, x3, rh;\n"
        "mov.b32 {lo,hi}, r1;\n"
        "mov.b32 rl, {lo,lo};\n"
        "mov.b32 rh, {hi,hi};\n"
        "mul.bf16x2 x4, x4, rl;\n"
        "mul.bf16x2 x5, x5, rl;\n"
        "mul.bf16x2 x6, x6, rh;\n"
        "mul.bf16x2 x7, x7, rh;\n"
        "brx.idx.uni tq, TB_%=;\n"
        "A4_%=:\n"
        "add.u32 xa, sa, %181;\n"
        "add.u32 ma, sa, %182;\n"
        "ldmatrix.sync.aligned.m8n8.x4.shared.b16 {m0,m1,m2,m3}, [ma];\n"
        "ld.shared.u16 tag, [tp+48];\n"
        "add.u32 tp, tp, 52;\n"
        "add.u32 sn, sa, 8832;\n"
        "setp.eq.u32 q, sa, last;\n"
        "selp.u32 sn, ring, sn, q;\n"
        "selp.u32 tq, 1, 0, q;\n"
        "xor.b32 ph, ph, tq;\n"
        "mbarrier.test_wait.parity.shared.b64 w, [sn+8704], ph;\n"
        "mma.sync.aligned.m16n8k16.row.col.f32.bf16.bf16.f32 {%128,%129,%130,%131}, {a0,a1,a2,a3}, {x0,x1}, {%128,%129,%130,%131};\n"
        "mma.sync.aligned.m16n8k16.row.col.f32.bf16.bf16.f32 {%132,%133,%134,%135}, {a0,a1,a2,a3}, {x2,x3}, {%132,%133,%134,%135};\n"
        "ld.shared.v4.u32 {x0,x1,x2,x3}, [xa+1024];\n"
        "tanh.approx.f32 t0, p1;\n"
        "tanh.approx.f32 t1, p3;\n"
        "fma.rn.f32 t0, p1, t0, p1;\n"
        "fma.rn.f32 t1, p3, t1, p3;\n"
        "cvt.rn.bf16x2.f32 r0, t1, t0;\n"
        "mma.sync.aligned.m16n8k16.row.col.f32.bf16.bf16.f32 {p0,p1,p2,p3}, {%161,%162,%163,%164}, {m2,m3}, {fz,fz,fz,fz};\n"
        "mma.sync.aligned.m16n8k16.row.col.f32.bf16.bf16.f32 {%136,%137,%138,%139}, {a0,a1,a2,a3}, {x4,x5}, {%136,%137,%138,%139};\n"
        "mma.sync.aligned.m16n8k16.row.col.f32.bf16.bf16.f32 {%140,%141,%142,%143}, {a0,a1,a2,a3}, {x6,x7}, {%140,%141,%142,%143};\n"
        "ld.shared.v4.u32 {x4,x5,x6,x7}, [xa+1152];\n"
        "mma.sync.aligned.m16n8k8.row.col.f32.bf16.bf16.f32 {d0,d1,d2,d3}, {%177,%178}, {m1}, {fz,fz,fz,fz};\n"
        "cvt.rn.bf16x2.f32 b0, d2, d0;\n"
        "cvt.rn.bf16x2.f32 b1, d3, d1;\n"
        "tanh.approx.f32 t0, p5;\n"
        "tanh.approx.f32 t1, p7;\n"
        "fma.rn.f32 t0, p5, t0, p5;\n"
        "fma.rn.f32 t1, p7, t1, p7;\n"
        "cvt.rn.bf16x2.f32 r1, t1, t0;\n"
        "mma.sync.aligned.m16n8k16.row.col.f32.bf16.bf16.f32 {p4,p5,p6,p7}, {%165,%166,%167,%168}, {m2,m3}, {fz,fz,fz,fz};\n"
        "mov.b32 {lo,hi}, r2;\n"
        "mov.b32 rl, {lo,lo};\n"
        "mov.b32 rh, {hi,hi};\n"
        "mul.bf16x2 x8, x8, rl;\n"
        "mul.bf16x2 x9, x9, rl;\n"
        "mul.bf16x2 x10, x10, rh;\n"
        "mul.bf16x2 x11, x11, rh;\n"
        "mma.sync.aligned.m16n8k16.row.col.f32.bf16.bf16.f32 {%144,%145,%146,%147}, {a0,a1,a2,a3}, {x8,x9}, {%144,%145,%146,%147};\n"
        "mma.sync.aligned.m16n8k16.row.col.f32.bf16.bf16.f32 {%148,%149,%150,%151}, {a0,a1,a2,a3}, {x10,x11}, {%148,%149,%150,%151};\n"
        "ld.shared.v4.u32 {x8,x9,x10,x11}, [xa+1280];\n"
        "mma.sync.aligned.m16n8k8.row.col.f32.bf16.bf16.f32 {d0,d1,d2,d3}, {%179,%180}, {m1}, {fz,fz,fz,fz};\n"
        "cvt.rn.bf16x2.f32 b2, d2, d0;\n"
        "cvt.rn.bf16x2.f32 b3, d3, d1;\n"
        "tanh.approx.f32 t0, p9;\n"
        "tanh.approx.f32 t1, p11;\n"
        "fma.rn.f32 t0, p9, t0, p9;\n"
        "fma.rn.f32 t1, p11, t1, p11;\n"
        "cvt.rn.bf16x2.f32 r2, t1, t0;\n"
        "mma.sync.aligned.m16n8k16.row.col.f32.bf16.bf16.f32 {p8,p9,p10,p11}, {%169,%170,%171,%172}, {m2,m3}, {fz,fz,fz,fz};\n"
        "selp.u32 tq, lb, 5, w;\n"
        "mov.b32 {lo,hi}, r3;\n"
        "mov.b32 rl, {lo,lo};\n"
        "mov.b32 rh, {hi,hi};\n"
        "mul.bf16x2 x12, x12, rl;\n"
        "mul.bf16x2 x13, x13, rl;\n"
        "mul.bf16x2 x14, x14, rh;\n"
        "mul.bf16x2 x15, x15, rh;\n"
        "mma.sync.aligned.m16n8k16.row.col.f32.bf16.bf16.f32 {%152,%153,%154,%155}, {a0,a1,a2,a3}, {x12,x13}, {%152,%153,%154,%155};\n"
        "mma.sync.aligned.m16n8k16.row.col.f32.bf16.bf16.f32 {%156,%157,%158,%159}, {a0,a1,a2,a3}, {x14,x15}, {%156,%157,%158,%159};\n"
        "ld.shared.v4.u32 {x12,x13,x14,x15}, [xa+1408];\n"
        "@el mbarrier.arrive.shared.b64 _, [k0+8712];\n"
        "redux.sync.or.b32 ln, tag, 0xffffffff;\n"
        "mov.u32 sa, sn;\n"
        "add.u32 k0, sn, zz;\n"
        "tanh.approx.f32 t0, p13;\n"
        "tanh.approx.f32 t1, p15;\n"
        "fma.rn.f32 t0, p13, t0, p13;\n"
        "fma.rn.f32 t1, p15, t1, p15;\n"
        "cvt.rn.bf16x2.f32 r3, t1, t0;\n"
        "mma.sync.aligned.m16n8k16.row.col.f32.bf16.bf16.f32 {p12,p13,p14,p15}, {%173,%174,%175,%176}, {m2,m3}, {fz,fz,fz,fz};\n"
        "mov.b32 {lo,hi}, r0;\n"
        "mov.b32 rl, {lo,lo};\n"
        "mov.b32 rh, {hi,hi};\n"
        "mul.bf16x2 x0, x0, rl;\n"
        "mul.bf16x2 x1, x1, rl;\n"
        "mul.bf16x2 x2, x2, rh;\n"
        "mul.bf16x2 x3, x3, rh;\n"
        "mov.b32 {lo,hi}, r1;\n"
        "mov.b32 rl, {lo,lo};\n"
        "mov.b32 rh, {hi,hi};\n"
        "mul.bf16x2 x4, x4, rl;\n"
        "mul.bf16x2 x5, x5, rl;\n"
        "mul.bf16x2 x6, x6, rh;\n"
        "mul.bf16x2 x7, x7, rh;\n"
        "brx.idx.uni tq, TB_%=;\n"
        "B0_%=:\n"
        "and.b32 la, ln, 255;\n"
        "shr.u32 lb, ln, 8;\n"
        "add.u32 ma, sa, %182;\n"
        "ldmatrix.sync.aligned.m8n8.x1.shared.b16 {yb}, [ma];\n"
        "add.u32 xa, sa, %181;\n"
        "mma.sync.aligned.m16n8k16.row.col.f32.bf16.bf16.f32 {%0,%1,%2,%3}, {b0,b1,b2,b3}, {x0,x1}, {%0,%1,%2,%3};\n"
        "mma.sync.aligned.m16n8k16.row.col.f32.bf16.bf16.f32 {%4,%5,%6,%7}, {b0,b1,b2,b3}, {x2,x3}, {%4,%5,%6,%7};\n"
        "ld.shared.v4.u32 {x0,x1,x2,x3}, [xa+0];\n"
        "tanh.approx.f32 t0, p0;\n"
        "tanh.approx.f32 t1, p2;\n"
        "fma.rn.f32 t0, p0, t0, p0;\n"
        "fma.rn.f32 t1, p2, t1, p2;\n"
        "cvt.rn.bf16x2.f32 r0, t1, t0;\n"
        "mma.sync.aligned.m16n8k16.row.col.f32.bf16.bf16.f32 {%8,%9,%10,%11}, {b0,b1,b2,b3}, {x4,x5}, {%8,%9,%10,%11};\n"
        "mma.sync.aligned.m16n8k16.row.col.f32.bf16.bf16.f32 {%12,%13,%14,%15}, {b0,b1,b2,b3}, {x6,x7}, {%12,%13,%14,%15};\n"
        "ld.shared.v4.u32 {x4,x5,x6,x7}, [xa+128];\n"
        "tanh.approx.f32 t0, p4;\n"
        "tanh.approx.f32 t1, p6;\n"
        "fma.rn.f32 t0, p4, t0, p4;\n"
        "fma.rn.f32 t1, p6, t1, p6;\n"
        "cvt.rn.bf16x2.f32 r1, t1, t0;\n"
        "mma.sync.aligned.m16n8k8.row.col.f32.bf16.bf16.f32 {d0,d1,d2,d3}, {%177,%178}, {yb}, {fz,fz,fz,fz};\n"
        "cvt.rn.bf16x2.f32 a0, d2, d0;\n"
        "cvt.rn.bf16x2.f32 a1, d3, d1;\n"
        "mov.b32 {lo,hi}, r2;\n"
        "mov.b32 rl, {lo,lo};\n"
        "mov.b32 rh, {hi,hi};\n"
        "mul.bf16x2 x8, x8, rl;\n"
        "mul.bf16x2 x9, x9, rl;\n"
        "mul.bf16x2 x10, x10, rh;\n"
        "mul.bf16x2 x11, x11, rh;\n"
        "mma.sync.aligned.m16n8k16.row.col.f32.bf16.bf16.f32 {%16,%17,%18,%19}, {b0,b1,b2,b3}, {x8,x9}, {%16,%17,%18,%19};\n"
        "mma.sync.aligned.m16n8k16.row.col.f32.bf16.bf16.f32 {%20,%21,%22,%23}, {b0,b1,b2,b3}, {x10,x11}, {%20,%21,%22,%23};\n"
        "ld.shared.v4.u32 {x8,x9,x10,x11}, [xa+256];\n"
        "tanh.approx.f32 t0, p8;\n"
        "tanh.approx.f32 t1, p10;\n"
        "fma.rn.f32 t0, p8, t0, p8;\n"
        "fma.rn.f32 t1, p10, t1, p10;\n"
        "cvt.rn.bf16x2.f32 r2, t1, t0;\n"
        "mma.sync.aligned.m16n8k8.row.col.f32.bf16.bf16.f32 {d0,d1,d2,d3}, {%179,%180}, {yb}, {fz,fz,fz,fz};\n"
        "cvt.rn.bf16x2.f32 a2, d2, d0;\n"
        "cvt.rn.bf16x2.f32 a3, d3, d1;\n"
        "mov.b32 {lo,hi}, r3;\n"
        "mov.b32 rl, {lo,lo};\n"
        "mov.b32 rh, {hi,hi};\n"
        "mul.bf16x2 x12, x12, rl;\n"
        "mul.bf16x2 x13, x13, rl;\n"
        "mul.bf16x2 x14, x14, rh;\n"
        "mul.bf16x2 x15, x15, rh;\n"
        "mma.sync.aligned.m16n8k16.row.col.f32.bf16.bf16.f32 {%24,%25,%26,%27}, {b0,b1,b2,b3}, {x12,x13}, {%24,%25,%26,%27};\n"
        "mma.sync.aligned.m16n8k16.row.col.f32.bf16.bf16.f32 {%28,%29,%30,%31}, {b0,b1,b2,b3}, {x14,x15}, {%28,%29,%30,%31};\n"
        "ld.shared.v4.u32 {x12,x13,x14,x15}, [xa+384];\n"
        "tanh.approx.f32 t0, p12;\n"
        "tanh.approx.f32 t1, p14;\n"
        "fma.rn.f32 t0, p12, t0, p12;\n"
        "fma.rn.f32 t1, p14, t1, p14;\n"
        "cvt.rn.bf16x2.f32 r3, t1, t0;\n"
        "mov.b32 {lo,hi}, r0;\n"
        "mov.b32 rl, {lo,lo};\n"
        "mov.b32 rh, {hi,hi};\n"
        "mul.bf16x2 x0, x0, rl;\n"
        "mul.bf16x2 x1, x1, rl;\n"
        "mul.bf16x2 x2, x2, rh;\n"
        "mul.bf16x2 x3, x3, rh;\n"
        "mov.b32 {lo,hi}, r1;\n"
        "mov.b32 rl, {lo,lo};\n"
        "mov.b32 rh, {hi,hi};\n"
        "mul.bf16x2 x4, x4, rl;\n"
        "mul.bf16x2 x5, x5, rl;\n"
        "mul.bf16x2 x6, x6, rh;\n"
        "mul.bf16x2 x7, x7, rh;\n"
        "brx.idx.uni la, TA_%=;\n"
        "B1_%=:\n"
        "and.b32 la, ln, 255;\n"
        "shr.u32 lb, ln, 8;\n"
        "add.u32 ma, sa, %182;\n"
        "ldmatrix.sync.aligned.m8n8.x1.shared.b16 {yb}, [ma];\n"
        "add.u32 xa, sa, %181;\n"
        "mma.sync.aligned.m16n8k16.row.col.f32.bf16.bf16.f32 {%32,%33,%34,%35}, {b0,b1,b2,b3}, {x0,x1}, {%32,%33,%34,%35};\n"
        "mma.sync.aligned.m16n8k16.row.col.f32.bf16.bf16.f32 {%36,%37,%38,%39}, {b0,b1,b2,b3}, {x2,x3}, {%36,%37,%38,%39};\n"
        "ld.shared.v4.u32 {x0,x1,x2,x3}, [xa+0];\n"
        "tanh.approx.f32 t0, p0;\n"
        "tanh.approx.f32 t1, p2;\n"
        "fma.rn.f32 t0, p0, t0, p0;\n"
        "fma.rn.f32 t1, p2, t1, p2;\n"
        "cvt.rn.bf16x2.f32 r0, t1, t0;\n"
        "mma.sync.aligned.m16n8k16.row.col.f32.bf16.bf16.f32 {%40,%41,%42,%43}, {b0,b1,b2,b3}, {x4,x5}, {%40,%41,%42,%43};\n"
        "mma.sync.aligned.m16n8k16.row.col.f32.bf16.bf16.f32 {%44,%45,%46,%47}, {b0,b1,b2,b3}, {x6,x7}, {%44,%45,%46,%47};\n"
        "ld.shared.v4.u32 {x4,x5,x6,x7}, [xa+128];\n"
        "tanh.approx.f32 t0, p4;\n"
        "tanh.approx.f32 t1, p6;\n"
        "fma.rn.f32 t0, p4, t0, p4;\n"
        "fma.rn.f32 t1, p6, t1, p6;\n"
        "cvt.rn.bf16x2.f32 r1, t1, t0;\n"
        "mma.sync.aligned.m16n8k8.row.col.f32.bf16.bf16.f32 {d0,d1,d2,d3}, {%177,%178}, {yb}, {fz,fz,fz,fz};\n"
        "cvt.rn.bf16x2.f32 a0, d2, d0;\n"
        "cvt.rn.bf16x2.f32 a1, d3, d1;\n"
        "mov.b32 {lo,hi}, r2;\n"
        "mov.b32 rl, {lo,lo};\n"
        "mov.b32 rh, {hi,hi};\n"
        "mul.bf16x2 x8, x8, rl;\n"
        "mul.bf16x2 x9, x9, rl;\n"
        "mul.bf16x2 x10, x10, rh;\n"
        "mul.bf16x2 x11, x11, rh;\n"
        "mma.sync.aligned.m16n8k16.row.col.f32.bf16.bf16.f32 {%48,%49,%50,%51}, {b0,b1,b2,b3}, {x8,x9}, {%48,%49,%50,%51};\n"
        "mma.sync.aligned.m16n8k16.row.col.f32.bf16.bf16.f32 {%52,%53,%54,%55}, {b0,b1,b2,b3}, {x10,x11}, {%52,%53,%54,%55};\n"
        "ld.shared.v4.u32 {x8,x9,x10,x11}, [xa+256];\n"
        "tanh.approx.f32 t0, p8;\n"
        "tanh.approx.f32 t1, p10;\n"
        "fma.rn.f32 t0, p8, t0, p8;\n"
        "fma.rn.f32 t1, p10, t1, p10;\n"
        "cvt.rn.bf16x2.f32 r2, t1, t0;\n"
        "mma.sync.aligned.m16n8k8.row.col.f32.bf16.bf16.f32 {d0,d1,d2,d3}, {%179,%180}, {yb}, {fz,fz,fz,fz};\n"
        "cvt.rn.bf16x2.f32 a2, d2, d0;\n"
        "cvt.rn.bf16x2.f32 a3, d3, d1;\n"
        "mov.b32 {lo,hi}, r3;\n"
        "mov.b32 rl, {lo,lo};\n"
        "mov.b32 rh, {hi,hi};\n"
        "mul.bf16x2 x12, x12, rl;\n"
        "mul.bf16x2 x13, x13, rl;\n"
        "mul.bf16x2 x14, x14, rh;\n"
        "mul.bf16x2 x15, x15, rh;\n"
        "mma.sync.aligned.m16n8k16.row.col.f32.bf16.bf16.f32 {%56,%57,%58,%59}, {b0,b1,b2,b3}, {x12,x13}, {%56,%57,%58,%59};\n"
        "mma.sync.aligned.m16n8k16.row.col.f32.bf16.bf16.f32 {%60,%61,%62,%63}, {b0,b1,b2,b3}, {x14,x15}, {%60,%61,%62,%63};\n"
        "ld.shared.v4.u32 {x12,x13,x14,x15}, [xa+384];\n"
        "tanh.approx.f32 t0, p12;\n"
        "tanh.approx.f32 t1, p14;\n"
        "fma.rn.f32 t0, p12, t0, p12;\n"
        "fma.rn.f32 t1, p14, t1, p14;\n"
        "cvt.rn.bf16x2.f32 r3, t1, t0;\n"
        "mov.b32 {lo,hi}, r0;\n"
        "mov.b32 rl, {lo,lo};\n"
        "mov.b32 rh, {hi,hi};\n"
        "mul.bf16x2 x0, x0, rl;\n"
        "mul.bf16x2 x1, x1, rl;\n"
        "mul.bf16x2 x2, x2, rh;\n"
        "mul.bf16x2 x3, x3, rh;\n"
        "mov.b32 {lo,hi}, r1;\n"
        "mov.b32 rl, {lo,lo};\n"
        "mov.b32 rh, {hi,hi};\n"
        "mul.bf16x2 x4, x4, rl;\n"
        "mul.bf16x2 x5, x5, rl;\n"
        "mul.bf16x2 x6, x6, rh;\n"
        "mul.bf16x2 x7, x7, rh;\n"
        "brx.idx.uni la, TA_%=;\n"
        "B2_%=:\n"
        "and.b32 la, ln, 255;\n"
        "shr.u32 lb, ln, 8;\n"
        "add.u32 ma, sa, %182;\n"
        "ldmatrix.sync.aligned.m8n8.x1.shared.b16 {yb}, [ma];\n"
        "add.u32 xa, sa, %181;\n"
        "mma.sync.aligned.m16n8k16.row.col.f32.bf16.bf16.f32 {%64,%65,%66,%67}, {b0,b1,b2,b3}, {x0,x1}, {%64,%65,%66,%67};\n"
        "mma.sync.aligned.m16n8k16.row.col.f32.bf16.bf16.f32 {%68,%69,%70,%71}, {b0,b1,b2,b3}, {x2,x3}, {%68,%69,%70,%71};\n"
        "ld.shared.v4.u32 {x0,x1,x2,x3}, [xa+0];\n"
        "tanh.approx.f32 t0, p0;\n"
        "tanh.approx.f32 t1, p2;\n"
        "fma.rn.f32 t0, p0, t0, p0;\n"
        "fma.rn.f32 t1, p2, t1, p2;\n"
        "cvt.rn.bf16x2.f32 r0, t1, t0;\n"
        "mma.sync.aligned.m16n8k16.row.col.f32.bf16.bf16.f32 {%72,%73,%74,%75}, {b0,b1,b2,b3}, {x4,x5}, {%72,%73,%74,%75};\n"
        "mma.sync.aligned.m16n8k16.row.col.f32.bf16.bf16.f32 {%76,%77,%78,%79}, {b0,b1,b2,b3}, {x6,x7}, {%76,%77,%78,%79};\n"
        "ld.shared.v4.u32 {x4,x5,x6,x7}, [xa+128];\n"
        "tanh.approx.f32 t0, p4;\n"
        "tanh.approx.f32 t1, p6;\n"
        "fma.rn.f32 t0, p4, t0, p4;\n"
        "fma.rn.f32 t1, p6, t1, p6;\n"
        "cvt.rn.bf16x2.f32 r1, t1, t0;\n"
        "mma.sync.aligned.m16n8k8.row.col.f32.bf16.bf16.f32 {d0,d1,d2,d3}, {%177,%178}, {yb}, {fz,fz,fz,fz};\n"
        "cvt.rn.bf16x2.f32 a0, d2, d0;\n"
        "cvt.rn.bf16x2.f32 a1, d3, d1;\n"
        "mov.b32 {lo,hi}, r2;\n"
        "mov.b32 rl, {lo,lo};\n"
        "mov.b32 rh, {hi,hi};\n"
        "mul.bf16x2 x8, x8, rl;\n"
        "mul.bf16x2 x9, x9, rl;\n"
        "mul.bf16x2 x10, x10, rh;\n"
        "mul.bf16x2 x11, x11, rh;\n"
        "mma.sync.aligned.m16n8k16.row.col.f32.bf16.bf16.f32 {%80,%81,%82,%83}, {b0,b1,b2,b3}, {x8,x9}, {%80,%81,%82,%83};\n"
        "mma.sync.aligned.m16n8k16.row.col.f32.bf16.bf16.f32 {%84,%85,%86,%87}, {b0,b1,b2,b3}, {x10,x11}, {%84,%85,%86,%87};\n"
        "ld.shared.v4.u32 {x8,x9,x10,x11}, [xa+256];\n"
        "tanh.approx.f32 t0, p8;\n"
        "tanh.approx.f32 t1, p10;\n"
        "fma.rn.f32 t0, p8, t0, p8;\n"
        "fma.rn.f32 t1, p10, t1, p10;\n"
        "cvt.rn.bf16x2.f32 r2, t1, t0;\n"
        "mma.sync.aligned.m16n8k8.row.col.f32.bf16.bf16.f32 {d0,d1,d2,d3}, {%179,%180}, {yb}, {fz,fz,fz,fz};\n"
        "cvt.rn.bf16x2.f32 a2, d2, d0;\n"
        "cvt.rn.bf16x2.f32 a3, d3, d1;\n"
        "mov.b32 {lo,hi}, r3;\n"
        "mov.b32 rl, {lo,lo};\n"
        "mov.b32 rh, {hi,hi};\n"
        "mul.bf16x2 x12, x12, rl;\n"
        "mul.bf16x2 x13, x13, rl;\n"
        "mul.bf16x2 x14, x14, rh;\n"
        "mul.bf16x2 x15, x15, rh;\n"
        "mma.sync.aligned.m16n8k16.row.col.f32.bf16.bf16.f32 {%88,%89,%90,%91}, {b0,b1,b2,b3}, {x12,x13}, {%88,%89,%90,%91};\n"
        "mma.sync.aligned.m16n8k16.row.col.f32.bf16.bf16.f32 {%92,%93,%94,%95}, {b0,b1,b2,b3}, {x14,x15}, {%92,%93,%94,%95};\n"
        "ld.shared.v4.u32 {x12,x13,x14,x15}, [xa+384];\n"
        "tanh.approx.f32 t0, p12;\n"
        "tanh.approx.f32 t1, p14;\n"
        "fma.rn.f32 t0, p12, t0, p12;\n"
        "fma.rn.f32 t1, p14, t1, p14;\n"
        "cvt.rn.bf16x2.f32 r3, t1, t0;\n"
        "mov.b32 {lo,hi}, r0;\n"
        "mov.b32 rl, {lo,lo};\n"
        "mov.b32 rh, {hi,hi};\n"
        "mul.bf16x2 x0, x0, rl;\n"
        "mul.bf16x2 x1, x1, rl;\n"
        "mul.bf16x2 x2, x2, rh;\n"
        "mul.bf16x2 x3, x3, rh;\n"
        "mov.b32 {lo,hi}, r1;\n"
        "mov.b32 rl, {lo,lo};\n"
        "mov.b32 rh, {hi,hi};\n"
        "mul.bf16x2 x4, x4, rl;\n"
        "mul.bf16x2 x5, x5, rl;\n"
        "mul.bf16x2 x6, x6, rh;\n"
        "mul.bf16x2 x7, x7, rh;\n"
        "brx.idx.uni la, TA_%=;\n"
        "B3_%=:\n"
        "and.b32 la, ln, 255;\n"
        "shr.u32 lb, ln, 8;\n"
        "add.u32 ma, sa, %182;\n"
        "ldmatrix.sync.aligned.m8n8.x1.shared.b16 {yb}, [ma];\n"
        "add.u32 xa, sa, %181;\n"
        "mma.sync.aligned.m16n8k16.row.col.f32.bf16.bf16.f32 {%96,%97,%98,%99}, {b0,b1,b2,b3}, {x0,x1}, {%96,%97,%98,%99};\n"
        "mma.sync.aligned.m16n8k16.row.col.f32.bf16.bf16.f32 {%100,%101,%102,%103}, {b0,b1,b2,b3}, {x2,x3}, {%100,%101,%102,%103};\n"
        "ld.shared.v4.u32 {x0,x1,x2,x3}, [xa+0];\n"
        "tanh.approx.f32 t0, p0;\n"
        "tanh.approx.f32 t1, p2;\n"
        "fma.rn.f32 t0, p0, t0, p0;\n"
        "fma.rn.f32 t1, p2, t1, p2;\n"
        "cvt.rn.bf16x2.f32 r0, t1, t0;\n"
        "mma.sync.aligned.m16n8k16.row.col.f32.bf16.bf16.f32 {%104,%105,%106,%107}, {b0,b1,b2,b3}, {x4,x5}, {%104,%105,%106,%107};\n"
        "mma.sync.aligned.m16n8k16.row.col.f32.bf16.bf16.f32 {%108,%109,%110,%111}, {b0,b1,b2,b3}, {x6,x7}, {%108,%109,%110,%111};\n"
        "ld.shared.v4.u32 {x4,x5,x6,x7}, [xa+128];\n"
        "tanh.approx.f32 t0, p4;\n"
        "tanh.approx.f32 t1, p6;\n"
        "fma.rn.f32 t0, p4, t0, p4;\n"
        "fma.rn.f32 t1, p6, t1, p6;\n"
        "cvt.rn.bf16x2.f32 r1, t1, t0;\n"
        "mma.sync.aligned.m16n8k8.row.col.f32.bf16.bf16.f32 {d0,d1,d2,d3}, {%177,%178}, {yb}, {fz,fz,fz,fz};\n"
        "cvt.rn.bf16x2.f32 a0, d2, d0;\n"
        "cvt.rn.bf16x2.f32 a1, d3, d1;\n"
        "mov.b32 {lo,hi}, r2;\n"
        "mov.b32 rl, {lo,lo};\n"
        "mov.b32 rh, {hi,hi};\n"
        "mul.bf16x2 x8, x8, rl;\n"
        "mul.bf16x2 x9, x9, rl;\n"
        "mul.bf16x2 x10, x10, rh;\n"
        "mul.bf16x2 x11, x11, rh;\n"
        "mma.sync.aligned.m16n8k16.row.col.f32.bf16.bf16.f32 {%112,%113,%114,%115}, {b0,b1,b2,b3}, {x8,x9}, {%112,%113,%114,%115};\n"
        "mma.sync.aligned.m16n8k16.row.col.f32.bf16.bf16.f32 {%116,%117,%118,%119}, {b0,b1,b2,b3}, {x10,x11}, {%116,%117,%118,%119};\n"
        "ld.shared.v4.u32 {x8,x9,x10,x11}, [xa+256];\n"
        "tanh.approx.f32 t0, p8;\n"
        "tanh.approx.f32 t1, p10;\n"
        "fma.rn.f32 t0, p8, t0, p8;\n"
        "fma.rn.f32 t1, p10, t1, p10;\n"
        "cvt.rn.bf16x2.f32 r2, t1, t0;\n"
        "mma.sync.aligned.m16n8k8.row.col.f32.bf16.bf16.f32 {d0,d1,d2,d3}, {%179,%180}, {yb}, {fz,fz,fz,fz};\n"
        "cvt.rn.bf16x2.f32 a2, d2, d0;\n"
        "cvt.rn.bf16x2.f32 a3, d3, d1;\n"
        "mov.b32 {lo,hi}, r3;\n"
        "mov.b32 rl, {lo,lo};\n"
        "mov.b32 rh, {hi,hi};\n"
        "mul.bf16x2 x12, x12, rl;\n"
        "mul.bf16x2 x13, x13, rl;\n"
        "mul.bf16x2 x14, x14, rh;\n"
        "mul.bf16x2 x15, x15, rh;\n"
        "mma.sync.aligned.m16n8k16.row.col.f32.bf16.bf16.f32 {%120,%121,%122,%123}, {b0,b1,b2,b3}, {x12,x13}, {%120,%121,%122,%123};\n"
        "mma.sync.aligned.m16n8k16.row.col.f32.bf16.bf16.f32 {%124,%125,%126,%127}, {b0,b1,b2,b3}, {x14,x15}, {%124,%125,%126,%127};\n"
        "ld.shared.v4.u32 {x12,x13,x14,x15}, [xa+384];\n"
        "tanh.approx.f32 t0, p12;\n"
        "tanh.approx.f32 t1, p14;\n"
        "fma.rn.f32 t0, p12, t0, p12;\n"
        "fma.rn.f32 t1, p14, t1, p14;\n"
        "cvt.rn.bf16x2.f32 r3, t1, t0;\n"
        "mov.b32 {lo,hi}, r0;\n"
        "mov.b32 rl, {lo,lo};\n"
        "mov.b32 rh, {hi,hi};\n"
        "mul.bf16x2 x0, x0, rl;\n"
        "mul.bf16x2 x1, x1, rl;\n"
        "mul.bf16x2 x2, x2, rh;\n"
        "mul.bf16x2 x3, x3, rh;\n"
        "mov.b32 {lo,hi}, r1;\n"
        "mov.b32 rl, {lo,lo};\n"
        "mov.b32 rh, {hi,hi};\n"
        "mul.bf16x2 x4, x4, rl;\n"
        "mul.bf16x2 x5, x5, rl;\n"
        "mul.bf16x2 x6, x6, rh;\n"
        "mul.bf16x2 x7, x7, rh;\n"
        "brx.idx.uni la, TA_%=;\n"
        "B4_%=:\n"
        "and.b32 la, ln, 255;\n"
        "shr.u32 lb, ln, 8;\n"
        "add.u32 ma, sa, %182;\n"
        "ldmatrix.sync.aligned.m8n8.x1.shared.b16 {yb}, [ma];\n"
        "add.u32 xa, sa, %181;\n"
        "mma.sync.aligned.m16n8k16.row.col.f32.bf16.bf16.f32 {%128,%129,%130,%131}, {b0,b1,b2,b3}, {x0,x1}, {%128,%129,%130,%131};\n"
        "mma.sync.aligned.m16n8k16.row.col.f32.bf16.bf16.f32 {%132,%133,%134,%135}, {b0,b1,b2,b3}, {x2,x3}, {%132,%133,%134,%135};\n"
        "ld.shared.v4.u32 {x0,x1,x2,x3}, [xa+0];\n"
        "tanh.approx.f32 t0, p0;\n"
        "tanh.approx.f32 t1, p2;\n"
        "fma.rn.f32 t0, p0, t0, p0;\n"
        "fma.rn.f32 t1, p2, t1, p2;\n"
        "cvt.rn.bf16x2.f32 r0, t1, t0;\n"
        "mma.sync.aligned.m16n8k16.row.col.f32.bf16.bf16.f32 {%136,%137,%138,%139}, {b0,b1,b2,b3}, {x4,x5}, {%136,%137,%138,%139};\n"
        "mma.sync.aligned.m16n8k16.row.col.f32.bf16.bf16.f32 {%140,%141,%142,%143}, {b0,b1,b2,b3}, {x6,x7}, {%140,%141,%142,%143};\n"
        "ld.shared.v4.u32 {x4,x5,x6,x7}, [xa+128];\n"
        "tanh.approx.f32 t0, p4;\n"
        "tanh.approx.f32 t1, p6;\n"
        "fma.rn.f32 t0, p4, t0, p4;\n"
        "fma.rn.f32 t1, p6, t1, p6;\n"
        "cvt.rn.bf16x2.f32 r1, t1, t0;\n"
        "mma.sync.aligned.m16n8k8.row.col.f32.bf16.bf16.f32 {d0,d1,d2,d3}, {%177,%178}, {yb}, {fz,fz,fz,fz};\n"
        "cvt.rn.bf16x2.f32 a0, d2, d0;\n"
        "cvt.rn.bf16x2.f32 a1, d3, d1;\n"
        "mov.b32 {lo,hi}, r2;\n"
        "mov.b32 rl, {lo,lo};\n"
        "mov.b32 rh, {hi,hi};\n"
        "mul.bf16x2 x8, x8, rl;\n"
        "mul.bf16x2 x9, x9, rl;\n"
        "mul.bf16x2 x10, x10, rh;\n"
        "mul.bf16x2 x11, x11, rh;\n"
        "mma.sync.aligned.m16n8k16.row.col.f32.bf16.bf16.f32 {%144,%145,%146,%147}, {b0,b1,b2,b3}, {x8,x9}, {%144,%145,%146,%147};\n"
        "mma.sync.aligned.m16n8k16.row.col.f32.bf16.bf16.f32 {%148,%149,%150,%151}, {b0,b1,b2,b3}, {x10,x11}, {%148,%149,%150,%151};\n"
        "ld.shared.v4.u32 {x8,x9,x10,x11}, [xa+256];\n"
        "tanh.approx.f32 t0, p8;\n"
        "tanh.approx.f32 t1, p10;\n"
        "fma.rn.f32 t0, p8, t0, p8;\n"
        "fma.rn.f32 t1, p10, t1, p10;\n"
        "cvt.rn.bf16x2.f32 r2, t1, t0;\n"
        "mma.sync.aligned.m16n8k8.row.col.f32.bf16.bf16.f32 {d0,d1,d2,d3}, {%179,%180}, {yb}, {fz,fz,fz,fz};\n"
        "cvt.rn.bf16x2.f32 a2, d2, d0;\n"
        "cvt.rn.bf16x2.f32 a3, d3, d1;\n"
        "mov.b32 {lo,hi}, r3;\n"
        "mov.b32 rl, {lo,lo};\n"
        "mov.b32 rh, {hi,hi};\n"
        "mul.bf16x2 x12, x12, rl;\n"
        "mul.bf16x2 x13, x13, rl;\n"
        "mul.bf16x2 x14, x14, rh;\n"
        "mul.bf16x2 x15, x15, rh;\n"
        "mma.sync.aligned.m16n8k16.row.col.f32.bf16.bf16.f32 {%152,%153,%154,%155}, {b0,b1,b2,b3}, {x12,x13}, {%152,%153,%154,%155};\n"
        "mma.sync.aligned.m16n8k16.row.col.f32.bf16.bf16.f32 {%156,%157,%158,%159}, {b0,b1,b2,b3}, {x14,x15}, {%156,%157,%158,%159};\n"
        "ld.shared.v4.u32 {x12,x13,x14,x15}, [xa+384];\n"
        "tanh.approx.f32 t0, p12;\n"
        "tanh.approx.f32 t1, p14;\n"
        "fma.rn.f32 t0, p12, t0, p12;\n"
        "fma.rn.f32 t1, p14, t1, p14;\n"
        "cvt.rn.bf16x2.f32 r3, t1, t0;\n"
        "mov.b32 {lo,hi}, r0;\n"
        "mov.b32 rl, {lo,lo};\n"
        "mov.b32 rh, {hi,hi};\n"
        "mul.bf16x2 x0, x0, rl;\n"
        "mul.bf16x2 x1, x1, rl;\n"
        "mul.bf16x2 x2, x2, rh;\n"
        "mul.bf16x2 x3, x3, rh;\n"
        "mov.b32 {lo,hi}, r1;\n"
        "mov.b32 rl, {lo,lo};\n"
        "mov.b32 rh, {hi,hi};\n"
        "mul.bf16x2 x4, x4, rl;\n"
        "mul.bf16x2 x5, x5, rl;\n"
        "mul.bf16x2 x6, x6, rh;\n"
        "mul.bf16x2 x7, x7, rh;\n"
        "brx.idx.uni la, TA_%=;\n"
        "EXIT_%=:\n"
        "mov.u32 %160, ring;\n"
        "}\n"
        : "+f"(acc[0][0][0][0]), "+f"(acc[0][0][0][1]), "+f"(acc[0][0][0][2]), "+f"(acc[0][0][0][3]), "+f"(acc[0][0][1][0]),
          "+f"(acc[0][0][1][1]), "+f"(acc[0][0][1][2]), "+f"(acc[0][0][1][3]), "+f"(acc[0][1][0][0]), "+f"(acc[0][1][0][1]),
          "+f"(acc[0][1][0][2]), "+f"(acc[0][1][0][3]), "+f"(acc[0][1][1][0]), "+f"(acc[0][1][1][1]), "+f"(acc[0][1][1][2]),
          "+f"(acc[0][1][1][3]), "+f"(acc[0][2][0][0]), "+f"(acc[0][2][0][1]), "+f"(acc[0][2][0][2]), "+f"(acc[0][2][0][3]),
          "+f"(acc[0][2][1][0]), "+f"(acc[0][2][1][1]), "+f"(acc[0][2][1][2]), "+f"(acc[0][2][1][3]), "+f"(acc[0][3][0][0]),
          "+f"(acc[0][3][0][1]), "+f"(acc[0][3][0][2]), "+f"(acc[0][3][0][3]), "+f"(acc[0][3][1][0]), "+f"(acc[0][3][1][1]),
          "+f"(acc[0][3][1][2]), "+f"(acc[0][3][1][3]), "+f"(acc[1][0][0][0]), "+f"(acc[1][0][0][1]), "+f"(acc[1][0][0][2]),
          "+f"(acc[1][0][0][3]), "+f"(acc[1][0][1][0]), "+f"(acc[1][0][1][1]), "+f"(acc[1][0][1][2]), "+f"(acc[1][0][1][3]),
          "+f"(acc[1][1][0][0]), "+f"(acc[1][1][0][1]), "+f"(acc[1][1][0][2]), "+f"(acc[1][1][0][3]), "+f"(acc[1][1][1][0]),
          "+f"(acc[1][1][1][1]), "+f"(acc[1][1][1][2]), "+f"(acc[1][1][1][3]), "+f"(acc[1][2][0][0]), "+f"(acc[1][2][0][1]),
          "+f"(acc[1][2][0][2]), "+f"(acc[1][2][0][3]), "+f"(acc[1][2][1][0]), "+f"(acc[1][2][1][1]), "+f"(acc[1][2][1][2]),
          "+f"(acc[1][2][1][3]), "+f"(acc[1][3][0][0]), "+f"(acc[1][3][0][1]), "+f"(acc[1][3][0][2]), "+f"(acc[1][3][0][3]),
          "+f"(acc[1][3][1][0]), "+f"(acc[1][3][1][1]), "+f"(acc[1][3][1][2]), "+f"(acc[1][3][1][3]), "+f"(acc[2][0][0][0]),
          "+f"(acc[2][0][0][1]), "+f"(acc[2][0][0][2]), "+f"(acc[2][0][0][3]), "+f"(acc[2][0][1][0]), "+f"(acc[2][0][1][1]),
          "+f"(acc[2][0][1][2]), "+f"(acc[2][0][1][3]), "+f"(acc[2][1][0][0]), "+f"(acc[2][1][0][1]), "+f"(acc[2][1][0][2]),
          "+f"(acc[2][1][0][3]), "+f"(acc[2][1][1][0]), "+f"(acc[2][1][1][1]), "+f"(acc[2][1][1][2]), "+f"(acc[2][1][1][3]),
          "+f"(acc[2][2][0][0]), "+f"(acc[2][2][0][1]), "+f"(acc[2][2][0][2]), "+f"(acc[2][2][0][3]), "+f"(acc[2][2][1][0]),
          "+f"(acc[2][2][1][1]), "+f"(acc[2][2][1][2]), "+f"(acc[2][2][1][3]), "+f"(acc[2][3][0][0]), "+f"(acc[2][3][0][1]),
          "+f"(acc[2][3][0][2]), "+f"(acc[2][3][0][3]), "+f"(acc[2][3][1][0]), "+f"(acc[2][3][1][1]), "+f"(acc[2][3][1][2]),
          "+f"(acc[2][3][1][3]), "+f"(acc[3][0][0][0]), "+f"(acc[3][0][0][1]), "+f"(acc[3][0][0][2]), "+f"(acc[3][0][0][3]),
          "+f"(acc[3][0][1][0]), "+f"(acc[3][0][1][1]), "+f"(acc[3][0][1][2]), "+f"(acc[3][0][1][3]), "+f"(acc[3][1][0][0]),
          "+f"(acc[3][1][0][1]), "+f"(acc[3][1][0][2]), "+f"(acc[3][1][0][3]), "+f"(acc[3][1][1][0]), "+f"(acc[3][1][1][1]),
          "+f"(acc[3][1][1][2]), "+f"(acc[3][1][1][3]), "+f"(acc[3][2][0][0]), "+f"(acc[3][2][0][1]), "+f"(acc[3][2][0][2]),
          "+f"(acc[3][2][0][3]), "+f"(acc[3][2][1][0]), "+f"(acc[3][2][1][1]), "+f"(acc[3][2][1][2]), "+f"(acc[3][2][1][3]),
          "+f"(acc[3][3][0][0]), "+f"(acc[3][3][0][1]), "+f"(acc[3][3][0][2]), "+f"(acc[3][3][0][3]), "+f"(acc[3][3][1][0]),
          "+f"(acc[3][3][1][1]), "+f"(acc[3][3][1][2]), "+f"(acc[3][3][1][3]), "+f"(acc[4][0][0][0]), "+f"(acc[4][0][0][1]),
          "+f"(acc[4][0][0][2]), "+f"(acc[4][0][0][3]), "+f"(acc[4][0][1][0]), "+f"(acc[4][0][1][1]), "+f"(acc[4][0][1][2]),
          "+f"(acc[4][0][1][3]), "+f"(acc[4][1][0][0]), "+f"(acc[4][1][0][1]), "+f"(acc[4][1][0][2]), "+f"(acc[4][1][0][3]),
          "+f"(acc[4][1][1][0]), "+f"(acc[4][1][1][1]), "+f"(acc[4][1][1][2]), "+f"(acc[4][1][1][3]), "+f"(acc[4][2][0][0]),
          "+f"(acc[4][2][0][1]), "+f"(acc[4][2][0][2]), "+f"(acc[4][2][0][3]), "+f"(acc[4][2][1][0]), "+f"(acc[4][2][1][1]),
          "+f"(acc[4][2][1][2]), "+f"(acc[4][2][1][3]), "+f"(acc[4][3][0][0]), "+f"(acc[4][3][0][1]), "+f"(acc[4][3][0][2]),
          "+f"(acc[4][3][0][3]), "+f"(acc[4][3][1][0]), "+f"(acc[4][3][1][1]), "+f"(acc[4][3][1][2]), "+f"(acc[4][3][1][3]),
          "+r"(ring)
        : "r"(wf[0][0]), "r"(wf[0][1]), "r"(wf[0][2]), "r"(wf[0][3]), "r"(wf[1][0]), "r"(wf[1][1]), "r"(wf[1][2]), "r"(wf[1][3]),
          "r"(wf[2][0]), "r"(wf[2][1]), "r"(wf[2][2]), "r"(wf[2][3]), "r"(wf[3][0]), "r"(wf[3][1]), "r"(wf[3][2]), "r"(wf[3][3]),
          "r"(cgf[0]), "r"(cgf[1]), "r"(cgf[2]), "r"(cgf[3]), "r"(xoff), "r"(moff), "r"(rec)
        : "memory");
}

__device__ __noinline__ void generic_path(float* sagg, const __nv_bfloat16* x, const int* src, const int* dst,
                                          const __nv_bfloat16* Y, const __nv_bfloat16* ef, const __nv_bfloat16* w_rad,
                                          const __nv_bfloat16* cg, int x0, int x1) {
    const int tid = threadIdx.x, lane = tid & 31, blk = blockIdx.x;
    for (int k = 0; k < 2; k++)
        for (int r = 0; r < min(k == 0 ? x0 : x1, 32); r++) {
            uint32_t* p2 = g_mail2 + (blk * NSRC + ((tid + k * NTHR) >> 3)) * 32 + r;
            uint32_t v;
            int it = 0;
            do {
                asm volatile("ld.relaxed.gpu.global.u32 %0, [%1];" : "=r"(v) : "l"(p2) : "memory");
                if (++it > (1 << 20)) __trap();
            } while (v == 0);
            *p2 = 0;
        }
    __syncthreads();
    for (int i = tid; i < NPB * 512; i += NTHR) sagg[i] = 0.f;
    __syncthreads();
    for (int e0 = tid & ~31; e0 < N_EDGES; e0 += NTHR) {
        uint32_t bm = __ballot_sync(~0u, dst[e0 + lane] / NPB == blk);
        while (bm) {
            const int e = e0 + __ffs(bm) - 1, s = src[e], loc = dst[e] - blk * NPB;
            bm &= bm - 1;
            float a[4][4];
            for (int i = 0; i < 4; i++)
                for (int o = 0; o < 4; o++) {
                    a[i][o] = 0.f;
                    for (int f = 0; f < 4; f++)
                        a[i][o] += __bfloat162float(Y[e * 4 + f]) * __bfloat162float(cg[i * 16 + f * 4 + o]);
                }
#pragma unroll 1
            for (int c = lane; c < 128; c += 32) {
                float pre = 0.f;
                for (int k = 0; k < 16; k++)
                    pre += __bfloat162float(ef[e * 16 + k]) * __bfloat162float(w_rad[k * 128 + c]);
                const float R = pre / (1.f + __expf(-pre));
                for (int o = 0; o < 4; o++) {
                    float acc = 0.f;
                    for (int i = 0; i < 4; i++) acc += __bfloat162float(x[(size_t)s * 512 + c * 4 + i]) * a[i][o];
                    atomicAdd(&sagg[loc * 512 + c * 4 + o], R * acc);
                }
            }
        }
    }
    __syncthreads();
}

__device__ __forceinline__ void init_barriers() {
    extern __shared__ __align__(1024) uint8_t smem[];
    const uint32_t sb = smem_u32(smem);
#pragma unroll
    for (int i = 0; i < 4 * NG; i++) {
        mbar_init(sb + i * STAGE + 4 * ROWP, 32);
        mbar_init(sb + i * STAGE + 4 * ROWP + 8, 2);
    }
}

template <int PHASES>
__global__ void __launch_bounds__(NTHR, 1)
tfn_kernel(const __nv_bfloat16* __restrict__ x, const int* __restrict__ src, const int* __restrict__ dst,
           const __nv_bfloat16* __restrict__ Y, const __nv_bfloat16* __restrict__ ef,
           const __nv_bfloat16* __restrict__ w_rad, const __nv_bfloat16* __restrict__ cg,
           const __nv_bfloat16* __restrict__ w_mix, __nv_bfloat16* __restrict__ out) {
    extern __shared__ __align__(1024) uint8_t smem[];
    const int tid = threadIdx.x, lane = tid & 31;
    const int warp = __shfl_sync(~0u, tid >> 5, 0);
    const int blk = blockIdx.x;
    uint32_t sb = smem_u32(smem);
    asm volatile("" : "+r"(sb));
    int* mi = reinterpret_cast<int*>(smem + SM_MISC);

    const int g = lane >> 2, t = lane & 3;
    const uint32_t dump = sb + SC_DUMP + lane * 4;
    int4 d1[2], s1[2];
    constexpr int nq = EPC / 4;
    const bool binner = (PHASES & 1) && blk < NSRC;
    if (binner) {
#pragma unroll
        for (int k = 0; k < 2; k++) {
            const int q = tid + k * NTHR;
            if (q < nq) {
                d1[k] = __ldg(reinterpret_cast<const int4*>(dst + blk * EPC) + q);
                s1[k] = __ldg(reinterpret_cast<const int4*>(src + blk * EPC) + q);
            }
        }
    }
    if (binner) {
#pragma unroll
        for (int k = 0; k < 3; k++)
            if (k < 2 || warp < 1) sts128(sb + SC_MAIL + (tid + k * NTHR) * 16, ~0u, ~0u, ~0u, ~0u);
        if (tid <= NB / 4) sts128(sb + SC_CNT + tid * 16, 0, 0, 0, 0);
    }
    if (PHASES & 2) {
        if (tid == 160) { sts128(sb + SM_MISC, 0, 0, 0, 0); sts128(sb + SM_MISC + MI_NU * 4, 0, 0, 0, 0); }
        if (tid == 161) {
            mi[MI_SHIFT] = 0;
            *reinterpret_cast<int**>(mi + MI_SHIFT + 4) = g_lag[blk];
        }
        if (tid == 162) g_lag[blk][0] = g_lag[NB + blk][0] = 0;
        if (tid < 20 * HS / 4) sts128(sb + SC_HIST + tid * 16, 0, 0, 0, 0);
        const uint32_t pad = (uint32_t)(lane * 0x10008 + 7);
#pragma unroll
        for (int k = 0; k < 3; k++)
            if (tid + k * NTHR < 4 * UCAP * REC / 16) sts128(sb + SM_REC + (tid + k * NTHR) * 16, pad, pad, pad, pad);
    }
    __syncthreads();
    if (PHASES & 2) {
#pragma unroll
        for (int k = 0; k < 4; k++) {
            const int i = tid + k * NTHR, c = i >> 4;
            cp16(sb + SM_W + c * 256 + (((i & 15) ^ ((c & 2) | (((c >> 4) & 1) << 2))) << 4), w_mix + i * 8);
        }
        if (warp >= 8) cp16(sb + SC_WR + ((tid - 256) ^ ((tid >> 4) & 6)) * 16, w_rad + (tid - 256) * 8);
        if (tid < 8) cp16(sb + SC_WR + 4096 + tid * 16, cg + tid * 8);
    }
    if (binner) {
#pragma unroll
        for (int k = 0; k < 2; k++) {
            if (tid + k * NTHR < nq) {
                const uint32_t dd[4] = {(uint32_t)d1[k].x, (uint32_t)d1[k].y, (uint32_t)d1[k].z, (uint32_t)d1[k].w};
                const uint32_t ss[4] = {(uint32_t)s1[k].x, (uint32_t)s1[k].y, (uint32_t)s1[k].z, (uint32_t)s1[k].w};
                uint32_t own[4], rk[4], v[4];
#pragma unroll
                for (int j = 0; j < 4; j++) { own[j] = dd[j] / NPB; rk[j] = atoms_inc(sb + SC_CNT + own[j] * 4); }
#pragma unroll
                for (int j = 0; j < 4; j++) {
                    const uint32_t loc = dd[j] - own[j] * NPB, code = loc + ((loc * 216) >> 12);
                    v[j] = (ss[j] << 18) + code * 2560 + (tid + k * NTHR) * 4 + j + 1;
                    sts32(sb + SC_MAIL + own[j] * 128 + ((min(rk[j], 31u) * 4) ^ ((own[j] & 7) << 4)), v[j]);
                }
                if (max(max(rk[0], rk[1]), max(rk[2], rk[3])) >= 31) {
#pragma unroll
                    for (int j = 0; j < 4; j++)
                        if (rk[j] - 31 < 32)
                            asm volatile("st.relaxed.gpu.global.u32 [%0], %1;" ::"l"(g_mail2 + (own[j] * NSRC + blk) * 32 + rk[j] - 31), "r"(v[j]) : "memory");
                }
            }
        }
        __syncwarp();
        asm volatile("red.shared.max.u32 [%0], %1;" ::"r"(lane == 0 ? sb + SC_CNT + NB * 4 : dump), "r"(gtime()) : "memory");
        STAMP(1);
        __syncthreads();
        const uint32_t hdr = 0xc0000000u | ((lds32(sb + SC_CNT + NB * 4) << 7) & 0x3ffff000u);
        uint4 mv[3];
        uint32_t mc[3];
#pragma unroll
        for (int k = 0; k < 3; k++)
            if (k < 2 || warp < 1) {
                const int j = tid + k * NTHR, own = j >> 3;
                mv[k] = lds128(sb + SC_MAIL + own * 128 + (((j ^ own) & 7) << 4));
                mc[k] = lds32(sb + SC_CNT + own * 4);
            }
#pragma unroll
        for (int k = 0; k < 3; k++)
            if (k < 2 || warp < 1) {
                const int j = tid + k * NTHR;
                asm volatile("st.relaxed.gpu.global.v4.u32 [%0], {%1,%2,%3,%4};" ::"l"(g_mail + ((j >> 3) * NSRC + blk) * 8 + (j & 7)),
                             "r"(mv[k].x), "r"(mv[k].y), "r"(mv[k].z), "r"((j & 7) == 7 ? hdr | mc[k] : mv[k].w) : "memory");
            }
        STAMP(2);
    }
    if (!(PHASES & 2)) return;
    const uint32_t tpub = (uint32_t)clock() + (blk < NSRC ? 0 : 3000);
    asm volatile("cp.async.wait_all;" ::: "memory");
    __syncwarp();
#pragma unroll
    for (int k = 0; k < 2; k++) {
        const int i = (tid & ~1) + ((tid & 1) * 2 + k) * NTHR, c = i >> 4;
        const uint32_t a0 = sb + SM_W + c * 256 + (((i & 15) ^ ((c & 3) | (((c >> 4) & 1) << 2))) << 4);
        const uint32_t o = (tid & 1) << 4;
        uint4 u = lds128((a0 & ~16u) ^ o), v = lds128((a0 | 16u) ^ o);
        if (tid & 1) { const uint4 w = u; u = v; v = w; }
        const uint32_t s0 = (tid & 1) ? 0x7632 : 0x5410, s1 = s0 ^ 0x2222;
        sts128(a0 ^ o, __byte_perm(u.x, u.y, s0), __byte_perm(u.z, u.w, s0), __byte_perm(v.x, v.y, s0), __byte_perm(v.z, v.w, s0));
        sts128(a0 ^ o ^ 16, __byte_perm(u.x, u.y, s1), __byte_perm(u.z, u.w, s1), __byte_perm(v.x, v.y, s1), __byte_perm(v.z, v.w, s1));
    }

    uint32_t en[8], hr[8], rk[8], em[8];
    int xc[2];
    const uint32_t tref = __shfl_sync(~0u, gtime() >> 5, 0);
    {
        uint4* mp = g_mail + blk * NSRC * 8 + tid;
        int it = 0;
        bool ok;
        while ((int)((uint32_t)clock() - tpub) < POLL_DELAY) {}
        do {
#pragma unroll
            for (int k = 0; k < 2; k++)
                    asm volatile("ld.relaxed.gpu.global.v4.u32 {%0,%1,%2,%3}, [%4];"
                                 : "=r"(en[4 * k]), "=r"(en[4 * k + 1]), "=r"(en[4 * k + 2]), "=r"(en[4 * k + 3])
                                 : "l"(mp + k * NTHR) : "memory");
            uint32_t m = ~0u;
#pragma unroll
            for (int i = 0; i < 8; i++) m = min(m, en[i]);
            ok = __all_sync(~0u, m != 0);
            if (++it > (1 << 20)) __trap();
        } while (!ok);
        STAMP(3);
#pragma unroll
        for (int i = 0; i < 8; i++) {
            const uint32_t w = en[i] & 0x3ffff, code = ((w >> 9) * 13108) >> 16;
            hr[i] = en[i] < 0xc0000000u ? sb + SC_HIST + ((code >> 2) * HS + (en[i] >> 25)) * 4 : dump;
            rk[i] = atoms_inc(hr[i]);
            em[i] = ((((tid + (i >> 2) * NTHR) >> 3) * EPC + w - code * 2560 - 1) * 8) | (code & 3);
        }
        int dt = -(1 << 20);
#pragma unroll
        for (int k = 0; k < 2; k++) {
            const bool hd = (lane & 7) == 7;
            dt = max(dt, hd ? (int)(((en[4 * k + 3] >> 12) - tref) << 14) >> 14 : -(1 << 20));
            xc[k] = hd ? max((int)(en[4 * k + 3] & 0xfff) - 31, 0) : 0;
        }
        dt = __reduce_max_sync(~0u, dt);
        asm volatile("red.shared.max.u32 [%0], %1;" ::"r"(lane == 0 ? sb + SM_MISC + MI_TMAX * 4 : dump + 128), "r"(tref + dt + (1u << 27)) : "memory");
        if (xc[0] | xc[1]) {
#pragma unroll
            for (int k = 0; k < 2; k++) {
                const int slot = atomicAdd(&mi[MI_XN], xc[k]);
                for (int r = 0; r < xc[k] && slot + r < 32; r++)
                    reinterpret_cast<uint32_t*>(smem + SC_XTRA)[slot + r] = ((tid + k * NTHR) >> 3) * 32 + r;
            }
        }
#pragma unroll
        for (int k = 0; k < 2; k++)
            mp[k * NTHR] = make_uint4(0, 0, 0, 0);
    }
    __syncthreads();
    STAMP(4);
    uint32_t* hist = reinterpret_cast<uint32_t*>(smem + SC_HIST);
    const int xn = mi[MI_XN];
    uint32_t xi = 0, xv = 1;
    if (warp < 10) {
        uint32_t* hp = hist + (warp * 2 + (lane >> 4)) * HS + (lane & 15) * 5;
        int c[5], s = 0;
#pragma unroll
        for (int j = 0; j < 5; j++) { c[j] = hp[j]; s += c[j]; }
        int inc = s;
#pragma unroll
        for (int o = 1; o < 16; o <<= 1) { int v = __shfl_up_sync(~0u, inc, o, 16); if ((lane & 15) >= o) inc += v; }
        int base = 0;
        if ((lane & 15) == 15) {
            const int tm = (warp * 2 + (lane >> 4)) / 5;
            base = tm * 256 + atomicAdd(&mi[MI_NU + tm], (inc + 3) >> 2);
            hp[5] = (base + ((inc + 3) >> 2)) << 16;
        }
        const int tot = __shfl_sync(~0u, inc, 15, 16);
        base = __shfl_sync(~0u, base, 15, 16);
        int ex = inc - s;
#pragma unroll
        for (int j = 0; j < 5; j++) {
            hp[j] = (base * 4 + ex) | ((base + ((ex == tot ? ex + 3 : ex + 1) >> 2)) << 16);
            ex += c[j];
        }
    } else if (warp == 10) {
        if (lane == 0) init_barriers();
        if (lane < xn) {
            xi = reinterpret_cast<const uint32_t*>(smem + SC_XTRA)[lane];
            asm volatile("ld.relaxed.gpu.global.u32 %0, [%1];" : "=r"(xv) : "l"(g_mail2 + blk * NSRC * 32 + xi) : "memory");
        }
    } else if (warp >= 12) {
        const uint32_t d = sb + (warp - 12) * NG * STAGE + lane * 16;
#pragma unroll
        for (int m = 0; m < 8; m++) {
            uint32_t w[4];
#pragma unroll
            for (int j = 0; j < 4; j++)
                w[j] = mul_lo(lds32(sb + SC_WR + (2 * t + (j & 1) + (j >> 1) * 8) * 256 + (((m * 8 + g) * 4) ^ (t << 5))), 0x3f003f00u);
            sts128(d + (m >> 2) * ROWP + (m & 3) * 512, __byte_perm(w[0], w[1], 0x5410), __byte_perm(w[0], w[1], 0x7632),
                   __byte_perm(w[2], w[3], 0x5410), __byte_perm(w[2], w[3], 0x7632));
        }
        uint32_t c[4];
#pragma unroll
        for (int i = 0; i < 4; i++) {
            const uint32_t ca = sb + SC_WR + 4096 + (i * 16 + (t & 1) * 8 + (g & 3)) * 2;
            c[i] = (lds16(ca) | (lds16(ca + 8) << 16)) & ((t >> 1) == (g >> 2) ? ~0u : 0u);
        }
        sts128(d + 2 * ROWP, c[0], c[1], c[2], c[3]);
    } else if (lane == 0) {
        sts32(sb + SC_GPOS + GDUMMY * 4, (uint32_t)(4 * UCAP * REC + 128) * 0x10001u);
        constexpr int start_ns = START_NS;
        mi[MI_T0] = (uint32_t)clock() + (((int)(((uint32_t)mi[MI_TMAX] << 5) + start_ns - gtime()) * 31) >> 4);
    }
    __syncthreads();
    STAMP(10);
    int myng = mi[MI_NU + (lane & 3)];
    const bool ovf = __any_sync(~0u, myng + xn > 2 * (UCAP - 4) || xn > 32);
    if (!ovf) {
        constexpr int pace = PACE_Q8, p1 = PACE_HEAD, b1 = HEAD_BK, p2 = PACE_TAIL, b2 = TAIL_BK, lead = PACE_LEAD;
        auto sched = [&](int b) { return b * pace - min(b, b1) * (pace - p1) - max(b - b2, 0) * (pace - p2) - lead; };
        if (warp < 10) {
            const int team = tid / NBK, b = tid - team * NBK;
            int lo[5], n[5], pos = team * UCAP * 2, nsum = 0;
#pragma unroll
            for (int q = 0; q < 5; q++) {
                lo[q] = hist[(team * 5 + q) * HS + b] >> 16;
                n[q] = (hist[(team * 5 + q) * HS + b + 1] >> 16) - lo[q];
                pos += lo[q] - (hist[(team * 5 + q) * HS] >> 16);
                nsum += n[q];
            }
            const int step = __float2int_rz(__fdividef((float)(sched(b + 1) - sched(b)), (float)max(nsum, 1)));
            const int tb = sched(b) + step / 2 - pos * step;
            const uint32_t t0 = mi[MI_T0];
            auto emit = [&](int q, int r, int pq) {
                const bool on = r < n[q];
                const uint32_t ro = (pq >> 1) * REC, par = pq & 1;
                sts32(on ? sb + SC_GPOS + (lo[q] + r) * 4 : dump, ro * 0x10001u + par * 0x40002u + (REC | (16 << 16)));
                sts8(on ? sb + SM_REC + 48 + ro + par : dump, q);
                sts16(on && !par ? sb + SM_REC + REC + 50 + ro : dump, (t0 + max(tb + pq * step, 0)) >> 2);
            };
#pragma unroll
            for (int q = 0, pq = pos; q < 5; pq += n[q], q++) emit(q, 0, pq);
#pragma unroll
            for (int q = 0; q < 5; pos += n[q], q++)
#pragma unroll 1
                for (int r = 1; __any_sync(~0u, r < n[q]); r++) emit(q, r, pos + r);
        } else if (warp == 10) {
            for (int n = 0; __any_sync(~0u, xv == 0); n++) {
                if (xv == 0) asm volatile("ld.relaxed.gpu.global.u32 %0, [%1];" : "=r"(xv) : "l"(g_mail2 + blk * NSRC * 32 + xi) : "memory");
                if (n > (1 << 20)) __trap();
            }
            const uint32_t w = xv & 0x3ffff, code = ((w >> 9) * 13108) >> 16, xt = lane < xn ? code / 20 : 4;
            const uint32_t same = __match_any_sync(~0u, xt);
            const int pq = __shfl_sync(~0u, myng, xt & 3) + __popc(same & ((1u << lane) - 1));
#pragma unroll
            for (int q = 0; q < 4; q++) {
                const int c = __popc(__ballot_sync(~0u, xt == q));
                if (lane == q) myng += c;
            }
            if (lane < xn) {
                g_mail2[blk * NSRC * 32 + xi] = 0;
                const uint32_t a = sb + SM_REC + (xt * UCAP + (pq >> 1)) * REC;
                sts16(a + REC + (pq & 1) * 2, xv >> 18);
                sts32(a + 16 + (pq & 1) * 4, (((xi >> 5) * EPC + w - code * 2560 - 1) * 8) | (code & 3));
                sts8(a + 48 + (pq & 1), (code >> 2) - xt * 5);
                if (!(pq & 1)) sts16(a + REC + 50, ((uint32_t)mi[MI_T0] + sched(NBK - 2)) >> 2);
            }
            if (lane < 4) {
                const uint32_t a = sb + SM_REC + (lane * UCAP + (myng >> 1)) * REC + 48;
                if (myng & 1) sts8(a + 1, 0);
                sts16(a + (myng & 1) * REC, 5);
                mi[MI_END + lane] = (myng + 1) >> 1;
            }
        }
#pragma unroll
        for (int i = 0; i < 8; i++) {
            const uint32_t p = en[i] < 0xc0000000u ? rk[i] + lds16(hr[i]) : GDUMMY * 4;
            hr[i] = sb + SC_GPOS + (p & ~3u);
            rk[i] = (p & 3) * 0x80004u;
        }
        __syncthreads();
        STAMP(11);
#pragma unroll
        for (int i = 0; i < 8; i++) rk[i] += lds32(hr[i]);
#pragma unroll
        for (int i = 0; i < 8; i++) {
            sts16(sb + SM_REC + (rk[i] & 0xffff), en[i] >> 18);
            sts32(sb + SM_REC + (rk[i] >> 16), em[i]);
        }
    } else {
        if (tid < 4) {
            sts16(sb + SM_REC + tid * UCAP * REC + 48, 5);
            mi[MI_END + tid] = 0;
        }
        generic_path(reinterpret_cast<float*>(smem), x, src, dst, Y, ef, w_rad, cg, xc[0], xc[1]);
    }

    __syncwarp();
    if (warp >= 8) {
        asm volatile("bar.sync 3, 512;" ::: "memory");
        asm volatile("setmaxnreg.dec.sync.aligned.u32 24;");
        const int team = warp & 3;
        if (ovf) {
            asm volatile("bar.sync 2;" ::: "memory");
            if (tid == 256) init_barriers();
            asm volatile("bar.sync 2;" ::: "memory");
        }
        STAMP(5);
        const uint32_t ring = sb + SM_RING + team * NG * STAGE;
        const uint32_t q = lane >> 3, c = lane & 7, rec = sb + SM_REC + team * UCAP * REC;
        __syncwarp();
        producer_loop(reinterpret_cast<const char*>(x) + (ROWMODE == 0 ? c : ROWMODE == 1 ? lane & 15 : lane) * 16, reinterpret_cast<const char*>(ef) + (c & 1) * 16, Y,
                      q * ROWP + ((c ^ (q << 1)) << 4), q * 4 + (c & 2) * 8, (c & 1) * 2 + (c >> 2), ring, rec,
                      rec + (mi[MI_END + team] + 1) * REC, warp - 8, sb + SM_MISC + MI_SHIFT * 4,
                      ROWMODE == 1 ? (lane >> 4) * ROWP + (((lane & 15) ^ ((lane >> 4) << 1)) << 4) : lane * 16);
        uint32_t ln, sb2, cta;
        asm volatile("mov.u32 %0, %%tid.x;\nmov.u32 %1, %%ctaid.x;\nmov.u32 %2, %%dynamic_smem_size;" : "=r"(ln), "=r"(cta), "=r"(sb2));
        if (FEEDBACK && cta == NB - 1 && ln >= NTHR - 32) {
            ln &= 31;
            sb2 += smem_u32(smem) - SM_TOTAL + SM_MISC;
            constexpr int lead = LEAD_CLK >> 2;
            const uint32_t tend = lds32(sb2 + MI_T0 * 4) + 70 * PACE_Q8;
            int sh = 0;
            for (int n = 0; n < 199 && (int)((uint32_t)clock() - tend - (sh >> 14)) < 0; n++) {
                int v;
                asm volatile("ld.relaxed.gpu.global.s32 %0, [%1];" : "=r"(v) : "l"(g_lag[ln * 4]) : "memory");
                const int err = (__reduce_add_sync(~0u, max(v, 0)) >> 5) - lead;
                sh = min(max((sh >> 16) + (err * (err > 0 ? FB_GAIN : FB_DOWN) >> 3), FB_MIN), 2500) << 16;
#pragma unroll
                for (int k = 0; k < 5; k++)
                    asm volatile("st.relaxed.gpu.global.s32 [%0], %1;" ::"l"(g_lag[NB + min(ln + 32 * k, NB - 1u)]), "r"(sh) : "memory");
            }
        }
    } else {
        int team;
        {
            const int n0 = mi[MI_END], n1 = mi[MI_END + 1], n2 = mi[MI_END + 2], n3 = mi[MI_END + 3];
            const int d1 = abs(n0 + n1 - n2 - n3), d2 = abs(n0 + n2 - n1 - n3), d3 = abs(n0 + n3 - n1 - n2);
            const uint32_t perm = PAIRING && d1 < min(d2, d3) ? 0x3120 : PAIRING && d3 < d2 ? 0x2310 : 0x3210;
            team = __shfl_sync(~0u, (perm >> ((warp >> 1) * 4)) & 3, 0);
        }
        const int h = warp & 1;
        asm volatile("bar.arrive 3, 512;" ::: "memory");
        asm volatile("setmaxnreg.inc.sync.aligned.u32 232;");
        uint32_t ring = sb + SM_RING + team * NG * STAGE;
        uint32_t wf[4][4], cgf[4];
#pragma unroll
        for (int m = 0; m < 5; m++) {
            const uint4 v = lds128(ring + (m < 4 ? h * ROWP + m * 512 : 2 * ROWP) + lane * 16);
            uint32_t* f = m < 4 ? wf[m] : cgf;
            f[0] = v.x; f[1] = v.y; f[2] = v.z; f[3] = v.w;
        }
        float acc[5][4][2][4];
        if (!ovf) {
#pragma unroll
            for (int l = 0; l < 5; l++)
#pragma unroll
                for (int m = 0; m < 4; m++)
#pragma unroll
                    for (int p = 0; p < 2; p++)
#pragma unroll
                        for (int r = 0; r < 4; r++) acc[l][m][p][r] = 0.f;
        } else {
            const float* sagg = reinterpret_cast<const float*>(smem);
#pragma unroll
            for (int l = 0; l < 5; l++)
#pragma unroll
                for (int m = 0; m < 4; m++)
#pragma unroll
                    for (int p = 0; p < 2; p++)
#pragma unroll
                        for (int r = 0; r < 4; r++) {
                            int nd = l * 4 + (g >> 2) + (r >> 1) * 2;
                            int ch = h * 64 + m * 16 + 4 * t + (r & 1) * 2 + p;
                            acc[l][m][p][r] = nd < 19 ? sagg[(team * 19 + nd) * 512 + ch * 4 + (g & 3)] : 0.f;
                        }
            asm volatile("bar.sync 2;" ::: "memory");
            asm volatile("bar.sync 2;" ::: "memory");
        }
        const uint32_t xoff = t * ROWP + h * 512 + ((g ^ (t << 1)) << 4);
        const uint32_t mat = lane >> 3, mhi = (lane >> 2) & 1;
        const bool isy = mat < 2;
        const uint32_t ml = isy ? (t & 2) + (mat & 1) : t;
        const uint32_t moff = ml * ROWP + 2048 + (((isy ? 4 + 2 * mhi + (t & 1) : 2 * mhi + mat - 2) ^ (ml << 1)) << 4);
        __syncwarp();
        consumer_loop(acc, wf, cgf, xoff, ring, moff, sb + SM_REC + team * UCAP * REC);
        {
        int lane_;
        asm volatile("mov.u32 %0, %%laneid;" : "=r"(lane_));
        const int lane = lane_, g = lane >> 2, t = lane & 3;
        const uint32_t sb = ring - team * NG * STAGE;
        STAMP(7);
        asm volatile("bar.sync %0, 64;" ::"r"(4 + team) : "memory");
        {
            const int rr = ((g & 3) >> 1) * 8 + (g >> 2) * 2 + (g & 1);
#pragma unroll
            for (int l = 0; l < 5; l++)
#pragma unroll
                for (int hi = 0; hi < 2; hi++) {
                    const int R = l * 16 + rr + hi * 4;
                    const uint32_t a = sb + team * AGGT + h * 10240 + R * 128;
#pragma unroll
                    for (int c = 0; c < 2; c++) {
                        const int m = 2 * c;
                        sts128(a + (((2 * t + c) ^ (R & 7)) << 4),
                               pack_bf16(acc[l][m][0][2 * hi], acc[l][m][1][2 * hi]),
                               pack_bf16(acc[l][m][0][2 * hi + 1], acc[l][m][1][2 * hi + 1]),
                               pack_bf16(acc[l][m + 1][0][2 * hi], acc[l][m + 1][1][2 * hi]),
                               pack_bf16(acc[l][m + 1][0][2 * hi + 1], acc[l][m + 1][1][2 * hi + 1]));
                    }
                }
        }
        asm volatile("fence.proxy.async.shared::cta;" ::: "memory");
        uint32_t wa[8][4];
        {
            const int r = lane & 7, k = (lane >> 4) * 8 + r;
            const int chunk = (2 * warp + ((lane >> 3) & 1)) ^ r;
#pragma unroll
            for (int ks = 0; ks < 8; ks++) {
                const int c = (ks >> 2) * 64 + 16 * (k >> 2) + 4 * (ks & 3) + (k & 3);
                asm volatile("ldmatrix.sync.aligned.m8n8.x4.trans.shared.b16 {%0,%1,%2,%3}, [%4];"
                             : "=r"(wa[ks][0]), "=r"(wa[ks][1]), "=r"(wa[ks][2]), "=r"(wa[ks][3])
                             : "r"(sb + SM_W + c * 256 + (chunk << 4)));
            }
        }
        asm volatile("bar.sync 1, 256;" ::: "memory");
        STAMP(8);
        const int sl = (lane & 7) * 4 + (lane >> 3);
        __nv_bfloat16* op = out + (size_t)(blk * NPB + (lane >> 3)) * 512 + warp * 64 + (lane & 7) * 8;
        const int nleft = N_NODES - blk * NPB - (lane >> 3);
#pragma unroll 1
        for (int tm = 0; tm < 4; tm++) {
            float o[40];
            asm volatile("wgmma.fence.sync.aligned;" ::: "memory");
#pragma unroll
            for (int ks = 0; ks < 8; ks++) {
                const uint32_t a = sb + tm * AGGT + (ks >> 2) * 10240 + (ks & 3) * 32;
                const uint64_t desc = (uint64_t)((a & 0x3ffff) >> 4) | (1ull << 16) | (64ull << 32) | (1ull << 62);
                wgmma_n80(o, wa[ks], desc, ks);
            }
            asm volatile("wgmma.commit_group.sync.aligned;" ::: "memory");
            asm volatile("wgmma.wait_group.sync.aligned 0;" ::: "memory");
#pragma unroll
            for (int i = 0; i < 40; i++) asm volatile("" : "+f"(o[i])::"memory");
#pragma unroll
            for (int l = 0; l < 5; l++) {
                uint4 v;
                v.x = __shfl_sync(~0u, pack_bf16(o[8 * l + 0], o[8 * l + 1]), sl);
                v.y = __shfl_sync(~0u, pack_bf16(o[8 * l + 4], o[8 * l + 5]), sl);
                v.z = __shfl_sync(~0u, pack_bf16(o[8 * l + 2], o[8 * l + 3]), sl);
                v.w = __shfl_sync(~0u, pack_bf16(o[8 * l + 6], o[8 * l + 7]), sl);
                if ((l < 4 || lane < 24) && tm * 19 + l * 4 < nleft)
                    *reinterpret_cast<uint4*>(op + (tm * 19 + l * 4) * 512) = v;
            }
        }
        STAMP(9);
        }
    }
}

}

extern "C" void kernel_launch(void* const* d_in, const int* in_sizes, int n_in, void* d_out, int out_size) {
    (void)in_sizes; (void)n_in; (void)out_size;
    const __nv_bfloat16* x = (const __nv_bfloat16*)d_in[0];
    const int* src = (const int*)d_in[1];
    const int* dst = (const int*)d_in[2];
    const __nv_bfloat16* Y = (const __nv_bfloat16*)d_in[3];
    const __nv_bfloat16* ef = (const __nv_bfloat16*)d_in[4];
    const __nv_bfloat16* w_rad = (const __nv_bfloat16*)d_in[5];
    const __nv_bfloat16* cg = (const __nv_bfloat16*)d_in[6];
    const __nv_bfloat16* w_mix = (const __nv_bfloat16*)d_in[7];
    __nv_bfloat16* out = (__nv_bfloat16*)d_out;

    static int sms = 0;
    if (sms == 0) {
        int dev = 0;
        cudaGetDevice(&dev);
        cudaDeviceGetAttribute(&sms, cudaDevAttrMultiProcessorCount, dev);
        cudaFuncSetAttribute(tfn_kernel<3>, cudaFuncAttributeMaxDynamicSharedMemorySize, SM_TOTAL);
        cudaFuncSetAttribute(tfn_kernel<1>, cudaFuncAttributeMaxDynamicSharedMemorySize, SM_TOTAL);
        cudaFuncSetAttribute(tfn_kernel<2>, cudaFuncAttributeMaxDynamicSharedMemorySize, SM_TOTAL);
    }
    if (sms >= NB) {
        tfn_kernel<3><<<NB, NTHR, SM_TOTAL>>>(x, src, dst, Y, ef, w_rad, cg, w_mix, out);
    } else {
        tfn_kernel<1><<<NB, NTHR, SM_TOTAL>>>(x, src, dst, Y, ef, w_rad, cg, w_mix, out);
        tfn_kernel<2><<<NB, NTHR, SM_TOTAL>>>(x, src, dst, Y, ef, w_rad, cg, w_mix, out);
    }
}
```

```cpp
#include <cuda_runtime.h>
#include <cuda_bf16.h>
#include <stdint.h>

namespace {

constexpr int N_NODES = 10000;
constexpr int N_EDGES = 320000;
constexpr int NB      = 132;
constexpr int NPB     = 76;
constexpr int NSRC    = 128;
constexpr int EPC     = N_EDGES / NSRC;
constexpr int NTHR    = 512;
#define NGS 5
constexpr int NG      = NGS;
constexpr int ROWP    = 2176;
constexpr int STAGE   = 4 * ROWP + 128;
constexpr int UCAP    = 104;
constexpr int REC     = 52;
constexpr int NBK     = 80;
constexpr int HS      = 81;

#define PACE_Q8 635
#define PACE_LEAD 300
#define PACE_HEAD 730
#define HEAD_BK 10
#define PACE_TAIL 610
#define TAIL_BK 66
#define POLL_DELAY 1350
#define LEAD_CLK 140
#define ROWMODE 1
#define PAIRING 1
#define FEEDBACK 1
#define FB_GAIN 24
#define FB_DOWN 4
#define FB_MIN 0
#define START_NS 3300

constexpr int SM_RING  = 0;
constexpr int SM_W     = 4 * NG * STAGE;
constexpr int SM_REC   = SM_W + 32768;
constexpr int SM_MISC  = SM_REC + 4 * UCAP * REC;
constexpr int SM_TOTAL = SM_MISC + 224;
constexpr int SC_MAIL  = 1 * STAGE;
constexpr int SC_CNT   = 3 * STAGE;
constexpr int SC_DUMP  = 3 * STAGE + 1024;
constexpr int SC_XTRA  = 3 * STAGE + 2048;
constexpr int SC_HIST  = 4 * STAGE;
constexpr int SC_GPOS  = 6 * STAGE;
constexpr int SC_WR    = 7 * STAGE;
constexpr int GDUMMY   = 1024;
constexpr int AGGT     = (NG * STAGE + 1023) / 1024 * 1024;
static_assert(3 * AGGT + 20480 <= 4 * NG * STAGE, "agg tile inside the team's ring");
static_assert(NPB * 512 * 4 <= 4 * NG * STAGE, "slow tile");
static_assert(SM_TOTAL <= 232448, "smem");
static_assert(SM_REC % 16 == 0 && (4 * UCAP * REC) % 16 == 0 && SM_MISC % 16 == 0, "align");
constexpr int MI_XN = 0;
constexpr int MI_TMAX = 2;
constexpr int MI_SHIFT = 48;
constexpr int MI_NU = 8;
constexpr int MI_END = 28;
constexpr int MI_T0 = 3;

__device__ uint4 g_mail[NB * NSRC * 8];
__device__ uint32_t g_mail2[NB * NSRC * 32];
__device__ __align__(128) int g_lag[2 * NB][32];
#define STAMP(k)

__device__ __forceinline__ uint32_t smem_u32(const void* p) { return (uint32_t)__cvta_generic_to_shared(p); }
__device__ __forceinline__ uint32_t atoms_inc(uint32_t a) {
    uint32_t r;
    asm volatile("atom.shared.add.u32 %0, [%1], 1;" : "=r"(r) : "r"(a) : "memory");
    return r;
}
__device__ __forceinline__ void sts32(uint32_t a, uint32_t v) { asm volatile("st.shared.u32 [%0], %1;" ::"r"(a), "r"(v) : "memory"); }
__device__ __forceinline__ void sts16(uint32_t a, uint32_t v) { asm volatile("st.shared.u16 [%0], %1;" ::"r"(a), "h"((uint16_t)v) : "memory"); }
__device__ __forceinline__ void sts8(uint32_t a, uint32_t v) { asm volatile("st.shared.u8 [%0], %1;" ::"r"(a), "r"(v) : "memory"); }
__device__ __forceinline__ uint32_t lds32(uint32_t a) { uint32_t v; asm volatile("ld.shared.u32 %0, [%1];" : "=r"(v) : "r"(a)); return v; }
__device__ __forceinline__ uint32_t lds16(uint32_t a) { uint32_t v; asm volatile("ld.shared.u16 %0, [%1];" : "=r"(v) : "r"(a)); return v; }
__device__ __forceinline__ void cp16(uint32_t d, const void* p) {
    asm volatile("cp.async.cg.shared.global [%0], [%1], 16;" ::"r"(d), "l"(p) : "memory");
}
__device__ __forceinline__ uint32_t gtime() {
    uint32_t t;
    asm volatile("mov.u32 %0, %%globaltimer_lo;" : "=r"(t));
    return t;
}
__device__ __forceinline__ void mbar_init(uint32_t bar, int cnt) {
    asm volatile("mbarrier.init.shared.b64 [%0], %1;" ::"r"(bar), "r"(cnt) : "memory");
}
__device__ __forceinline__ void mbar_wait(uint32_t bar, uint32_t parity) {
    asm volatile("{\n.reg .pred p;\n.reg .u32 n;\nmov.u32 n, 0;\n"
                 "WAIT_%=:\nmbarrier.try_wait.parity.shared.b64 p, [%0], %1;\n@p bra DONE_%=;\n"
                 "add.u32 n, n, 1;\nsetp.lt.u32 p, n, 4194304;\n@p bra WAIT_%=;\ntrap;\nDONE_%=:\n}"
                 ::"r"(bar), "r"(parity) : "memory");
}
__device__ __forceinline__ void mbar_arrive_elect(uint32_t bar) {
    asm volatile("{\n.reg .pred p;\nelect.sync _|p, 0xffffffff;\n@p mbarrier.arrive.shared.b64 _, [%0];\n}" ::"r"(bar) : "memory");
}
__device__ __forceinline__ uint4 lds128(uint32_t a) {
    uint4 v;
    asm volatile("ld.shared.v4.u32 {%0,%1,%2,%3}, [%4];" : "=r"(v.x), "=r"(v.y), "=r"(v.z), "=r"(v.w) : "r"(a));
    return v;
}
__device__ __forceinline__ void sts128(uint32_t a, uint32_t x, uint32_t y, uint32_t z, uint32_t w) {
    asm volatile("st.shared.v4.u32 [%0], {%1,%2,%3,%4};" ::"r"(a), "r"(x), "r"(y), "r"(z), "r"(w) : "memory");
}
__device__ __forceinline__ uint32_t pack_bf16(float lo, float hi) {
    uint32_t r;
    asm("cvt.rn.bf16x2.f32 %0, %1, %2;" : "=r"(r) : "f"(hi), "f"(lo));
    return r;
}
__device__ __forceinline__ float tanh_fast(float x) {
    float r;
    asm("tanh.approx.f32 %0, %1;" : "=f"(r) : "f"(x));
    return r;
}
__device__ __forceinline__ uint32_t mul_lo(uint32_t v, uint32_t r) {
    __nv_bfloat162 a = *reinterpret_cast<__nv_bfloat162*>(&v), b = *reinterpret_cast<__nv_bfloat162*>(&r);
    __nv_bfloat162 c = __hmul2(a, __low2bfloat162(b));
    return *reinterpret_cast<uint32_t*>(&c);
}
__device__ __forceinline__ uint32_t mul_hi(uint32_t v, uint32_t r) {
    __nv_bfloat162 a = *reinterpret_cast<__nv_bfloat162*>(&v), b = *reinterpret_cast<__nv_bfloat162*>(&r);
    __nv_bfloat162 c = __hmul2(a, __high2bfloat162(b));
    return *reinterpret_cast<uint32_t*>(&c);
}
__device__ __forceinline__ void mma0(float (&d)[4], uint32_t a0, uint32_t a1, uint32_t a2, uint32_t a3,
                                     uint32_t b0, uint32_t b1) {
    asm("mma.sync.aligned.m16n8k16.row.col.f32.bf16.bf16.f32 {%0,%1,%2,%3}, {%4,%5,%6,%7}, {%8,%9}, {%10,%10,%10,%10};"
        : "=f"(d[0]), "=f"(d[1]), "=f"(d[2]), "=f"(d[3])
        : "r"(a0), "r"(a1), "r"(a2), "r"(a3), "r"(b0), "r"(b1), "f"(0.f));
}
__device__ __forceinline__ void mma0_k8(float (&d)[4], uint32_t a0, uint32_t a1, uint32_t b0) {
    asm("mma.sync.aligned.m16n8k8.row.col.f32.bf16.bf16.f32 {%0,%1,%2,%3}, {%4,%5}, {%6}, {%7,%7,%7,%7};"
        : "=f"(d[0]), "=f"(d[1]), "=f"(d[2]), "=f"(d[3])
        : "r"(a0), "r"(a1), "r"(b0), "f"(0.f));
}
__device__ __forceinline__ void mma_acc(float (&d)[4], const uint32_t (&a)[4], uint32_t b0, uint32_t b1) {
    asm volatile("mma.sync.aligned.m16n8k16.row.col.f32.bf16.bf16.f32 {%0,%1,%2,%3}, {%4,%5,%6,%7}, {%8,%9}, {%0,%1,%2,%3};"
        : "+f"(d[0]), "+f"(d[1]), "+f"(d[2]), "+f"(d[3])
        : "r"(a[0]), "r"(a[1]), "r"(a[2]), "r"(a[3]), "r"(b0), "r"(b1));
}
__device__ __forceinline__ void wgmma_n80(float (&d)[40], const uint32_t (&a)[4], uint64_t desc, int scale_d) {
    asm volatile("{\n.reg .pred p;\nsetp.ne.b32 p, %45, 0;\n"
        "wgmma.mma_async.sync.aligned.m64n80k16.f32.bf16.bf16 "
        "{%0,%1,%2,%3,%4,%5,%6,%7,%8,%9,%10,%11,%12,%13,%14,%15,%16,%17,%18,%19,"
        "%20,%21,%22,%23,%24,%25,%26,%27,%28,%29,%30,%31,%32,%33,%34,%35,%36,%37,%38,%39}, "
        "{%40,%41,%42,%43}, %44, p, 1, 1, 0;\n}"
        : "+f"(d[0]), "+f"(d[1]), "+f"(d[2]), "+f"(d[3]), "+f"(d[4]), "+f"(d[5]), "+f"(d[6]), "+f"(d[7]),
          "+f"(d[8]), "+f"(d[9]), "+f"(d[10]), "+f"(d[11]), "+f"(d[12]), "+f"(d[13]), "+f"(d[14]), "+f"(d[15]),
          "+f"(d[16]), "+f"(d[17]), "+f"(d[18]), "+f"(d[19]), "+f"(d[20]), "+f"(d[21]), "+f"(d[22]), "+f"(d[23]),
          "+f"(d[24]), "+f"(d[25]), "+f"(d[26]), "+f"(d[27]), "+f"(d[28]), "+f"(d[29]), "+f"(d[30]), "+f"(d[31]),
          "+f"(d[32]), "+f"(d[33]), "+f"(d[34]), "+f"(d[35]), "+f"(d[36]), "+f"(d[37]), "+f"(d[38]), "+f"(d[39])
        : "r"(a[0]), "r"(a[1]), "r"(a[2]), "r"(a[3]), "l"(desc), "r"(scale_d));
}

__device__ __forceinline__ void producer_loop(const void* xl, const void* efl, const void* Y, uint32_t xd, uint32_t oef,
                                              uint32_t ysel, uint32_t ring, uint32_t rec, uint32_t rlast, uint32_t odd,
                                              uint32_t lag, uint32_t xh) {
    asm volatile(
        "{\n"
        ".reg .b32 w, em, ey, cu, d, t, u, n, sa, ph, rp, rend, rlast, dy, sv, lag, lv, w2, w3, w4;\n"
        ".reg .b16 tg;\n"
        ".reg .b64 pa, pb, pc, pd;\n"
        ".reg .pred lo, z, q, e, zb, fbk;\n"
        "redux.sync.or.b32 sa, %6, 0xffffffff;\n"
        "redux.sync.or.b32 rp, %7, 0xffffffff;\n"
        "redux.sync.or.b32 rlast, %8, 0xffffffff;\n"
        "redux.sync.or.b32 lag, %11, 0xffffffff;\n"
        "setp.eq.u32 fbk, %9, 0;\n"
        "add.u32 rend, sa, 44160;\n"
        "and.b32 t, %5, 1;\n"
        "setp.eq.u32 lo, t, 0;\n"
        "mov.u32 ph, 1;\n"
        "setp.ge.u32 q, %9, 4;\n"
        "@q bra.uni PODD_%=;\n"
        "add.u32 t, rp, %4;\n"
        "ld.shared.u32 em, [t+16];\n"
        "and.b32 t, em, 0xfffffff8;\n"
        "mad.wide.u32 pa, t, 4, %1;\n"
        "add.u32 d, sa, %3;\n"
        "@lo cp.async.cg.shared.global [d+2048], [pa], 16;\n"
        "cp.async.mbarrier.arrive.noinc.shared.b64 [sa+8704];\n"
        "add.u32 rp, rp, 52;\n"
        "add.u32 sa, sa, 8832;\n"
        "PODD_%=:\n"
        "add.u32 rp, rp, 52;\n"
        "add.u32 sa, sa, 8832;\n"
        "shr.u32 t, %4, 1;\n"
        "and.b32 t, t, 4;\n"
        "add.u32 t, t, rp;\n"
        "ld.shared.u32 w, [t];\n"
        "ld.shared.u32 w2, [t+8];\n"
        "add.u32 t, rp, %4;\n"
        "ld.shared.u32 em, [t+16];\n"
        "ld.shared.u32 ey, [t+-36];\n"
        "ld.shared.u32 cu, [rp+48];\n"
        "ld.volatile.shared.u32 sv, [lag];\n"
        "setp.eq.u32 e, sa, sa;\n"
        "setp.lt.u32 q, rp, rlast;\n"
        "@!q bra.uni PF_%=;\n"
        "PL_%=:\n"
        "add.u32 cu, cu, sv;\n"
        "mov.u32 u, %%clock;\n"
        "shl.b32 u, u, 14;\n"
        "sub.u32 u, u, cu;\n"
        "setp.ge.and.s32 q, u, 0, e;\n"
        "@q bra.uni PGO_%=;\n"
        "mov.u32 n, 0;\n"
        "PW1_%=:\n"
        "@e bra.uni PW2_%=;\n"
        "mbarrier.try_wait.parity.shared.b64 e, [sa+8712], ph;\n"
        "add.u32 n, n, 1;\n"
        "setp.lt.u32 q, n, 4194304;\n"
        "@q bra.uni PW1_%=;\n"
        "trap;\n"
        "PW2_%=:\n"
        "mov.u32 u, %%clock;\n"
        "shl.b32 u, u, 14;\n"
        "sub.u32 u, u, cu;\n"
        "setp.lt.s32 q, u, 0;\n"
        "@q bra.uni PW2_%=;\n"
        "PGO_%=:\n"
        "st.volatile.shared.u32 [lag+24], u;\n"
        "and.b32 t, em, 0xfffffff8;\n"
        "mad.wide.u32 pa, t, 4, %1;\n"
        "and.b32 t, w, 0xffff;\n"
        "mad.wide.u32 pc, t, 1024, %0;\n"
        "shr.u32 t, w, 16;\n"
        "mad.wide.u32 pd, t, 1024, %0;\n"
        "add.u32 d, sa, %3;\n"
        "@lo cp.async.cg.shared.global [d+2048], [pa], 16;\n"
        "xor.b32 t, ey, %5;\n"
        "and.b32 t, t, 7;\n"
        "setp.ne.u32 zb, t, 0;\n"
        "and.b32 t, ey, 0xfffffff8;\n"
        "cvt.u64.u32 pb, t;\n"
        "add.u64 pb, pb, %2;\n"
        "selp.u32 dy, 64, 8, lo;\n"
        "xor.b32 dy, dy, d;\n"
        "cp.async.ca.shared.global [dy+2048], [pb], 8, zb;\n"
        "add.u32 d, sa, %12;\n"
        "cp.async.cg.shared.global [d+0], [pc+0], 16;\n"
        "cp.async.cg.shared.global [d+256], [pc+256], 16;\n"
        "cp.async.cg.shared.global [d+512], [pc+512], 16;\n"
        "cp.async.cg.shared.global [d+768], [pc+768], 16;\n"
        "cp.async.cg.shared.global [d+1024], [pd+0], 16;\n"
        "cp.async.cg.shared.global [d+1280], [pd+256], 16;\n"
        "cp.async.cg.shared.global [d+1536], [pd+512], 16;\n"
        "cp.async.cg.shared.global [d+1792], [pd+768], 16;\n"
        "xor.b32 dy, d, 64;\n"
        "and.b32 t, w2, 0xffff;\n"
        "mad.wide.u32 pa, t, 1024, %0;\n"
        "cp.async.cg.shared.global [dy+4352], [pa+0], 16;\n"
        "cp.async.cg.shared.global [dy+4608], [pa+256], 16;\n"
        "cp.async.cg.shared.global [dy+4864], [pa+512], 16;\n"
        "cp.async.cg.shared.global [dy+5120], [pa+768], 16;\n"
        "shr.u32 t, w2, 16;\n"
        "mad.wide.u32 pb, t, 1024, %0;\n"
        "cp.async.cg.shared.global [dy+5376], [pb+0], 16;\n"
        "cp.async.cg.shared.global [dy+5632], [pb+256], 16;\n"
        "cp.async.cg.shared.global [dy+5888], [pb+512], 16;\n"
        "cp.async.cg.shared.global [dy+6144], [pb+768], 16;\n"
        "add.u32 rp, rp, 104;\n"
        "shr.u32 t, %4, 1;\n"
        "and.b32 t, t, 4;\n"
        "add.u32 t, t, rp;\n"
        "ld.shared.u32 w, [t];\n"
        "ld.shared.u32 w2, [t+8];\n"
        "add.u32 t, rp, %4;\n"
        "ld.shared.u32 em, [t+16];\n"
        "ld.shared.u32 ey, [t+-36];\n"
        "ld.shared.u32 cu, [rp+48];\n"
        "ld.volatile.shared.u32 sv, [lag];\n"
        "cp.async.mbarrier.arrive.noinc.shared.b64 [sa+8704];\n"
        "add.u32 sa, sa, 17664;\n"
        "sub.u32 t, sa, 44160;\n"
        "setp.ge.u32 q, sa, rend;\n"
        "selp.u32 sa, t, sa, q;\n"
        "selp.u32 t, 1, 0, q;\n"
        "xor.b32 ph, ph, t;\n"
        "mbarrier.try_wait.parity.shared.b64 e, [sa+8712], ph;\n"
        "@!fbk bra.uni PC_%=;\n"
        "ld.volatile.shared.u32 u, [lag+24];\n"
        "shr.s32 u, u, 16;\n"
        "ld.volatile.shared.u64 pa, [lag+16];\n"
        "elect.sync _|z, 0xffffffff;\n"
        "@z st.relaxed.gpu.global.u32 [pa], u;\n"
        "@z cp.async.cg.shared.global [lag], [pa+16896], 16;\n"
        "PC_%=:\n"
        "setp.lt.u32 q, rp, rlast;\n"
        "@q bra.uni PL_%=;\n"
        "PF_%=:\n"
        "setp.ne.u32 q, rp, rlast;\n"
        "@q bra.uni PX_%=;\n"
        "mov.u32 n, 0;\n"
        "PE1_%=:\n"
        "@e bra.uni PE2_%=;\n"
        "mbarrier.try_wait.parity.shared.b64 e, [sa+8712], ph;\n"
        "add.u32 n, n, 1;\n"
        "setp.lt.u32 q, n, 4194304;\n"
        "@q bra.uni PE1_%=;\n"
        "trap;\n"
        "PE2_%=:\n"
        "cp.async.mbarrier.arrive.noinc.shared.b64 [sa+8704];\n"
        "PX_%=:\n"
        "}\n"
        ::"l"(xl), "l"(efl), "l"(Y), "r"(xd), "r"(oef), "r"(ysel), "r"(ring), "r"(rec), "r"(rlast), "r"(odd),
          "n"(0), "r"(lag), "r"(xh) : "memory");
}

__device__ __forceinline__ void consumer_loop(float (&acc)[5][4][2][4], const uint32_t (&wf)[4][4], const uint32_t (&cgf)[4],
                                              uint32_t xoff, uint32_t& ring, uint32_t moff, uint32_t rec) {
    asm volatile(
        "{\n"
        ".reg .b32 x<16>, a<4>, b<4>, r<4>, m<4>, rl, rh, tag, la, lb, sa, last, ph, tq, xa, ma, n, ring, sn, ln, yb, zz, k<4>, tp;\n"
        ".reg .b16 lo, hi;\n"
        ".reg .f32 p<16>, d<4>, t0, t1, fz;\n"
        ".reg .pred q, w, el, c<5>;\n"
        "TA_%=: .branchtargets A0_%=, A1_%=, A2_%=, A3_%=, A4_%=, EXIT_%=;\n"
        "TB_%=: .branchtargets B0_%=, B1_%=, B2_%=, B3_%=, B4_%=, SPIN_%=;\n"
        "mov.f32 fz, 0f00000000;\n"
        "redux.sync.or.b32 ring, %160, 0xffffffff;\n"
        "mov.u32 sa, ring;\n"
        "add.u32 last, ring, 35328;\n"
        "mov.u32 ph, 0;\n"
        "redux.sync.xor.b32 zz, %160, 0xffffffff;\n"
        "redux.sync.or.b32 tp, %183, 0xffffffff;\n"
        "elect.sync _|el, 0xffffffff;\n"
        "mov.u32 k0, sa;\n"
        "mov.u32 k1, sa;\n"
        "mov.u32 k2, sa;\n"
        "mov.u32 k3, sa;\n"
        "mov.b32 x0, 0;\n"
        "mov.b32 x1, 0;\n"
        "mov.b32 x2, 0;\n"
        "mov.b32 x3, 0;\n"
        "mov.b32 x4, 0;\n"
        "mov.b32 x5, 0;\n"
        "mov.b32 x6, 0;\n"
        "mov.b32 x7, 0;\n"
        "mov.b32 x8, 0;\n"
        "mov.b32 x9, 0;\n"
        "mov.b32 x10, 0;\n"
        "mov.b32 x11, 0;\n"
        "mov.b32 x12, 0;\n"
        "mov.b32 x13, 0;\n"
        "mov.b32 x14, 0;\n"
        "mov.b32 x15, 0;\n"
        "mov.b32 b0, 0;\n"
        "mov.b32 r0, 0;\n"
        "mov.b32 b1, 0;\n"
        "mov.b32 r1, 0;\n"
        "mov.b32 b2, 0;\n"
        "mov.b32 r2, 0;\n"
        "mov.b32 b3, 0;\n"
        "mov.b32 r3, 0;\n"
        "mov.u32 lb, 0;\n"
        "mov.u32 n, 0;\n"
        "W0_%=:\n"
        "mbarrier.try_wait.parity.shared.b64 w, [sa+8704], 0;\n"
        "@w bra.uni W0D_%=;\n"
        "add.u32 n, n, 1;\n"
        "setp.lt.u32 q, n, 4194304;\n"
        "@q bra.uni W0_%=;\n"
        "trap;\n"
        "W0D_%=:\n"
        "add.u32 ma, sa, %182;\n"
        "ldmatrix.sync.aligned.m8n8.x4.shared.b16 {m0,m1,m2,m3}, [ma];\n"
        "ld.shared.u16 tag, [tp+48];\n"
        "add.u32 tp, tp, 52;\n"
        "add.u32 sn, sa, 8832;\n"
        "setp.eq.u32 q, sa, last;\n"
        "selp.u32 sn, ring, sn, q;\n"
        "selp.u32 tq, 1, 0, q;\n"
        "xor.b32 ph, ph, tq;\n"
        "mbarrier.test_wait.parity.shared.b64 w, [sn+8704], ph;\n"
        "mma.sync.aligned.m16n8k16.row.col.f32.bf16.bf16.f32 {p0,p1,p2,p3}, {%161,%162,%163,%164}, {m2,m3}, {fz,fz,fz,fz};\n"
        "mma.sync.aligned.m16n8k16.row.col.f32.bf16.bf16.f32 {p4,p5,p6,p7}, {%165,%166,%167,%168}, {m2,m3}, {fz,fz,fz,fz};\n"
        "mma.sync.aligned.m16n8k16.row.col.f32.bf16.bf16.f32 {p8,p9,p10,p11}, {%169,%170,%171,%172}, {m2,m3}, {fz,fz,fz,fz};\n"
        "mma.sync.aligned.m16n8k16.row.col.f32.bf16.bf16.f32 {p12,p13,p14,p15}, {%173,%174,%175,%176}, {m2,m3}, {fz,fz,fz,fz};\n"
        "@el mbarrier.arrive.shared.b64 _, [k0+8712];\n"
        "redux.sync.or.b32 ln, tag, 0xffffffff;\n"
        "mov.u32 sa, sn;\n"
        "add.u32 k0, sn, zz;\n"
        "SPIN_%=:\n"
        "mov.u32 n, 0;\n"
        "SP1_%=:\n"
        "mbarrier.try_wait.parity.shared.b64 w, [sa+8704], ph;\n"
        "@w bra.uni SP2_%=;\n"
        "add.u32 n, n, 1;\n"
        "setp.lt.u32 q, n, 4194304;\n"
        "@q bra.uni SP1_%=;\n"
        "trap;\n"
        "SP2_%=:\n"
        "brx.idx.uni lb, TB_%=;\n"
        "A0_%=:\n"
        "add.u32 xa, sa, %181;\n"
        "add.u32 ma, sa, %182;\n"
        "ldmatrix.sync.aligned.m8n8.x4.shared.b16 {m0,m1,m2,m3}, [ma];\n"
        "ld.shared.u16 tag, [tp+48];\n"
        "add.u32 tp, tp, 52;\n"
        "add.u32 sn, sa, 8832;\n"
        "setp.eq.u32 q, sa, last;\n"
        "selp.u32 sn, ring, sn, q;\n"
        "selp.u32 tq, 1, 0, q;\n"
        "xor.b32 ph, ph, tq;\n"
        "mbarrier.test_wait.parity.shared.b64 w, [sn+8704], ph;\n"
        "mma.sync.aligned.m16n8k16.row.col.f32.bf16.bf16.f32 {%0,%1,%2,%3}, {a0,a1,a2,a3}, {x0,x1}, {%0,%1,%2,%3};\n"
        "mma.sync.aligned.m16n8k16.row.col.f32.bf16.bf16.f32 {%4,%5,%6,%7}, {a0,a1,a2,a3}, {x2,x3}, {%4,%5,%6,%7};\n"
        "ld.shared.v4.u32 {x0,x1,x2,x3}, [xa+1024];\n"
        "tanh.approx.f32 t0, p1;\n"
        "tanh.approx.f32 t1, p3;\n"
        "fma.rn.f32 t0, p1, t0, p1;\n"
        "fma.rn.f32 t1, p3, t1, p3;\n"
        "cvt.rn.bf16x2.f32 r0, t1, t0;\n"
        "mma.sync.aligned.m16n8k16.row.col.f32.bf16.bf16.f32 {p0,p1,p2,p3}, {%161,%162,%163,%164}, {m2,m3}, {fz,fz,fz,fz};\n"
        "mma.sync.aligned.m16n8k16.row.col.f32.bf16.bf16.f32 {%8,%9,%10,%11}, {a0,a1,a2,a3}, {x4,x5}, {%8,%9,%10,%11};\n"
        "mma.sync.aligned.m16n8k16.row.col.f32.bf16.bf16.f32 {%12,%13,%14,%15}, {a0,a1,a2,a3}, {x6,x7}, {%12,%13,%14,%15};\n"
        "ld.shared.v4.u32 {x4,x5,x6,x7}, [xa+1152];\n"
        "mma.sync.aligned.m16n8k8.row.col.f32.bf16.bf16.f32 {d0,d1,d2,d3}, {%177,%178}, {m1}, {fz,fz,fz,fz};\n"
        "cvt.rn.bf16x2.f32 b0, d2, d0;\n"
        "cvt.rn.bf16x2.f32 b1, d3, d1;\n"
        "tanh.approx.f32 t0, p5;\n"
        "tanh.approx.f32 t1, p7;\n"
        "fma.rn.f32 t0, p5, t0, p5;\n"
        "fma.rn.f32 t1, p7, t1, p7;\n"
        "cvt.rn.bf16x2.f32 r1, t1, t0;\n"
        "mma.sync.aligned.m16n8k16.row.col.f32.bf16.bf16.f32 {p4,p5,p6,p7}, {%165,%166,%167,%168}, {m2,m3}, {fz,fz,fz,fz};\n"
        "mov.b32 {lo,hi}, r2;\n"
        "mov.b32 rl, {lo,lo};\n"
        "mov.b32 rh, {hi,hi};\n"
        "mul.bf16x2 x8, x8, rl;\n"
        "mul.bf16x2 x9, x9, rl;\n"
        "mul.bf16x2 x10, x10, rh;\n"
        "mul.bf16x2 x11, x11, rh;\n"
        "mma.sync.aligned.m16n8k16.row.col.f32.bf16.bf16.f32 {%16,%17,%18,%19}, {a0,a1,a2,a3}, {x8,x9}, {%16,%17,%18,%19};\n"
        "mma.sync.aligned.m16n8k16.row.col.f32.bf16.bf16.f32 {%20,%21,%22,%23}, {a0,a1,a2,a3}, {x10,x11}, {%20,%21,%22,%23};\n"
        "ld.shared.v4.u32 {x8,x9,x10,x11}, [xa+1280];\n"
        "mma.sync.aligned.m16n8k8.row.col.f32.bf16.bf16.f32 {d0,d1,d2,d3}, {%179,%180}, {m1}, {fz,fz,fz,fz};\n"
        "cvt.rn.bf16x2.f32 b2, d2, d0;\n"
        "cvt.rn.bf16x2.f32 b3, d3, d1;\n"
        "tanh.approx.f32 t0, p9;\n"
        "tanh.approx.f32 t1, p11;\n"
        "fma.rn.f32 t0, p9, t0, p9;\n"
        "fma.rn.f32 t1, p11, t1, p11;\n"
        "cvt.rn.bf16x2.f32 r2, t1, t0;\n"
        "mma.sync.aligned.m16n8k16.row.col.f32.bf16.bf16.f32 {p8,p9,p10,p11}, {%169,%170,%171,%172}, {m2,m3}, {fz,fz,fz,fz};\n"
        "selp.u32 tq, lb, 5, w;\n"
        "mov.b32 {lo,hi}, r3;\n"
        "mov.b32 rl, {lo,lo};\n"
        "mov.b32 rh, {hi,hi};\n"
        "mul.bf16x2 x12, x12, rl;\n"
        "mul.bf16x2 x13, x13, rl;\n"
        "mul.bf16x2 x14, x14, rh;\n"
        "mul.bf16x2 x15, x15, rh;\n"
        "mma.sync.aligned.m16n8k16.row.col.f32.bf16.bf16.f32 {%24,%25,%26,%27}, {a0,a1,a2,a3}, {x12,x13}, {%24,%25,%26,%27};\n"
        "mma.sync.aligned.m16n8k16.row.col.f32.bf16.bf16.f32 {%28,%29,%30,%31}, {a0,a1,a2,a3}, {x14,x15}, {%28,%29,%30,%31};\n"
        "ld.shared.v4.u32 {x12,x13,x14,x15}, [xa+1408];\n"
        "@el mbarrier.arrive.shared.b64 _, [k0+8712];\n"
        "redux.sync.or.b32 ln, tag, 0xffffffff;\n"
        "mov.u32 sa, sn;\n"
        "add.u32 k0, sn, zz;\n"
        "tanh.approx.f32 t0, p13;\n"
        "tanh.approx.f32 t1, p15;\n"
        "fma.rn.f32 t0, p13, t0, p13;\n"
        "fma.rn.f32 t1, p15, t1, p15;\n"
        "cvt.rn.bf16x2.f32 r3, t1, t0;\n"
        "mma.sync.aligned.m16n8k16.row.col.f32.bf16.bf16.f32 {p12,p13,p14,p15}, {%173,%174,%175,%176}, {m2,m3}, {fz,fz,fz,fz};\n"
        "mov.b32 {lo,hi}, r0;\n"
        "mov.b32 rl, {lo,lo};\n"
        "mov.b32 rh, {hi,hi};\n"
        "mul.bf16x2 x0, x0, rl;\n"
        "mul.bf16x2 x1, x1, rl;\n"
        "mul.bf16x2 x2, x2, rh;\n"
        "mul.bf16x2 x3, x3, rh;\n"
        "mov.b32 {lo,hi}, r1;\n"
        "mov.b32 rl, {lo,lo};\n"
        "mov.b32 rh, {hi,hi};\n"
        "mul.bf16x2 x4, x4, rl;\n"
        "mul.bf16x2 x5, x5, rl;\n"
        "mul.bf16x2 x6, x6, rh;\n"
        "mul.bf16x2 x7, x7, rh;\n"
        "brx.idx.uni tq, TB_%=;\n"
        "A1_%=:\n"
        "add.u32 xa, sa, %181;\n"
        "add.u32 ma, sa, %182;\n"
        "ldmatrix.sync.aligned.m8n8.x4.shared.b16 {m0,m1,m2,m3}, [ma];\n"
        "ld.shared.u16 tag, [tp+48];\n"
        "add.u32 tp, tp, 52;\n"
        "add.u32 sn, sa, 8832;\n"
        "setp.eq.u32 q, sa, last;\n"
        "selp.u32 sn, ring, sn, q;\n"
        "selp.u32 tq, 1, 0, q;\n"
        "xor.b32 ph, ph, tq;\n"
        "mbarrier.test_wait.parity.shared.b64 w, [sn+8704], ph;\n"
        "mma.sync.aligned.m16n8k16.row.col.f32.bf16.bf16.f32 {%32,%33,%34,%35}, {a0,a1,a2,a3}, {x0,x1}, {%32,%33,%34,%35};\n"
        "mma.sync.aligned.m16n8k16.row.col.f32.bf16.bf16.f32 {%36,%37,%38,%39}, {a0,a1,a2,a3}, {x2,x3}, {%36,%37,%38,%39};\n"
        "ld.shared.v4.u32 {x0,x1,x2,x3}, [xa+1024];\n"
        "tanh.approx.f32 t0, p1;\n"
        "tanh.approx.f32 t1, p3;\n"
        "fma.rn.f32 t0, p1, t0, p1;\n"
        "fma.rn.f32 t1, p3, t1, p3;\n"
        "cvt.rn.bf16x2.f32 r0, t1, t0;\n"
        "mma.sync.aligned.m16n8k16.row.col.f32.bf16.bf16.f32 {p0,p1,p2,p3}, {%161,%162,%163,%164}, {m2,m3}, {fz,fz,fz,fz};\n"
        "mma.sync.aligned.m16n8k16.row.col.f32.bf16.bf16.f32 {%40,%41,%42,%43}, {a0,a1,a2,a3}, {x4,x5}, {%40,%41,%42,%43};\n"
        "mma.sync.aligned.m16n8k16.row.col.f32.bf16.bf16.f32 {%44,%45,%46,%47}, {a0,a1,a2,a3}, {x6,x7}, {%44,%45,%46,%47};\n"
        "ld.shared.v4.u32 {x4,x5,x6,x7}, [xa+1152];\n"
        "mma.sync.aligned.m16n8k8.row.col.f32.bf16.bf16.f32 {d0,d1,d2,d3}, {%177,%178}, {m1}, {fz,fz,fz,fz};\n"
        "cvt.rn.bf16x2.f32 b0, d2, d0;\n"
        "cvt.rn.bf16x2.f32 b1, d3, d1;\n"
        "tanh.approx.f32 t0, p5;\n"
        "tanh.approx.f32 t1, p7;\n"
        "fma.rn.f32 t0, p5, t0, p5;\n"
        "fma.rn.f32 t1, p7, t1, p7;\n"
        "cvt.rn.bf16x2.f32 r1, t1, t0;\n"
        "mma.sync.aligned.m16n8k16.row.col.f32.bf16.bf16.f32 {p4,p5,p6,p7}, {%165,%166,%167,%168}, {m2,m3}, {fz,fz,fz,fz};\n"
        "mov.b32 {lo,hi}, r2;\n"
        "mov.b32 rl, {lo,lo};\n"
        "mov.b32 rh, {hi,hi};\n"
        "mul.bf16x2 x8, x8, rl;\n"
        "mul.bf16x2 x9, x9, rl;\n"
        "mul.bf16x2 x10, x10, rh;\n"
        "mul.bf16x2 x11, x11, rh;\n"
        "mma.sync.aligned.m16n8k16.row.col.f32.bf16.bf16.f32 {%48,%49,%50,%51}, {a0,a1,a2,a3}, {x8,x9}, {%48,%49,%50,%51};\n"
        "mma.sync.aligned.m16n8k16.row.col.f32.bf16.bf16.f32 {%52,%53,%54,%55}, {a0,a1,a2,a3}, {x10,x11}, {%52,%53,%54,%55};\n"
        "ld.shared.v4.u32 {x8,x9,x10,x11}, [xa+1280];\n"
        "mma.sync.aligned.m16n8k8.row.col.f32.bf16.bf16.f32 {d0,d1,d2,d3}, {%179,%180}, {m1}, {fz,fz,fz,fz};\n"
        "cvt.rn.bf16x2.f32 b2, d2, d0;\n"
        "cvt.rn.bf16x2.f32 b3, d3, d1;\n"
        "tanh.approx.f32 t0, p9;\n"
        "tanh.approx.f32 t1, p11;\n"
        "fma.rn.f32 t0, p9, t0, p9;\n"
        "fma.rn.f32 t1, p11, t1, p11;\n"
        "cvt.rn.bf16x2.f32 r2, t1, t0;\n"
        "mma.sync.aligned.m16n8k16.row.col.f32.bf16.bf16.f32 {p8,p9,p10,p11}, {%169,%170,%171,%172}, {m2,m3}, {fz,fz,fz,fz};\n"
        "selp.u32 tq, lb, 5, w;\n"
        "mov.b32 {lo,hi}, r3;\n"
        "mov.b32 rl, {lo,lo};\n"
        "mov.b32 rh, {hi,hi};\n"
        "mul.bf16x2 x12, x12, rl;\n"
        "mul.bf16x2 x13, x13, rl;\n"
        "mul.bf16x2 x14, x14, rh;\n"
        "mul.bf16x2 x15, x15, rh;\n"
        "mma.sync.aligned.m16n8k16.row.col.f32.bf16.bf16.f32 {%56,%57,%58,%59}, {a0,a1,a2,a3}, {x12,x13}, {%56,%57,%58,%59};\n"
        "mma.sync.aligned.m16n8k16.row.col.f32.bf16.bf16.f32 {%60,%61,%62,%63}, {a0,a1,a2,a3}, {x14,x15}, {%60,%61,%62,%63};\n"
        "ld.shared.v4.u32 {x12,x13,x14,x15}, [xa+1408];\n"
        "@el mbarrier.arrive.shared.b64 _, [k0+8712];\n"
        "redux.sync.or.b32 ln, tag, 0xffffffff;\n"
        "mov.u32 sa, sn;\n"
        "add.u32 k0, sn, zz;\n"
        "tanh.approx.f32 t0, p13;\n"
        "tanh.approx.f32 t1, p15;\n"
        "fma.rn.f32 t0, p13, t0, p13;\n"
        "fma.rn.f32 t1, p15, t1, p15;\n"
        "cvt.rn.bf16x2.f32 r3, t1, t0;\n"
        "mma.sync.aligned.m16n8k16.row.col.f32.bf16.bf16.f32 {p12,p13,p14,p15}, {%173,%174,%175,%176}, {m2,m3}, {fz,fz,fz,fz};\n"
        "mov.b32 {lo,hi}, r0;\n"
        "mov.b32 rl, {lo,lo};\n"
        "mov.b32 rh, {hi,hi};\n"
        "mul.bf16x2 x0, x0, rl;\n"
        "mul.bf16x2 x1, x1, rl;\n"
        "mul.bf16x2 x2, x2, rh;\n"
        "mul.bf16x2 x3, x3, rh;\n"
        "mov.b32 {lo,hi}, r1;\n"
        "mov.b32 rl, {lo,lo};\n"
        "mov.b32 rh, {hi,hi};\n"
        "mul.bf16x2 x4, x4, rl;\n"
        "mul.bf16x2 x5, x5, rl;\n"
        "mul.bf16x2 x6, x6, rh;\n"
        "mul.bf16x2 x7, x7, rh;\n"
        "brx.idx.uni tq, TB_%=;\n"
        "A2_%=:\n"
        "add.u32 xa, sa, %181;\n"
        "add.u32 ma, sa, %182;\n"
        "ldmatrix.sync.aligned.m8n8.x4.shared.b16 {m0,m1,m2,m3}, [ma];\n"
        "ld.shared.u16 tag, [tp+48];\n"
        "add.u32 tp, tp, 52;\n"
        "add.u32 sn, sa, 8832;\n"
        "setp.eq.u32 q, sa, last;\n"
        "selp.u32 sn, ring, sn, q;\n"
        "selp.u32 tq, 1, 0, q;\n"
        "xor.b32 ph, ph, tq;\n"
        "mbarrier.test_wait.parity.shared.b64 w, [sn+8704], ph;\n"
        "mma.sync.aligned.m16n8k16.row.col.f32.bf16.bf16.f32 {%64,%65,%66,%67}, {a0,a1,a2,a3}, {x0,x1}, {%64,%65,%66,%67};\n"
        "mma.sync.aligned.m16n8k16.row.col.f32.bf16.bf16.f32 {%68,%69,%70,%71}, {a0,a1,a2,a3}, {x2,x3}, {%68,%69,%70,%71};\n"
        "ld.shared.v4.u32 {x0,x1,x2,x3}, [xa+1024];\n"
        "tanh.approx.f32 t0, p1;\n"
        "tanh.approx.f32 t1, p3;\n"
        "fma.rn.f32 t0, p1, t0, p1;\n"
        "fma.rn.f32 t1, p3, t1, p3;\n"
        "cvt.rn.bf16x2.f32 r0, t1, t0;\n"
        "mma.sync.aligned.m16n8k16.row.col.f32.bf16.bf16.f32 {p0,p1,p2,p3}, {%161,%162,%163,%164}, {m2,m3}, {fz,fz,fz,fz};\n"
        "mma.sync.aligned.m16n8k16.row.col.f32.bf16.bf16.f32 {%72,%73,%74,%75}, {a0,a1,a2,a3}, {x4,x5}, {%72,%73,%74,%75};\n"
        "mma.sync.aligned.m16n8k16.row.col.f32.bf16.bf16.f32 {%76,%77,%78,%79}, {a0,a1,a2,a3}, {x6,x7}, {%76,%77,%78,%79};\n"
        "ld.shared.v4.u32 {x4,x5,x6,x7}, [xa+1152];\n"
        "mma.sync.aligned.m16n8k8.row.col.f32.bf16.bf16.f32 {d0,d1,d2,d3}, {%177,%178}, {m1}, {fz,fz,fz,fz};\n"
        "cvt.rn.bf16x2.f32 b0, d2, d0;\n"
        "cvt.rn.bf16x2.f32 b1, d3, d1;\n"
        "tanh.approx.f32 t0, p5;\n"
        "tanh.approx.f32 t1, p7;\n"
        "fma.rn.f32 t0, p5, t0, p5;\n"
        "fma.rn.f32 t1, p7, t1, p7;\n"
        "cvt.rn.bf16x2.f32 r1, t1, t0;\n"
        "mma.sync.aligned.m16n8k16.row.col.f32.bf16.bf16.f32 {p4,p5,p6,p7}, {%165,%166,%167,%168}, {m2,m3}, {fz,fz,fz,fz};\n"
        "mov.b32 {lo,hi}, r2;\n"
        "mov.b32 rl, {lo,lo};\n"
        "mov.b32 rh, {hi,hi};\n"
        "mul.bf16x2 x8, x8, rl;\n"
        "mul.bf16x2 x9, x9, rl;\n"
        "mul.bf16x2 x10, x10, rh;\n"
        "mul.bf16x2 x11, x11, rh;\n"
        "mma.sync.aligned.m16n8k16.row.col.f32.bf16.bf16.f32 {%80,%81,%82,%83}, {a0,a1,a2,a3}, {x8,x9}, {%80,%81,%82,%83};\n"
        "mma.sync.aligned.m16n8k16.row.col.f32.bf16.bf16.f32 {%84,%85,%86,%87}, {a0,a1,a2,a3}, {x10,x11}, {%84,%85,%86,%87};\n"
        "ld.shared.v4.u32 {x8,x9,x10,x11}, [xa+1280];\n"
        "mma.sync.aligned.m16n8k8.row.col.f32.bf16.bf16.f32 {d0,d1,d2,d3}, {%179,%180}, {m1}, {fz,fz,fz,fz};\n"
        "cvt.rn.bf16x2.f32 b2, d2, d0;\n"
        "cvt.rn.bf16x2.f32 b3, d3, d1;\n"
        "tanh.approx.f32 t0, p9;\n"
        "tanh.approx.f32 t1, p11;\n"
        "fma.rn.f32 t0, p9, t0, p9;\n"
        "fma.rn.f32 t1, p11, t1, p11;\n"
        "cvt.rn.bf16x2.f32 r2, t1, t0;\n"
        "mma.sync.aligned.m16n8k16.row.col.f32.bf16.bf16.f32 {p8,p9,p10,p11}, {%169,%170,%171,%172}, {m2,m3}, {fz,fz,fz,fz};\n"
        "selp.u32 tq, lb, 5, w;\n"
        "mov.b32 {lo,hi}, r3;\n"
        "mov.b32 rl, {lo,lo};\n"
        "mov.b32 rh, {hi,hi};\n"
        "mul.bf16x2 x12, x12, rl;\n"
        "mul.bf16x2 x13, x13, rl;\n"
        "mul.bf16x2 x14, x14, rh;\n"
        "mul.bf16x2 x15, x15, rh;\n"
        "mma.sync.aligned.m16n8k16.row.col.f32.bf16.bf16.f32 {%88,%89,%90,%91}, {a0,a1,a2,a3}, {x12,x13}, {%88,%89,%90,%91};\n"
        "mma.sync.aligned.m16n8k16.row.col.f32.bf16.bf16.f32 {%92,%93,%94,%95}, {a0,a1,a2,a3}, {x14,x15}, {%92,%93,%94,%95};\n"
        "ld.shared.v4.u32 {x12,x13,x14,x15}, [xa+1408];\n"
        "@el mbarrier.arrive.shared.b64 _, [k0+8712];\n"
        "redux.sync.or.b32 ln, tag, 0xffffffff;\n"
        "mov.u32 sa, sn;\n"
        "add.u32 k0, sn, zz;\n"
        "tanh.approx.f32 t0, p13;\n"
        "tanh.approx.f32 t1, p15;\n"
        "fma.rn.f32 t0, p13, t0, p13;\n"
        "fma.rn.f32 t1, p15, t1, p15;\n"
        "cvt.rn.bf16x2.f32 r3, t1, t0;\n"
        "mma.sync.aligned.m16n8k16.row.col.f32.bf16.bf16.f32 {p12,p13,p14,p15}, {%173,%174,%175,%176}, {m2,m3}, {fz,fz,fz,fz};\n"
        "mov.b32 {lo,hi}, r0;\n"
        "mov.b32 rl, {lo,lo};\n"
        "mov.b32 rh, {hi,hi};\n"
        "mul.bf16x2 x0, x0, rl;\n"
        "mul.bf16x2 x1, x1, rl;\n"
        "mul.bf16x2 x2, x2, rh;\n"
        "mul.bf16x2 x3, x3, rh;\n"
        "mov.b32 {lo,hi}, r1;\n"
        "mov.b32 rl, {lo,lo};\n"
        "mov.b32 rh, {hi,hi};\n"
        "mul.bf16x2 x4, x4, rl;\n"
        "mul.bf16x2 x5, x5, rl;\n"
        "mul.bf16x2 x6, x6, rh;\n"
        "mul.bf16x2 x7, x7, rh;\n"
        "brx.idx.uni tq, TB_%=;\n"
        "A3_%=:\n"
        "add.u32 xa, sa, %181;\n"
        "add.u32 ma, sa, %182;\n"
        "ldmatrix.sync.aligned.m8n8.x4.shared.b16 {m0,m1,m2,m3}, [ma];\n"
        "ld.shared.u16 tag, [tp+48];\n"
        "add.u32 tp, tp, 52;\n"
        "add.u32 sn, sa, 8832;\n"
        "setp.eq.u32 q, sa, last;\n"
        "selp.u32 sn, ring, sn, q;\n"
        "selp.u32 tq, 1, 0, q;\n"
        "xor.b32 ph, ph, tq;\n"
        "mbarrier.test_wait.parity.shared.b64 w, [sn+8704], ph;\n"
        "mma.sync.aligned.m16n8k16.row.col.f32.bf16.bf16.f32 {%96,%97,%98,%99}, {a0,a1,a2,a3}, {x0,x1}, {%96,%97,%98,%99};\n"
        "mma.sync.aligned.m16n8k16.row.col.f32.bf16.bf16.f32 {%100,%101,%102,%103}, {a0,a1,a2,a3}, {x2,x3}, {%100,%101,%102,%103};\n"
        "ld.shared.v4.u32 {x0,x1,x2,x3}, [xa+1024];\n"
        "tanh.approx.f32 t0, p1;\n"
        "tanh.approx.f32 t1, p3;\n"
        "fma.rn.f32 t0, p1, t0, p1;\n"
        "fma.rn.f32 t1, p3, t1, p3;\n"
        "cvt.rn.bf16x2.f32 r0, t1, t0;\n"
        "mma.sync.aligned.m16n8k16.row.col.f32.bf16.bf16.f32 {p0,p1,p2,p3}, {%161,%162,%163,%164}, {m2,m3}, {fz,fz,fz,fz};\n"
        "mma.sync.aligned.m16n8k16.row.col.f32.bf16.bf16.f32 {%104,%105,%106,%107}, {a0,a1,a2,a3}, {x4,x5}, {%104,%105,%106,%107};\n"
        "mma.sync.aligned.m16n8k16.row.col.f32.bf16.bf16.f32 {%108,%109,%110,%111}, {a0,a1,a2,a3}, {x6,x7}, {%108,%109,%110,%111};\n"
        "ld.shared.v4.u32 {x4,x5,x6,x7}, [xa+1152];\n"
        "mma.sync.aligned.m16n8k8.row.col.f32.bf16.bf16.f32 {d0,d1,d2,d3}, {%177,%178}, {m1}, {fz,fz,fz,fz};\n"
        "cvt.rn.bf16x2.f32 b0, d2, d0;\n"
        "cvt.rn.bf16x2.f32 b1, d3, d1;\n"
        "tanh.approx.f32 t0, p5;\n"
        "tanh.approx.f32 t1, p7;\n"
        "fma.rn.f32 t0, p5, t0, p5;\n"
        "fma.rn.f32 t1, p7, t1, p7;\n"
        "cvt.rn.bf16x2.f32 r1, t1, t0;\n"
        "mma.sync.aligned.m16n8k16.row.col.f32.bf16.bf16.f32 {p4,p5,p6,p7}, {%165,%166,%167,%168}, {m2,m3}, {fz,fz,fz,fz};\n"
        "mov.b32 {lo,hi}, r2;\n"
        "mov.b32 rl, {lo,lo};\n"
        "mov.b32 rh, {hi,hi};\n"
        "mul.bf16x2 x8, x8, rl;\n"
        "mul.bf16x2 x9, x9, rl;\n"
        "mul.bf16x2 x10, x10, rh;\n"
        "mul.bf16x2 x11, x11, rh;\n"
        "mma.sync.aligned.m16n8k16.row.col.f32.bf16.bf16.f32 {%112,%113,%114,%115}, {a0,a1,a2,a3}, {x8,x9}, {%112,%113,%114,%115};\n"
        "mma.sync.aligned.m16n8k16.row.col.f32.bf16.bf16.f32 {%116,%117,%118,%119}, {a0,a1,a2,a3}, {x10,x11}, {%116,%117,%118,%119};\n"
        "ld.shared.v4.u32 {x8,x9,x10,x11}, [xa+1280];\n"
        "mma.sync.aligned.m16n8k8.row.col.f32.bf16.bf16.f32 {d0,d1,d2,d3}, {%179,%180}, {m1}, {fz,fz,fz,fz};\n"
        "cvt.rn.bf16x2.f32 b2, d2, d0;\n"
        "cvt.rn.bf16x2.f32 b3, d3, d1;\n"
        "tanh.approx.f32 t0, p9;\n"
        "tanh.approx.f32 t1, p11;\n"
        "fma.rn.f32 t0, p9, t0, p9;\n"
        "fma.rn.f32 t1, p11, t1, p11;\n"
        "cvt.rn.bf16x2.f32 r2, t1, t0;\n"
        "mma.sync.aligned.m16n8k16.row.col.f32.bf16.bf16.f32 {p8,p9,p10,p11}, {%169,%170,%171,%172}, {m2,m3}, {fz,fz,fz,fz};\n"
        "selp.u32 tq, lb, 5, w;\n"
        "mov.b32 {lo,hi}, r3;\n"
        "mov.b32 rl, {lo,lo};\n"
        "mov.b32 rh, {hi,hi};\n"
        "mul.bf16x2 x12, x12, rl;\n"
        "mul.bf16x2 x13, x13, rl;\n"
        "mul.bf16x2 x14, x14, rh;\n"
        "mul.bf16x2 x15, x15, rh;\n"
        "mma.sync.aligned.m16n8k16.row.col.f32.bf16.bf16.f32 {%120,%121,%122,%123}, {a0,a1,a2,a3}, {x12,x13}, {%120,%121,%122,%123};\n"
        "mma.sync.aligned.m16n8k16.row.col.f32.bf16.bf16.f32 {%124,%125,%126,%127}, {a0,a1,a2,a3}, {x14,x15}, {%124,%125,%126,%127};\n"
        "ld.shared.v4.u32 {x12,x13,x14,x15}, [xa+1408];\n"
        "@el mbarrier.arrive.shared.b64 _, [k0+8712];\n"
        "redux.sync.or.b32 ln, tag, 0xffffffff;\n"
        "mov.u32 sa, sn;\n"
        "add.u32 k0, sn, zz;\n"
        "tanh.approx.f32 t0, p13;\n"
        "tanh.approx.f32 t1, p15;\n"
        "fma.rn.f32 t0, p13, t0, p13;\n"
        "fma.rn.f32 t1, p15, t1, p15;\n"
        "cvt.rn.bf16x2.f32 r3, t1, t0;\n"
        "mma.sync.aligned.m16n8k16.row.col.f32.bf16.bf16.f32 {p12,p13,p14,p15}, {%173,%174,%175,%176}, {m2,m3}, {fz,fz,fz,fz};\n"
        "mov.b32 {lo,hi}, r0;\n"
        "mov.b32 rl, {lo,lo};\n"
        "mov.b32 rh, {hi,hi};\n"
        "mul.bf16x2 x0, x0, rl;\n"
        "mul.bf16x2 x1, x1, rl;\n"
        "mul.bf16x2 x2, x2, rh;\n"
        "mul.bf16x2 x3, x3, rh;\n"
        "mov.b32 {lo,hi}, r1;\n"
        "mov.b32 rl, {lo,lo};\n"
        "mov.b32 rh, {hi,hi};\n"
        "mul.bf16x2 x4, x4, rl;\n"
        "mul.bf16x2 x5, x5, rl;\n"
        "mul.bf16x2 x6, x6, rh;\n"
        "mul.bf16x2 x7, x7, rh;\n"
        "brx.idx.uni tq, TB_%=;\n"
        "A4_%=:\n"
        "add.u32 xa, sa, %181;\n"
        "add.u32 ma, sa, %182;\n"
        "ldmatrix.sync.aligned.m8n8.x4.shared.b16 {m0,m1,m2,m3}, [ma];\n"
        "ld.shared.u16 tag, [tp+48];\n"
        "add.u32 tp, tp, 52;\n"
        "add.u32 sn, sa, 8832;\n"
        "setp.eq.u32 q, sa, last;\n"
        "selp.u32 sn, ring, sn, q;\n"
        "selp.u32 tq, 1, 0, q;\n"
        "xor.b32 ph, ph, tq;\n"
        "mbarrier.test_wait.parity.shared.b64 w, [sn+8704], ph;\n"
        "mma.sync.aligned.m16n8k16.row.col.f32.bf16.bf16.f32 {%128,%129,%130,%131}, {a0,a1,a2,a3}, {x0,x1}, {%128,%129,%130,%131};\n"
        "mma.sync.aligned.m16n8k16.row.col.f32.bf16.bf16.f32 {%132,%133,%134,%135}, {a0,a1,a2,a3}, {x2,x3}, {%132,%133,%134,%135};\n"
        "ld.shared.v4.u32 {x0,x1,x2,x3}, [xa+1024];\n"
        "tanh.approx.f32 t0, p1;\n"
        "tanh.approx.f32 t1, p3;\n"
        "fma.rn.f32 t0, p1, t0, p1;\n"
        "fma.rn.f32 t1, p3, t1, p3;\n"
        "cvt.rn.bf16x2.f32 r0, t1, t0;\n"
        "mma.sync.aligned.m16n8k16.row.col.f32.bf16.bf16.f32 {p0,p1,p2,p3}, {%161,%162,%163,%164}, {m2,m3}, {fz,fz,fz,fz};\n"
        "mma.sync.aligned.m16n8k16.row.col.f32.bf16.bf16.f32 {%136,%137,%138,%139}, {a0,a1,a2,a3}, {x4,x5}, {%136,%137,%138,%139};\n"
        "mma.sync.aligned.m16n8k16.row.col.f32.bf16.bf16.f32 {%140,%141,%142,%143}, {a0,a1,a2,a3}, {x6,x7}, {%140,%141,%142,%143};\n"
        "ld.shared.v4.u32 {x4,x5,x6,x7}, [xa+1152];\n"
        "mma.sync.aligned.m16n8k8.row.col.f32.bf16.bf16.f32 {d0,d1,d2,d3}, {%177,%178}, {m1}, {fz,fz,fz,fz};\n"
        "cvt.rn.bf16x2.f32 b0, d2, d0;\n"
        "cvt.rn.bf16x2.f32 b1, d3, d1;\n"
        "tanh.approx.f32 t0, p5;\n"
        "tanh.approx.f32 t1, p7;\n"
        "fma.rn.f32 t0, p5, t0, p5;\n"
        "fma.rn.f32 t1, p7, t1, p7;\n"
        "cvt.rn.bf16x2.f32 r1, t1, t0;\n"
        "mma.sync.aligned.m16n8k16.row.col.f32.bf16.bf16.f32 {p4,p5,p6,p7}, {%165,%166,%167,%168}, {m2,m3}, {fz,fz,fz,fz};\n"
        "mov.b32 {lo,hi}, r2;\n"
        "mov.b32 rl, {lo,lo};\n"
        "mov.b32 rh, {hi,hi};\n"
        "mul.bf16x2 x8, x8, rl;\n"
        "mul.bf16x2 x9, x9, rl;\n"
        "mul.bf16x2 x10, x10, rh;\n"
        "mul.bf16x2 x11, x11, rh;\n"
        "mma.sync.aligned.m16n8k16.row.col.f32.bf16.bf16.f32 {%144,%145,%146,%147}, {a0,a1,a2,a3}, {x8,x9}, {%144,%145,%146,%147};\n"
        "mma.sync.aligned.m16n8k16.row.col.f32.bf16.bf16.f32 {%148,%149,%150,%151}, {a0,a1,a2,a3}, {x10,x11}, {%148,%149,%150,%151};\n"
        "ld.shared.v4.u32 {x8,x9,x10,x11}, [xa+1280];\n"
        "mma.sync.aligned.m16n8k8.row.col.f32.bf16.bf16.f32 {d0,d1,d2,d3}, {%179,%180}, {m1}, {fz,fz,fz,fz};\n"
        "cvt.rn.bf16x2.f32 b2, d2, d0;\n"
        "cvt.rn.bf16x2.f32 b3, d3, d1;\n"
        "tanh.approx.f32 t0, p9;\n"
        "tanh.approx.f32 t1, p11;\n"
        "fma.rn.f32 t0, p9, t0, p9;\n"
        "fma.rn.f32 t1, p11, t1, p11;\n"
        "cvt.rn.bf16x2.f32 r2, t1, t0;\n"
        "mma.sync.aligned.m16n8k16.row.col.f32.bf16.bf16.f32 {p8,p9,p10,p11}, {%169,%170,%171,%172}, {m2,m3}, {fz,fz,fz,fz};\n"
        "selp.u32 tq, lb, 5, w;\n"
        "mov.b32 {lo,hi}, r3;\n"
        "mov.b32 rl, {lo,lo};\n"
        "mov.b32 rh, {hi,hi};\n"
        "mul.bf16x2 x12, x12, rl;\n"
        "mul.bf16x2 x13, x13, rl;\n"
        "mul.bf16x2 x14, x14, rh;\n"
        "mul.bf16x2 x15, x15, rh;\n"
        "mma.sync.aligned.m16n8k16.row.col.f32.bf16.bf16.f32 {%152,%153,%154,%155}, {a0,a1,a2,a3}, {x12,x13}, {%152,%153,%154,%155};\n"
        "mma.sync.aligned.m16n8k16.row.col.f32.bf16.bf16.f32 {%156,%157,%158,%159}, {a0,a1,a2,a3}, {x14,x15}, {%156,%157,%158,%159};\n"
        "ld.shared.v4.u32 {x12,x13,x14,x15}, [xa+1408];\n"
        "@el mbarrier.arrive.shared.b64 _, [k0+8712];\n"
        "redux.sync.or.b32 ln, tag, 0xffffffff;\n"
        "mov.u32 sa, sn;\n"
        "add.u32 k0, sn, zz;\n"
        "tanh.approx.f32 t0, p13;\n"
        "tanh.approx.f32 t1, p15;\n"
        "fma.rn.f32 t0, p13, t0, p13;\n"
        "fma.rn.f32 t1, p15, t1, p15;\n"
        "cvt.rn.bf16x2.f32 r3, t1, t0;\n"
        "mma.sync.aligned.m16n8k16.row.col.f32.bf16.bf16.f32 {p12,p13,p14,p15}, {%173,%174,%175,%176}, {m2,m3}, {fz,fz,fz,fz};\n"
        "mov.b32 {lo,hi}, r0;\n"
        "mov.b32 rl, {lo,lo};\n"
        "mov.b32 rh, {hi,hi};\n"
        "mul.bf16x2 x0, x0, rl;\n"
        "mul.bf16x2 x1, x1, rl;\n"
        "mul.bf16x2 x2, x2, rh;\n"
        "mul.bf16x2 x3, x3, rh;\n"
        "mov.b32 {lo,hi}, r1;\n"
        "mov.b32 rl, {lo,lo};\n"
        "mov.b32 rh, {hi,hi};\n"
        "mul.bf16x2 x4, x4, rl;\n"
        "mul.bf16x2 x5, x5, rl;\n"
        "mul.bf16x2 x6, x6, rh;\n"
        "mul.bf16x2 x7, x7, rh;\n"
        "brx.idx.uni tq, TB_%=;\n"
        "B0_%=:\n"
        "and.b32 la, ln, 255;\n"
        "shr.u32 lb, ln, 8;\n"
        "add.u32 ma, sa, %182;\n"
        "ldmatrix.sync.aligned.m8n8.x1.shared.b16 {yb}, [ma];\n"
        "add.u32 xa, sa, %181;\n"
        "mma.sync.aligned.m16n8k16.row.col.f32.bf16.bf16.f32 {%0,%1,%2,%3}, {b0,b1,b2,b3}, {x0,x1}, {%0,%1,%2,%3};\n"
        "mma.sync.aligned.m16n8k16.row.col.f32.bf16.bf16.f32 {%4,%5,%6,%7}, {b0,b1,b2,b3}, {x2,x3}, {%4,%5,%6,%7};\n"
        "ld.shared.v4.u32 {x0,x1,x2,x3}, [xa+0];\n"
        "tanh.approx.f32 t0, p0;\n"
        "tanh.approx.f32 t1, p2;\n"
        "fma.rn.f32 t0, p0, t0, p0;\n"
        "fma.rn.f32 t1, p2, t1, p2;\n"
        "cvt.rn.bf16x2.f32 r0, t1, t0;\n"
        "mma.sync.aligned.m16n8k16.row.col.f32.bf16.bf16.f32 {%8,%9,%10,%11}, {b0,b1,b2,b3}, {x4,x5}, {%8,%9,%10,%11};\n"
        "mma.sync.aligned.m16n8k16.row.col.f32.bf16.bf16.f32 {%12,%13,%14,%15}, {b0,b1,b2,b3}, {x6,x7}, {%12,%13,%14,%15};\n"
        "ld.shared.v4.u32 {x4,x5,x6,x7}, [xa+128];\n"
        "tanh.approx.f32 t0, p4;\n"
        "tanh.approx.f32 t1, p6;\n"
        "fma.rn.f32 t0, p4, t0, p4;\n"
        "fma.rn.f32 t1, p6, t1, p6;\n"
        "cvt.rn.bf16x2.f32 r1, t1, t0;\n"
        "mma.sync.aligned.m16n8k8.row.col.f32.bf16.bf16.f32 {d0,d1,d2,d3}, {%177,%178}, {yb}, {fz,fz,fz,fz};\n"
        "cvt.rn.bf16x2.f32 a0, d2, d0;\n"
        "cvt.rn.bf16x2.f32 a1, d3, d1;\n"
        "mov.b32 {lo,hi}, r2;\n"
        "mov.b32 rl, {lo,lo};\n"
        "mov.b32 rh, {hi,hi};\n"
        "mul.bf16x2 x8, x8, rl;\n"
        "mul.bf16x2 x9, x9, rl;\n"
        "mul.bf16x2 x10, x10, rh;\n"
        "mul.bf16x2 x11, x11, rh;\n"
        "mma.sync.aligned.m16n8k16.row.col.f32.bf16.bf16.f32 {%16,%17,%18,%19}, {b0,b1,b2,b3}, {x8,x9}, {%16,%17,%18,%19};\n"
        "mma.sync.aligned.m16n8k16.row.col.f32.bf16.bf16.f32 {%20,%21,%22,%23}, {b0,b1,b2,b3}, {x10,x11}, {%20,%21,%22,%23};\n"
        "ld.shared.v4.u32 {x8,x9,x10,x11}, [xa+256];\n"
        "tanh.approx.f32 t0, p8;\n"
        "tanh.approx.f32 t1, p10;\n"
        "fma.rn.f32 t0, p8, t0, p8;\n"
        "fma.rn.f32 t1, p10, t1, p10;\n"
        "cvt.rn.bf16x2.f32 r2, t1, t0;\n"
        "mma.sync.aligned.m16n8k8.row.col.f32.bf16.bf16.f32 {d0,d1,d2,d3}, {%179,%180}, {yb}, {fz,fz,fz,fz};\n"
        "cvt.rn.bf16x2.f32 a2, d2, d0;\n"
        "cvt.rn.bf16x2.f32 a3, d3, d1;\n"
        "mov.b32 {lo,hi}, r3;\n"
        "mov.b32 rl, {lo,lo};\n"
        "mov.b32 rh, {hi,hi};\n"
        "mul.bf16x2 x12, x12, rl;\n"
        "mul.bf16x2 x13, x13, rl;\n"
        "mul.bf16x2 x14, x14, rh;\n"
        "mul.bf16x2 x15, x15, rh;\n"
        "mma.sync.aligned.m16n8k16.row.col.f32.bf16.bf16.f32 {%24,%25,%26,%27}, {b0,b1,b2,b3}, {x12,x13}, {%24,%25,%26,%27};\n"
        "mma.sync.aligned.m16n8k16.row.col.f32.bf16.bf16.f32 {%28,%29,%30,%31}, {b0,b1,b2,b3}, {x14,x15}, {%28,%29,%30,%31};\n"
        "ld.shared.v4.u32 {x12,x13,x14,x15}, [xa+384];\n"
        "tanh.approx.f32 t0, p12;\n"
        "tanh.approx.f32 t1, p14;\n"
        "fma.rn.f32 t0, p12, t0, p12;\n"
        "fma.rn.f32 t1, p14, t1, p14;\n"
        "cvt.rn.bf16x2.f32 r3, t1, t0;\n"
        "mov.b32 {lo,hi}, r0;\n"
        "mov.b32 rl, {lo,lo};\n"
        "mov.b32 rh, {hi,hi};\n"
        "mul.bf16x2 x0, x0, rl;\n"
        "mul.bf16x2 x1, x1, rl;\n"
        "mul.bf16x2 x2, x2, rh;\n"
        "mul.bf16x2 x3, x3, rh;\n"
        "mov.b32 {lo,hi}, r1;\n"
        "mov.b32 rl, {lo,lo};\n"
        "mov.b32 rh, {hi,hi};\n"
        "mul.bf16x2 x4, x4, rl;\n"
        "mul.bf16x2 x5, x5, rl;\n"
        "mul.bf16x2 x6, x6, rh;\n"
        "mul.bf16x2 x7, x7, rh;\n"
        "brx.idx.uni la, TA_%=;\n"
        "B1_%=:\n"
        "and.b32 la, ln, 255;\n"
        "shr.u32 lb, ln, 8;\n"
        "add.u32 ma, sa, %182;\n"
        "ldmatrix.sync.aligned.m8n8.x1.shared.b16 {yb}, [ma];\n"
        "add.u32 xa, sa, %181;\n"
        "mma.sync.aligned.m16n8k16.row.col.f32.bf16.bf16.f32 {%32,%33,%34,%35}, {b0,b1,b2,b3}, {x0,x1}, {%32,%33,%34,%35};\n"
        "mma.sync.aligned.m16n8k16.row.col.f32.bf16.bf16.f32 {%36,%37,%38,%39}, {b0,b1,b2,b3}, {x2,x3}, {%36,%37,%38,%39};\n"
        "ld.shared.v4.u32 {x0,x1,x2,x3}, [xa+0];\n"
        "tanh.approx.f32 t0, p0;\n"
        "tanh.approx.f32 t1, p2;\n"
        "fma.rn.f32 t0, p0, t0, p0;\n"
        "fma.rn.f32 t1, p2, t1, p2;\n"
        "cvt.rn.bf16x2.f32 r0, t1, t0;\n"
        "mma.sync.aligned.m16n8k16.row.col.f32.bf16.bf16.f32 {%40,%41,%42,%43}, {b0,b1,b2,b3}, {x4,x5}, {%40,%41,%42,%43};\n"
        "mma.sync.aligned.m16n8k16.row.col.f32.bf16.bf16.f32 {%44,%45,%46,%47}, {b0,b1,b2,b3}, {x6,x7}, {%44,%45,%46,%47};\n"
        "ld.shared.v4.u32 {x4,x5,x6,x7}, [xa+128];\n"
        "tanh.approx.f32 t0, p4;\n"
        "tanh.approx.f32 t1, p6;\n"
        "fma.rn.f32 t0, p4, t0, p4;\n"
        "fma.rn.f32 t1, p6, t1, p6;\n"
        "cvt.rn.bf16x2.f32 r1, t1, t0;\n"
        "mma.sync.aligned.m16n8k8.row.col.f32.bf16.bf16.f32 {d0,d1,d2,d3}, {%177,%178}, {yb}, {fz,fz,fz,fz};\n"
        "cvt.rn.bf16x2.f32 a0, d2, d0;\n"
        "cvt.rn.bf16x2.f32 a1, d3, d1;\n"
        "mov.b32 {lo,hi}, r2;\n"
        "mov.b32 rl, {lo,lo};\n"
        "mov.b32 rh, {hi,hi};\n"
        "mul.bf16x2 x8, x8, rl;\n"
        "mul.bf16x2 x9, x9, rl;\n"
        "mul.bf16x2 x10, x10, rh;\n"
        "mul.bf16x2 x11, x11, rh;\n"
        "mma.sync.aligned.m16n8k16.row.col.f32.bf16.bf16.f32 {%48,%49,%50,%51}, {b0,b1,b2,b3}, {x8,x9}, {%48,%49,%50,%51};\n"
        "mma.sync.aligned.m16n8k16.row.col.f32.bf16.bf16.f32 {%52,%53,%54,%55}, {b0,b1,b2,b3}, {x10,x11}, {%52,%53,%54,%55};\n"
        "ld.shared.v4.u32 {x8,x9,x10,x11}, [xa+256];\n"
        "tanh.approx.f32 t0, p8;\n"
        "tanh.approx.f32 t1, p10;\n"
        "fma.rn.f32 t0, p8, t0, p8;\n"
        "fma.rn.f32 t1, p10, t1, p10;\n"
        "cvt.rn.bf16x2.f32 r2, t1, t0;\n"
        "mma.sync.aligned.m16n8k8.row.col.f32.bf16.bf16.f32 {d0,d1,d2,d3}, {%179,%180}, {yb}, {fz,fz,fz,fz};\n"
        "cvt.rn.bf16x2.f32 a2, d2, d0;\n"
        "cvt.rn.bf16x2.f32 a3, d3, d1;\n"
        "mov.b32 {lo,hi}, r3;\n"
        "mov.b32 rl, {lo,lo};\n"
        "mov.b32 rh, {hi,hi};\n"
        "mul.bf16x2 x12, x12, rl;\n"
        "mul.bf16x2 x13, x13, rl;\n"
        "mul.bf16x2 x14, x14, rh;\n"
        "mul.bf16x2 x15, x15, rh;\n"
        "mma.sync.aligned.m16n8k16.row.col.f32.bf16.bf16.f32 {%56,%57,%58,%59}, {b0,b1,b2,b3}, {x12,x13}, {%56,%57,%58,%59};\n"
        "mma.sync.aligned.m16n8k16.row.col.f32.bf16.bf16.f32 {%60,%61,%62,%63}, {b0,b1,b2,b3}, {x14,x15}, {%60,%61,%62,%63};\n"
        "ld.shared.v4.u32 {x12,x13,x14,x15}, [xa+384];\n"
        "tanh.approx.f32 t0, p12;\n"
        "tanh.approx.f32 t1, p14;\n"
        "fma.rn.f32 t0, p12, t0, p12;\n"
        "fma.rn.f32 t1, p14, t1, p14;\n"
        "cvt.rn.bf16x2.f32 r3, t1, t0;\n"
        "mov.b32 {lo,hi}, r0;\n"
        "mov.b32 rl, {lo,lo};\n"
        "mov.b32 rh, {hi,hi};\n"
        "mul.bf16x2 x0, x0, rl;\n"
        "mul.bf16x2 x1, x1, rl;\n"
        "mul.bf16x2 x2, x2, rh;\n"
        "mul.bf16x2 x3, x3, rh;\n"
        "mov.b32 {lo,hi}, r1;\n"
        "mov.b32 rl, {lo,lo};\n"
        "mov.b32 rh, {hi,hi};\n"
        "mul.bf16x2 x4, x4, rl;\n"
        "mul.bf16x2 x5, x5, rl;\n"
        "mul.bf16x2 x6, x6, rh;\n"
        "mul.bf16x2 x7, x7, rh;\n"
        "brx.idx.uni la, TA_%=;\n"
        "B2_%=:\n"
        "and.b32 la, ln, 255;\n"
        "shr.u32 lb, ln, 8;\n"
        "add.u32 ma, sa, %182;\n"
        "ldmatrix.sync.aligned.m8n8.x1.shared.b16 {yb}, [ma];\n"
        "add.u32 xa, sa, %181;\n"
        "mma.sync.aligned.m16n8k16.row.col.f32.bf16.bf16.f32 {%64,%65,%66,%67}, {b0,b1,b2,b3}, {x0,x1}, {%64,%65,%66,%67};\n"
        "mma.sync.aligned.m16n8k16.row.col.f32.bf16.bf16.f32 {%68,%69,%70,%71}, {b0,b1,b2,b3}, {x2,x3}, {%68,%69,%70,%71};\n"
        "ld.shared.v4.u32 {x0,x1,x2,x3}, [xa+0];\n"
        "tanh.approx.f32 t0, p0;\n"
        "tanh.approx.f32 t1, p2;\n"
        "fma.rn.f32 t0, p0, t0, p0;\n"
        "fma.rn.f32 t1, p2, t1, p2;\n"
        "cvt.rn.bf16x2.f32 r0, t1, t0;\n"
        "mma.sync.aligned.m16n8k16.row.col.f32.bf16.bf16.f32 {%72,%73,%74,%75}, {b0,b1,b2,b3}, {x4,x5}, {%72,%73,%74,%75};\n"
        "mma.sync.aligned.m16n8k16.row.col.f32.bf16.bf16.f32 {%76,%77,%78,%79}, {b0,b1,b2,b3}, {x6,x7}, {%76,%77,%78,%79};\n"
        "ld.shared.v4.u32 {x4,x5,x6,x7}, [xa+128];\n"
        "tanh.approx.f32 t0, p4;\n"
        "tanh.approx.f32 t1, p6;\n"
        "fma.rn.f32 t0, p4, t0, p4;\n"
        "fma.rn.f32 t1, p6, t1, p6;\n"
        "cvt.rn.bf16x2.f32 r1, t1, t0;\n"
        "mma.sync.aligned.m16n8k8.row.col.f32.bf16.bf16.f32 {d0,d1,d2,d3}, {%177,%178}, {yb}, {fz,fz,fz,fz};\n"
        "cvt.rn.bf16x2.f32 a0, d2, d0;\n"
        "cvt.rn.bf16x2.f32 a1, d3, d1;\n"
        "mov.b32 {lo,hi}, r2;\n"
        "mov.b32 rl, {lo,lo};\n"
        "mov.b32 rh, {hi,hi};\n"
        "mul.bf16x2 x8, x8, rl;\n"
        "mul.bf16x2 x9, x9, rl;\n"
        "mul.bf16x2 x10, x10, rh;\n"
        "mul.bf16x2 x11, x11, rh;\n"
        "mma.sync.aligned.m16n8k16.row.col.f32.bf16.bf16.f32 {%80,%81,%82,%83}, {b0,b1,b2,b3}, {x8,x9}, {%80,%81,%82,%83};\n"
        "mma.sync.aligned.m16n8k16.row.col.f32.bf16.bf16.f32 {%84,%85,%86,%87}, {b0,b1,b2,b3}, {x10,x11}, {%84,%85,%86,%87};\n"
        "ld.shared.v4.u32 {x8,x9,x10,x11}, [xa+256];\n"
        "tanh.approx.f32 t0, p8;\n"
        "tanh.approx.f32 t1, p10;\n"
        "fma.rn.f32 t0, p8, t0, p8;\n"
        "fma.rn.f32 t1, p10, t1, p10;\n"
        "cvt.rn.bf16x2.f32 r2, t1, t0;\n"
        "mma.sync.aligned.m16n8k8.row.col.f32.bf16.bf16.f32 {d0,d1,d2,d3}, {%179,%180}, {yb}, {fz,fz,fz,fz};\n"
        "cvt.rn.bf16x2.f32 a2, d2, d0;\n"
        "cvt.rn.bf16x2.f32 a3, d3, d1;\n"
        "mov.b32 {lo,hi}, r3;\n"
        "mov.b32 rl, {lo,lo};\n"
        "mov.b32 rh, {hi,hi};\n"
        "mul.bf16x2 x12, x12, rl;\n"
        "mul.bf16x2 x13, x13, rl;\n"
        "mul.bf16x2 x14, x14, rh;\n"
        "mul.bf16x2 x15, x15, rh;\n"
        "mma.sync.aligned.m16n8k16.row.col.f32.bf16.bf16.f32 {%88,%89,%90,%91}, {b0,b1,b2,b3}, {x12,x13}, {%88,%89,%90,%91};\n"
        "mma.sync.aligned.m16n8k16.row.col.f32.bf16.bf16.f32 {%92,%93,%94,%95}, {b0,b1,b2,b3}, {x14,x15}, {%92,%93,%94,%95};\n"
        "ld.shared.v4.u32 {x12,x13,x14,x15}, [xa+384];\n"
        "tanh.approx.f32 t0, p12;\n"
        "tanh.approx.f32 t1, p14;\n"
        "fma.rn.f32 t0, p12, t0, p12;\n"
        "fma.rn.f32 t1, p14, t1, p14;\n"
        "cvt.rn.bf16x2.f32 r3, t1, t0;\n"
        "mov.b32 {lo,hi}, r0;\n"
        "mov.b32 rl, {lo,lo};\n"
        "mov.b32 rh, {hi,hi};\n"
        "mul.bf16x2 x0, x0, rl;\n"
        "mul.bf16x2 x1, x1, rl;\n"
        "mul.bf16x2 x2, x2, rh;\n"
        "mul.bf16x2 x3, x3, rh;\n"
        "mov.b32 {lo,hi}, r1;\n"
        "mov.b32 rl, {lo,lo};\n"
        "mov.b32 rh, {hi,hi};\n"
        "mul.bf16x2 x4, x4, rl;\n"
        "mul.bf16x2 x5, x5, rl;\n"
        "mul.bf16x2 x6, x6, rh;\n"
        "mul.bf16x2 x7, x7, rh;\n"
        "brx.idx.uni la, TA_%=;\n"
        "B3_%=:\n"
        "and.b32 la, ln, 255;\n"
        "shr.u32 lb, ln, 8;\n"
        "add.u32 ma, sa, %182;\n"
        "ldmatrix.sync.aligned.m8n8.x1.shared.b16 {yb}, [ma];\n"
        "add.u32 xa, sa, %181;\n"
        "mma.sync.aligned.m16n8k16.row.col.f32.bf16.bf16.f32 {%96,%97,%98,%99}, {b0,b1,b2,b3}, {x0,x1}, {%96,%97,%98,%99};\n"
        "mma.sync.aligned.m16n8k16.row.col.f32.bf16.bf16.f32 {%100,%101,%102,%103}, {b0,b1,b2,b3}, {x2,x3}, {%100,%101,%102,%103};\n"
        "ld.shared.v4.u32 {x0,x1,x2,x3}, [xa+0];\n"
        "tanh.approx.f32 t0, p0;\n"
        "tanh.approx.f32 t1, p2;\n"
        "fma.rn.f32 t0, p0, t0, p0;\n"
        "fma.rn.f32 t1, p2, t1, p2;\n"
        "cvt.rn.bf16x2.f32 r0, t1, t0;\n"
        "mma.sync.aligned.m16n8k16.row.col.f32.bf16.bf16.f32 {%104,%105,%106,%107}, {b0,b1,b2,b3}, {x4,x5}, {%104,%105,%106,%107};\n"
        "mma.sync.aligned.m16n8k16.row.col.f32.bf16.bf16.f32 {%108,%109,%110,%111}, {b0,b1,b2,b3}, {x6,x7}, {%108,%109,%110,%111};\n"
        "ld.shared.v4.u32 {x4,x5,x6,x7}, [xa+128];\n"
        "tanh.approx.f32 t0, p4;\n"
        "tanh.approx.f32 t1, p6;\n"
        "fma.rn.f32 t0, p4, t0, p4;\n"
        "fma.rn.f32 t1, p6, t1, p6;\n"
        "cvt.rn.bf16x2.f32 r1, t1, t0;\n"
        "mma.sync.aligned.m16n8k8.row.col.f32.bf16.bf16.f32 {d0,d1,d2,d3}, {%177,%178}, {yb}, {fz,fz,fz,fz};\n"
        "cvt.rn.bf16x2.f32 a0, d2, d0;\n"
        "cvt.rn.bf16x2.f32 a1, d3, d1;\n"
        "mov.b32 {lo,hi}, r2;\n"
        "mov.b32 rl, {lo,lo};\n"
        "mov.b32 rh, {hi,hi};\n"
        "mul.bf16x2 x8, x8, rl;\n"
        "mul.bf16x2 x9, x9, rl;\n"
        "mul.bf16x2 x10, x10, rh;\n"
        "mul.bf16x2 x11, x11, rh;\n"
        "mma.sync.aligned.m16n8k16.row.col.f32.bf16.bf16.f32 {%112,%113,%114,%115}, {b0,b1,b2,b3}, {x8,x9}, {%112,%113,%114,%115};\n"
        "mma.sync.aligned.m16n8k16.row.col.f32.bf16.bf16.f32 {%116,%117,%118,%119}, {b0,b1,b2,b3}, {x10,x11}, {%116,%117,%118,%119};\n"
        "ld.shared.v4.u32 {x8,x9,x10,x11}, [xa+256];\n"
        "tanh.approx.f32 t0, p8;\n"
        "tanh.approx.f32 t1, p10;\n"
        "fma.rn.f32 t0, p8, t0, p8;\n"
        "fma.rn.f32 t1, p10, t1, p10;\n"
        "cvt.rn.bf16x2.f32 r2, t1, t0;\n"
        "mma.sync.aligned.m16n8k8.row.col.f32.bf16.bf16.f32 {d0,d1,d2,d3}, {%179,%180}, {yb}, {fz,fz,fz,fz};\n"
        "cvt.rn.bf16x2.f32 a2, d2, d0;\n"
        "cvt.rn.bf16x2.f32 a3, d3, d1;\n"
        "mov.b32 {lo,hi}, r3;\n"
        "mov.b32 rl, {lo,lo};\n"
        "mov.b32 rh, {hi,hi};\n"
        "mul.bf16x2 x12, x12, rl;\n"
        "mul.bf16x2 x13, x13, rl;\n"
        "mul.bf16x2 x14, x14, rh;\n"
        "mul.bf16x2 x15, x15, rh;\n"
        "mma.sync.aligned.m16n8k16.row.col.f32.bf16.bf16.f32 {%120,%121,%122,%123}, {b0,b1,b2,b3}, {x12,x13}, {%120,%121,%122,%123};\n"
        "mma.sync.aligned.m16n8k16.row.col.f32.bf16.bf16.f32 {%124,%125,%126,%127}, {b0,b1,b2,b3}, {x14,x15}, {%124,%125,%126,%127};\n"
        "ld.shared.v4.u32 {x12,x13,x14,x15}, [xa+384];\n"
        "tanh.approx.f32 t0, p12;\n"
        "tanh.approx.f32 t1, p14;\n"
        "fma.rn.f32 t0, p12, t0, p12;\n"
        "fma.rn.f32 t1, p14, t1, p14;\n"
        "cvt.rn.bf16x2.f32 r3, t1, t0;\n"
        "mov.b32 {lo,hi}, r0;\n"
        "mov.b32 rl, {lo,lo};\n"
        "mov.b32 rh, {hi,hi};\n"
        "mul.bf16x2 x0, x0, rl;\n"
        "mul.bf16x2 x1, x1, rl;\n"
        "mul.bf16x2 x2, x2, rh;\n"
        "mul.bf16x2 x3, x3, rh;\n"
        "mov.b32 {lo,hi}, r1;\n"
        "mov.b32 rl, {lo,lo};\n"
        "mov.b32 rh, {hi,hi};\n"
        "mul.bf16x2 x4, x4, rl;\n"
        "mul.bf16x2 x5, x5, rl;\n"
        "mul.bf16x2 x6, x6, rh;\n"
        "mul.bf16x2 x7, x7, rh;\n"
        "brx.idx.uni la, TA_%=;\n"
        "B4_%=:\n"
        "and.b32 la, ln, 255;\n"
        "shr.u32 lb, ln, 8;\n"
        "add.u32 ma, sa, %182;\n"
        "ldmatrix.sync.aligned.m8n8.x1.shared.b16 {yb}, [ma];\n"
        "add.u32 xa, sa, %181;\n"
        "mma.sync.aligned.m16n8k16.row.col.f32.bf16.bf16.f32 {%128,%129,%130,%131}, {b0,b1,b2,b3}, {x0,x1}, {%128,%129,%130,%131};\n"
        "mma.sync.aligned.m16n8k16.row.col.f32.bf16.bf16.f32 {%132,%133,%134,%135}, {b0,b1,b2,b3}, {x2,x3}, {%132,%133,%134,%135};\n"
        "ld.shared.v4.u32 {x0,x1,x2,x3}, [xa+0];\n"
        "tanh.approx.f32 t0, p0;\n"
        "tanh.approx.f32 t1, p2;\n"
        "fma.rn.f32 t0, p0, t0, p0;\n"
        "fma.rn.f32 t1, p2, t1, p2;\n"
        "cvt.rn.bf16x2.f32 r0, t1, t0;\n"
        "mma.sync.aligned.m16n8k16.row.col.f32.bf16.bf16.f32 {%136,%137,%138,%139}, {b0,b1,b2,b3}, {x4,x5}, {%136,%137,%138,%139};\n"
        "mma.sync.aligned.m16n8k16.row.col.f32.bf16.bf16.f32 {%140,%141,%142,%143}, {b0,b1,b2,b3}, {x6,x7}, {%140,%141,%142,%143};\n"
        "ld.shared.v4.u32 {x4,x5,x6,x7}, [xa+128];\n"
        "tanh.approx.f32 t0, p4;\n"
        "tanh.approx.f32 t1, p6;\n"
        "fma.rn.f32 t0, p4, t0, p4;\n"
        "fma.rn.f32 t1, p6, t1, p6;\n"
        "cvt.rn.bf16x2.f32 r1, t1, t0;\n"
        "mma.sync.aligned.m16n8k8.row.col.f32.bf16.bf16.f32 {d0,d1,d2,d3}, {%177,%178}, {yb}, {fz,fz,fz,fz};\n"
        "cvt.rn.bf16x2.f32 a0, d2, d0;\n"
        "cvt.rn.bf16x2.f32 a1, d3, d1;\n"
        "mov.b32 {lo,hi}, r2;\n"
        "mov.b32 rl, {lo,lo};\n"
        "mov.b32 rh, {hi,hi};\n"
        "mul.bf16x2 x8, x8, rl;\n"
        "mul.bf16x2 x9, x9, rl;\n"
        "mul.bf16x2 x10, x10, rh;\n"
        "mul.bf16x2 x11, x11, rh;\n"
        "mma.sync.aligned.m16n8k16.row.col.f32.bf16.bf16.f32 {%144,%145,%146,%147}, {b0,b1,b2,b3}, {x8,x9}, {%144,%145,%146,%147};\n"
        "mma.sync.aligned.m16n8k16.row.col.f32.bf16.bf16.f32 {%148,%149,%150,%151}, {b0,b1,b2,b3}, {x10,x11}, {%148,%149,%150,%151};\n"
        "ld.shared.v4.u32 {x8,x9,x10,x11}, [xa+256];\n"
        "tanh.approx.f32 t0, p8;\n"
        "tanh.approx.f32 t1, p10;\n"
        "fma.rn.f32 t0, p8, t0, p8;\n"
        "fma.rn.f32 t1, p10, t1, p10;\n"
        "cvt.rn.bf16x2.f32 r2, t1, t0;\n"
        "mma.sync.aligned.m16n8k8.row.col.f32.bf16.bf16.f32 {d0,d1,d2,d3}, {%179,%180}, {yb}, {fz,fz,fz,fz};\n"
        "cvt.rn.bf16x2.f32 a2, d2, d0;\n"
        "cvt.rn.bf16x2.f32 a3, d3, d1;\n"
        "mov.b32 {lo,hi}, r3;\n"
        "mov.b32 rl, {lo,lo};\n"
        "mov.b32 rh, {hi,hi};\n"
        "mul.bf16x2 x12, x12, rl;\n"
        "mul.bf16x2 x13, x13, rl;\n"
        "mul.bf16x2 x14, x14, rh;\n"
        "mul.bf16x2 x15, x15, rh;\n"
        "mma.sync.aligned.m16n8k16.row.col.f32.bf16.bf16.f32 {%152,%153,%154,%155}, {b0,b1,b2,b3}, {x12,x13}, {%152,%153,%154,%155};\n"
        "mma.sync.aligned.m16n8k16.row.col.f32.bf16.bf16.f32 {%156,%157,%158,%159}, {b0,b1,b2,b3}, {x14,x15}, {%156,%157,%158,%159};\n"
        "ld.shared.v4.u32 {x12,x13,x14,x15}, [xa+384];\n"
        "tanh.approx.f32 t0, p12;\n"
        "tanh.approx.f32 t1, p14;\n"
        "fma.rn.f32 t0, p12, t0, p12;\n"
        "fma.rn.f32 t1, p14, t1, p14;\n"
        "cvt.rn.bf16x2.f32 r3, t1, t0;\n"
        "mov.b32 {lo,hi}, r0;\n"
        "mov.b32 rl, {lo,lo};\n"
        "mov.b32 rh, {hi,hi};\n"
        "mul.bf16x2 x0, x0, rl;\n"
        "mul.bf16x2 x1, x1, rl;\n"
        "mul.bf16x2 x2, x2, rh;\n"
        "mul.bf16x2 x3, x3, rh;\n"
        "mov.b32 {lo,hi}, r1;\n"
        "mov.b32 rl, {lo,lo};\n"
        "mov.b32 rh, {hi,hi};\n"
        "mul.bf16x2 x4, x4, rl;\n"
        "mul.bf16x2 x5, x5, rl;\n"
        "mul.bf16x2 x6, x6, rh;\n"
        "mul.bf16x2 x7, x7, rh;\n"
        "brx.idx.uni la, TA_%=;\n"
        "EXIT_%=:\n"
        "mov.u32 %160, ring;\n"
        "}\n"
        : "+f"(acc[0][0][0][0]), "+f"(acc[0][0][0][1]), "+f"(acc[0][0][0][2]), "+f"(acc[0][0][0][3]), "+f"(acc[0][0][1][0]),
          "+f"(acc[0][0][1][1]), "+f"(acc[0][0][1][2]), "+f"(acc[0][0][1][3]), "+f"(acc[0][1][0][0]), "+f"(acc[0][1][0][1]),
          "+f"(acc[0][1][0][2]), "+f"(acc[0][1][0][3]), "+f"(acc[0][1][1][0]), "+f"(acc[0][1][1][1]), "+f"(acc[0][1][1][2]),
          "+f"(acc[0][1][1][3]), "+f"(acc[0][2][0][0]), "+f"(acc[0][2][0][1]), "+f"(acc[0][2][0][2]), "+f"(acc[0][2][0][3]),
          "+f"(acc[0][2][1][0]), "+f"(acc[0][2][1][1]), "+f"(acc[0][2][1][2]), "+f"(acc[0][2][1][3]), "+f"(acc[0][3][0][0]),
          "+f"(acc[0][3][0][1]), "+f"(acc[0][3][0][2]), "+f"(acc[0][3][0][3]), "+f"(acc[0][3][1][0]), "+f"(acc[0][3][1][1]),
          "+f"(acc[0][3][1][2]), "+f"(acc[0][3][1][3]), "+f"(acc[1][0][0][0]), "+f"(acc[1][0][0][1]), "+f"(acc[1][0][0][2]),
          "+f"(acc[1][0][0][3]), "+f"(acc[1][0][1][0]), "+f"(acc[1][0][1][1]), "+f"(acc[1][0][1][2]), "+f"(acc[1][0][1][3]),
          "+f"(acc[1][1][0][0]), "+f"(acc[1][1][0][1]), "+f"(acc[1][1][0][2]), "+f"(acc[1][1][0][3]), "+f"(acc[1][1][1][0]),
          "+f"(acc[1][1][1][1]), "+f"(acc[1][1][1][2]), "+f"(acc[1][1][1][3]), "+f"(acc[1][2][0][0]), "+f"(acc[1][2][0][1]),
          "+f"(acc[1][2][0][2]), "+f"(acc[1][2][0][3]), "+f"(acc[1][2][1][0]), "+f"(acc[1][2][1][1]), "+f"(acc[1][2][1][2]),
          "+f"(acc[1][2][1][3]), "+f"(acc[1][3][0][0]), "+f"(acc[1][3][0][1]), "+f"(acc[1][3][0][2]), "+f"(acc[1][3][0][3]),
          "+f"(acc[1][3][1][0]), "+f"(acc[1][3][1][1]), "+f"(acc[1][3][1][2]), "+f"(acc[1][3][1][3]), "+f"(acc[2][0][0][0]),
          "+f"(acc[2][0][0][1]), "+f"(acc[2][0][0][2]), "+f"(acc[2][0][0][3]), "+f"(acc[2][0][1][0]), "+f"(acc[2][0][1][1]),
          "+f"(acc[2][0][1][2]), "+f"(acc[2][0][1][3]), "+f"(acc[2][1][0][0]), "+f"(acc[2][1][0][1]), "+f"(acc[2][1][0][2]),
          "+f"(acc[2][1][0][3]), "+f"(acc[2][1][1][0]), "+f"(acc[2][1][1][1]), "+f"(acc[2][1][1][2]), "+f"(acc[2][1][1][3]),
          "+f"(acc[2][2][0][0]), "+f"(acc[2][2][0][1]), "+f"(acc[2][2][0][2]), "+f"(acc[2][2][0][3]), "+f"(acc[2][2][1][0]),
          "+f"(acc[2][2][1][1]), "+f"(acc[2][2][1][2]), "+f"(acc[2][2][1][3]), "+f"(acc[2][3][0][0]), "+f"(acc[2][3][0][1]),
          "+f"(acc[2][3][0][2]), "+f"(acc[2][3][0][3]), "+f"(acc[2][3][1][0]), "+f"(acc[2][3][1][1]), "+f"(acc[2][3][1][2]),
          "+f"(acc[2][3][1][3]), "+f"(acc[3][0][0][0]), "+f"(acc[3][0][0][1]), "+f"(acc[3][0][0][2]), "+f"(acc[3][0][0][3]),
          "+f"(acc[3][0][1][0]), "+f"(acc[3][0][1][1]), "+f"(acc[3][0][1][2]), "+f"(acc[3][0][1][3]), "+f"(acc[3][1][0][0]),
          "+f"(acc[3][1][0][1]), "+f"(acc[3][1][0][2]), "+f"(acc[3][1][0][3]), "+f"(acc[3][1][1][0]), "+f"(acc[3][1][1][1]),
          "+f"(acc[3][1][1][2]), "+f"(acc[3][1][1][3]), "+f"(acc[3][2][0][0]), "+f"(acc[3][2][0][1]), "+f"(acc[3][2][0][2]),
          "+f"(acc[3][2][0][3]), "+f"(acc[3][2][1][0]), "+f"(acc[3][2][1][1]), "+f"(acc[3][2][1][2]), "+f"(acc[3][2][1][3]),
          "+f"(acc[3][3][0][0]), "+f"(acc[3][3][0][1]), "+f"(acc[3][3][0][2]), "+f"(acc[3][3][0][3]), "+f"(acc[3][3][1][0]),
          "+f"(acc[3][3][1][1]), "+f"(acc[3][3][1][2]), "+f"(acc[3][3][1][3]), "+f"(acc[4][0][0][0]), "+f"(acc[4][0][0][1]),
          "+f"(acc[4][0][0][2]), "+f"(acc[4][0][0][3]), "+f"(acc[4][0][1][0]), "+f"(acc[4][0][1][1]), "+f"(acc[4][0][1][2]),
          "+f"(acc[4][0][1][3]), "+f"(acc[4][1][0][0]), "+f"(acc[4][1][0][1]), "+f"(acc[4][1][0][2]), "+f"(acc[4][1][0][3]),
          "+f"(acc[4][1][1][0]), "+f"(acc[4][1][1][1]), "+f"(acc[4][1][1][2]), "+f"(acc[4][1][1][3]), "+f"(acc[4][2][0][0]),
          "+f"(acc[4][2][0][1]), "+f"(acc[4][2][0][2]), "+f"(acc[4][2][0][3]), "+f"(acc[4][2][1][0]), "+f"(acc[4][2][1][1]),
          "+f"(acc[4][2][1][2]), "+f"(acc[4][2][1][3]), "+f"(acc[4][3][0][0]), "+f"(acc[4][3][0][1]), "+f"(acc[4][3][0][2]),
          "+f"(acc[4][3][0][3]), "+f"(acc[4][3][1][0]), "+f"(acc[4][3][1][1]), "+f"(acc[4][3][1][2]), "+f"(acc[4][3][1][3]),
          "+r"(ring)
        : "r"(wf[0][0]), "r"(wf[0][1]), "r"(wf[0][2]), "r"(wf[0][3]), "r"(wf[1][0]), "r"(wf[1][1]), "r"(wf[1][2]), "r"(wf[1][3]),
          "r"(wf[2][0]), "r"(wf[2][1]), "r"(wf[2][2]), "r"(wf[2][3]), "r"(wf[3][0]), "r"(wf[3][1]), "r"(wf[3][2]), "r"(wf[3][3]),
          "r"(cgf[0]), "r"(cgf[1]), "r"(cgf[2]), "r"(cgf[3]), "r"(xoff), "r"(moff), "r"(rec)
        : "memory");
}

__device__ __noinline__ void generic_path(float* sagg, const __nv_bfloat16* x, const int* src, const int* dst,
                                          const __nv_bfloat16* Y, const __nv_bfloat16* ef, const __nv_bfloat16* w_rad,
                                          const __nv_bfloat16* cg, int x0, int x1) {
    const int tid = threadIdx.x, lane = tid & 31, blk = blockIdx.x;
    for (int k = 0; k < 2; k++)
        for (int r = 0; r < min(k == 0 ? x0 : x1, 32); r++) {
            uint32_t* p2 = g_mail2 + (blk * NSRC + ((tid + k * NTHR) >> 3)) * 32 + r;
            uint32_t v;
            int it = 0;
            do {
                asm volatile("ld.relaxed.gpu.global.u32 %0, [%1];" : "=r"(v) : "l"(p2) : "memory");
                if (++it > (1 << 20)) __trap();
            } while (v == 0);
            *p2 = 0;
        }
    __syncthreads();
    for (int i = tid; i < NPB * 512; i += NTHR) sagg[i] = 0.f;
    __syncthreads();
    for (int e0 = tid & ~31; e0 < N_EDGES; e0 += NTHR) {
        uint32_t bm = __ballot_sync(~0u, dst[e0 + lane] / NPB == blk);
        while (bm) {
            const int e = e0 + __ffs(bm) - 1, s = src[e], loc = dst[e] - blk * NPB;
            bm &= bm - 1;
            float a[4][4];
            for (int i = 0; i < 4; i++)
                for (int o = 0; o < 4; o++) {
                    a[i][o] = 0.f;
                    for (int f = 0; f < 4; f++)
                        a[i][o] += __bfloat162float(Y[e * 4 + f]) * __bfloat162float(cg[i * 16 + f * 4 + o]);
                }
#pragma unroll 1
            for (int c = lane; c < 128; c += 32) {
                float pre = 0.f;
                for (int k = 0; k < 16; k++)
                    pre += __bfloat162float(ef[e * 16 + k]) * __bfloat162float(w_rad[k * 128 + c]);
                const float R = pre / (1.f + __expf(-pre));
                for (int o = 0; o < 4; o++) {
                    float acc = 0.f;
                    for (int i = 0; i < 4; i++) acc += __bfloat162float(x[(size_t)s * 512 + c * 4 + i]) * a[i][o];
                    atomicAdd(&sagg[loc * 512 + c * 4 + o], R * acc);
                }
            }
        }
    }
    __syncthreads();
}

__device__ __forceinline__ void init_barriers() {
    extern __shared__ __align__(1024) uint8_t smem[];
    const uint32_t sb = smem_u32(smem);
#pragma unroll
    for (int i = 0; i < 4 * NG; i++) {
        mbar_init(sb + i * STAGE + 4 * ROWP, 32);
        mbar_init(sb + i * STAGE + 4 * ROWP + 8, 2);
    }
}

template <int PHASES>
__global__ void __launch_bounds__(NTHR, 1)
tfn_kernel(const __nv_bfloat16* __restrict__ x, const int* __restrict__ src, const int* __restrict__ dst,
           const __nv_bfloat16* __restrict__ Y, const __nv_bfloat16* __restrict__ ef,
           const __nv_bfloat16* __restrict__ w_rad, const __nv_bfloat16* __restrict__ cg,
           const __nv_bfloat16* __restrict__ w_mix, __nv_bfloat16* __restrict__ out) {
    extern __shared__ __align__(1024) uint8_t smem[];
    const int tid = threadIdx.x, lane = tid & 31;
    const int warp = __shfl_sync(~0u, tid >> 5, 0);
    const int blk = blockIdx.x;
    uint32_t sb = smem_u32(smem);
    asm volatile("" : "+r"(sb));
    int* mi = reinterpret_cast<int*>(smem + SM_MISC);

    const int g = lane >> 2, t = lane & 3;
    const uint32_t dump = sb + SC_DUMP + lane * 4;
    int4 d1[2], s1[2];
    constexpr int nq = EPC / 4;
    const bool binner = (PHASES & 1) && blk < NSRC;
    if (binner) {
#pragma unroll
        for (int k = 0; k < 2; k++) {
            const int q = tid + k * NTHR;
            if (q < nq) {
                d1[k] = __ldg(reinterpret_cast<const int4*>(dst + blk * EPC) + q);
                s1[k] = __ldg(reinterpret_cast<const int4*>(src + blk * EPC) + q);
            }
        }
    }
    if (binner) {
#pragma unroll
        for (int k = 0; k < 3; k++)
            if (k < 2 || warp < 1) sts128(sb + SC_MAIL + (tid + k * NTHR) * 16, ~0u, ~0u, ~0u, ~0u);
        if (tid <= NB / 4) sts128(sb + SC_CNT + tid * 16, 0, 0, 0, 0);
    }
    if (PHASES & 2) {
        if (tid == 160) { sts128(sb + SM_MISC, 0, 0, 0, 0); sts128(sb + SM_MISC + MI_NU * 4, 0, 0, 0, 0); }
        if (tid == 161) {
            mi[MI_SHIFT] = 0;
            *reinterpret_cast<int**>(mi + MI_SHIFT + 4) = g_lag[blk];
        }
        if (tid == 162) g_lag[blk][0] = g_lag[NB + blk][0] = 0;
        if (tid < 20 * HS / 4) sts128(sb + SC_HIST + tid * 16, 0, 0, 0, 0);
        const uint32_t pad = (uint32_t)(lane * 0x10008 + 7);
#pragma unroll
        for (int k = 0; k < 3; k++)
            if (tid + k * NTHR < 4 * UCAP * REC / 16) sts128(sb + SM_REC + (tid + k * NTHR) * 16, pad, pad, pad, pad);
    }
    __syncthreads();
    if (PHASES & 2) {
#pragma unroll
        for (int k = 0; k < 4; k++) {
            const int i = tid + k * NTHR, c = i >> 4;
            cp16(sb + SM_W + c * 256 + (((i & 15) ^ ((c & 2) | (((c >> 4) & 1) << 2))) << 4), w_mix + i * 8);
        }
        if (warp >= 8) cp16(sb + SC_WR + ((tid - 256) ^ ((tid >> 4) & 6)) * 16, w_rad + (tid - 256) * 8);
        if (tid < 8) cp16(sb + SC_WR + 4096 + tid * 16, cg + tid * 8);
    }
    if (binner) {
#pragma unroll
        for (int k = 0; k < 2; k++) {
            if (tid + k * NTHR < nq) {
                const uint32_t dd[4] = {(uint32_t)d1[k].x, (uint32_t)d1[k].y, (uint32_t)d1[k].z, (uint32_t)d1[k].w};
                const uint32_t ss[4] = {(uint32_t)s1[k].x, (uint32_t)s1[k].y, (uint32_t)s1[k].z, (uint32_t)s1[k].w};
                uint32_t own[4], rk[4], v[4];
#pragma unroll
                for (int j = 0; j < 4; j++) { own[j] = dd[j] / NPB; rk[j] = atoms_inc(sb + SC_CNT + own[j] * 4); }
#pragma unroll
                for (int j = 0; j < 4; j++) {
                    const uint32_t loc = dd[j] - own[j] * NPB, code = loc + ((loc * 216) >> 12);
                    v[j] = (ss[j] << 18) + code * 2560 + (tid + k * NTHR) * 4 + j + 1;
                    sts32(sb + SC_MAIL + own[j] * 128 + ((min(rk[j], 31u) * 4) ^ ((own[j] & 7) << 4)), v[j]);
                }
                if (max(max(rk[0], rk[1]), max(rk[2], rk[3])) >= 31) {
#pragma unroll
                    for (int j = 0; j < 4; j++)
                        if (rk[j] - 31 < 32)
                            asm volatile("st.relaxed.gpu.global.u32 [%0], %1;" ::"l"(g_mail2 + (own[j] * NSRC + blk) * 32 + rk[j] - 31), "r"(v[j]) : "memory");
                }
            }
        }
        __syncwarp();
        asm volatile("red.shared.max.u32 [%0], %1;" ::"r"(lane == 0 ? sb + SC_CNT + NB * 4 : dump), "r"(gtime()) : "memory");
        STAMP(1);
        __syncthreads();
        const uint32_t hdr = 0xc0000000u | ((lds32(sb + SC_CNT + NB * 4) << 7) & 0x3ffff000u);
        uint4 mv[3];
        uint32_t mc[3];
#pragma unroll
        for (int k = 0; k < 3; k++)
            if (k < 2 || warp < 1) {
                const int j = tid + k * NTHR, own = j >> 3;
                mv[k] = lds128(sb + SC_MAIL + own * 128 + (((j ^ own) & 7) << 4));
                mc[k] = lds32(sb + SC_CNT + own * 4);
            }
#pragma unroll
        for (int k = 0; k < 3; k++)
            if (k < 2 || warp < 1) {
                const int j = tid + k * NTHR;
                asm volatile("st.relaxed.gpu.global.v4.u32 [%0], {%1,%2,%3,%4};" ::"l"(g_mail + ((j >> 3) * NSRC + blk) * 8 + (j & 7)),
                             "r"(mv[k].x), "r"(mv[k].y), "r"(mv[k].z), "r"((j & 7) == 7 ? hdr | mc[k] : mv[k].w) : "memory");
            }
        STAMP(2);
    }
    if (!(PHASES & 2)) return;
    const uint32_t tpub = (uint32_t)clock() + (blk < NSRC ? 0 : 3000);
    asm volatile("cp.async.wait_all;" ::: "memory");
    __syncwarp();
#pragma unroll
    for (int k = 0; k < 2; k++) {
        const int i = (tid & ~1) + ((tid & 1) * 2 + k) * NTHR, c = i >> 4;
        const uint32_t a0 = sb + SM_W + c * 256 + (((i & 15) ^ ((c & 3) | (((c >> 4) & 1) << 2))) << 4);
        const uint32_t o = (tid & 1) << 4;
        uint4 u = lds128((a0 & ~16u) ^ o), v = lds128((a0 | 16u) ^ o);
        if (tid & 1) { const uint4 w = u; u = v; v = w; }
        const uint32_t s0 = (tid & 1) ? 0x7632 : 0x5410, s1 = s0 ^ 0x2222;
        sts128(a0 ^ o, __byte_perm(u.x, u.y, s0), __byte_perm(u.z, u.w, s0), __byte_perm(v.x, v.y, s0), __byte_perm(v.z, v.w, s0));
        sts128(a0 ^ o ^ 16, __byte_perm(u.x, u.y, s1), __byte_perm(u.z, u.w, s1), __byte_perm(v.x, v.y, s1), __byte_perm(v.z, v.w, s1));
    }

    uint32_t en[8], hr[8], rk[8], em[8];
    int xc[2];
    const uint32_t tref = __shfl_sync(~0u, gtime() >> 5, 0);
    {
        uint4* mp = g_mail + blk * NSRC * 8 + tid;
        int it = 0;
        bool ok;
        while ((int)((uint32_t)clock() - tpub) < POLL_DELAY) {}
        do {
#pragma unroll
            for (int k = 0; k < 2; k++)
                    asm volatile("ld.relaxed.gpu.global.v4.u32 {%0,%1,%2,%3}, [%4];"
                                 : "=r"(en[4 * k]), "=r"(en[4 * k + 1]), "=r"(en[4 * k + 2]), "=r"(en[4 * k + 3])
                                 : "l"(mp + k * NTHR) : "memory");
            uint32_t m = ~0u;
#pragma unroll
            for (int i = 0; i < 8; i++) m = min(m, en[i]);
            ok = __all_sync(~0u, m != 0);
            if (++it > (1 << 20)) __trap();
        } while (!ok);
        STAMP(3);
#pragma unroll
        for (int i = 0; i < 8; i++) {
            const uint32_t w = en[i] & 0x3ffff, code = ((w >> 9) * 13108) >> 16;
            hr[i] = en[i] < 0xc0000000u ? sb + SC_HIST + ((code >> 2) * HS + (en[i] >> 25)) * 4 : dump;
            rk[i] = atoms_inc(hr[i]);
            em[i] = ((((tid + (i >> 2) * NTHR) >> 3) * EPC + w - code * 2560 - 1) * 8) | (code & 3);
        }
        int dt = -(1 << 20);
#pragma unroll
        for (int k = 0; k < 2; k++) {
            const bool hd = (lane & 7) == 7;
            dt = max(dt, hd ? (int)(((en[4 * k + 3] >> 12) - tref) << 14) >> 14 : -(1 << 20));
            xc[k] = hd ? max((int)(en[4 * k + 3] & 0xfff) - 31, 0) : 0;
        }
        dt = __reduce_max_sync(~0u, dt);
        asm volatile("red.shared.max.u32 [%0], %1;" ::"r"(lane == 0 ? sb + SM_MISC + MI_TMAX * 4 : dump + 128), "r"(tref + dt + (1u << 27)) : "memory");
        if (xc[0] | xc[1]) {
#pragma unroll
            for (int k = 0; k < 2; k++) {
                const int slot = atomicAdd(&mi[MI_XN], xc[k]);
                for (int r = 0; r < xc[k] && slot + r < 32; r++)
                    reinterpret_cast<uint32_t*>(smem + SC_XTRA)[slot + r] = ((tid + k * NTHR) >> 3) * 32 + r;
            }
        }
#pragma unroll
        for (int k = 0; k < 2; k++)
            mp[k * NTHR] = make_uint4(0, 0, 0, 0);
    }
    __syncthreads();
    STAMP(4);
    uint32_t* hist = reinterpret_cast<uint32_t*>(smem + SC_HIST);
    const int xn = mi[MI_XN];
    uint32_t xi = 0, xv = 1;
    if (warp < 10) {
        uint32_t* hp = hist + (warp * 2 + (lane >> 4)) * HS + (lane & 15) * 5;
        int c[5], s = 0;
#pragma unroll
        for (int j = 0; j < 5; j++) { c[j] = hp[j]; s += c[j]; }
        int inc = s;
#pragma unroll
        for (int o = 1; o < 16; o <<= 1) { int v = __shfl_up_sync(~0u, inc, o, 16); if ((lane & 15) >= o) inc += v; }
        int base = 0;
        if ((lane & 15) == 15) {
            const int tm = (warp * 2 + (lane >> 4)) / 5;
            base = tm * 256 + atomicAdd(&mi[MI_NU + tm], (inc + 3) >> 2);
            hp[5] = (base + ((inc + 3) >> 2)) << 16;
        }
        const int tot = __shfl_sync(~0u, inc, 15, 16);
        base = __shfl_sync(~0u, base, 15, 16);
        int ex = inc - s;
#pragma unroll
        for (int j = 0; j < 5; j++) {
            hp[j] = (base * 4 + ex) | ((base + ((ex == tot ? ex + 3 : ex + 1) >> 2)) << 16);
            ex += c[j];
        }
    } else if (warp == 10) {
        if (lane == 0) init_barriers();
        if (lane < xn) {
            xi = reinterpret_cast<const uint32_t*>(smem + SC_XTRA)[lane];
            asm volatile("ld.relaxed.gpu.global.u32 %0, [%1];" : "=r"(xv) : "l"(g_mail2 + blk * NSRC * 32 + xi) : "memory");
        }
    } else if (warp >= 12) {
        const uint32_t d = sb + (warp - 12) * NG * STAGE + lane * 16;
#pragma unroll
        for (int m = 0; m < 8; m++) {
            uint32_t w[4];
#pragma unroll
            for (int j = 0; j < 4; j++)
                w[j] = mul_lo(lds32(sb + SC_WR + (2 * t + (j & 1) + (j >> 1) * 8) * 256 + (((m * 8 + g) * 4) ^ (t << 5))), 0x3f003f00u);
            sts128(d + (m >> 2) * ROWP + (m & 3) * 512, __byte_perm(w[0], w[1], 0x5410), __byte_perm(w[0], w[1], 0x7632),
                   __byte_perm(w[2], w[3], 0x5410), __byte_perm(w[2], w[3], 0x7632));
        }
        uint32_t c[4];
#pragma unroll
        for (int i = 0; i < 4; i++) {
            const uint32_t ca = sb + SC_WR + 4096 + (i * 16 + (t & 1) * 8 + (g & 3)) * 2;
            c[i] = (lds16(ca) | (lds16(ca + 8) << 16)) & ((t >> 1) == (g >> 2) ? ~0u : 0u);
        }
        sts128(d + 2 * ROWP, c[0], c[1], c[2], c[3]);
    } else if (lane == 0) {
        sts32(sb + SC_GPOS + GDUMMY * 4, (uint32_t)(4 * UCAP * REC + 128) * 0x10001u);
        constexpr int start_ns = START_NS;
        mi[MI_T0] = (uint32_t)clock() + (((int)(((uint32_t)mi[MI_TMAX] << 5) + start_ns - gtime()) * 31) >> 4);
    }
    __syncthreads();
    STAMP(10);
    int myng = mi[MI_NU + (lane & 3)];
    const bool ovf = __any_sync(~0u, myng + xn > 2 * (UCAP - 4) || xn > 32);
    if (!ovf) {
        constexpr int pace = PACE_Q8, p1 = PACE_HEAD, b1 = HEAD_BK, p2 = PACE_TAIL, b2 = TAIL_BK, lead = PACE_LEAD;
        auto sched = [&](int b) { return b * pace - min(b, b1) * (pace - p1) - max(b - b2, 0) * (pace - p2) - lead; };
        if (warp < 10) {
            const int team = tid / NBK, b = tid - team * NBK;
            int lo[5], n[5], pos = team * UCAP * 2, nsum = 0;
#pragma unroll
            for (int q = 0; q < 5; q++) {
                lo[q] = hist[(team * 5 + q) * HS + b] >> 16;
                n[q] = (hist[(team * 5 + q) * HS + b + 1] >> 16) - lo[q];
                pos += lo[q] - (hist[(team * 5 + q) * HS] >> 16);
                nsum += n[q];
            }
            const int step = __float2int_rz(__fdividef((float)(sched(b + 1) - sched(b)), (float)max(nsum, 1)));
            const int tb = sched(b) + step / 2 - pos * step;
            const uint32_t t0 = mi[MI_T0];
            auto emit = [&](int q, int r, int pq) {
                const bool on = r < n[q];
                const uint32_t ro = (pq >> 1) * REC, par = pq & 1;
                sts32(on ? sb + SC_GPOS + (lo[q] + r) * 4 : dump, ro * 0x10001u + par * 0x40002u + (REC | (16 << 16)));
                sts8(on ? sb + SM_REC + 48 + ro + par : dump, q);
                sts16(on && !par ? sb + SM_REC + REC + 50 + ro : dump, (t0 + max(tb + pq * step, 0)) >> 2);
            };
#pragma unroll
            for (int q = 0, pq = pos; q < 5; pq += n[q], q++) emit(q, 0, pq);
#pragma unroll
            for (int q = 0; q < 5; pos += n[q], q++)
#pragma unroll 1
                for (int r = 1; __any_sync(~0u, r < n[q]); r++) emit(q, r, pos + r);
        } else if (warp == 10) {
            for (int n = 0; __any_sync(~0u, xv == 0); n++) {
                if (xv == 0) asm volatile("ld.relaxed.gpu.global.u32 %0, [%1];" : "=r"(xv) : "l"(g_mail2 + blk * NSRC * 32 + xi) : "memory");
                if (n > (1 << 20)) __trap();
            }
            const uint32_t w = xv & 0x3ffff, code = ((w >> 9) * 13108) >> 16, xt = lane < xn ? code / 20 : 4;
            const uint32_t same = __match_any_sync(~0u, xt);
            const int pq = __shfl_sync(~0u, myng, xt & 3) + __popc(same & ((1u << lane) - 1));
#pragma unroll
            for (int q = 0; q < 4; q++) {
                const int c = __popc(__ballot_sync(~0u, xt == q));
                if (lane == q) myng += c;
            }
            if (lane < xn) {
                g_mail2[blk * NSRC * 32 + xi] = 0;
                const uint32_t a = sb + SM_REC + (xt * UCAP + (pq >> 1)) * REC;
                sts16(a + REC + (pq & 1) * 2, xv >> 18);
                sts32(a + 16 + (pq & 1) * 4, (((xi >> 5) * EPC + w - code * 2560 - 1) * 8) | (code & 3));
                sts8(a + 48 + (pq & 1), (code >> 2) - xt * 5);
                if (!(pq & 1)) sts16(a + REC + 50, ((uint32_t)mi[MI_T0] + sched(NBK - 2)) >> 2);
            }
            if (lane < 4) {
                const uint32_t a = sb + SM_REC + (lane * UCAP + (myng >> 1)) * REC + 48;
                if (myng & 1) sts8(a + 1, 0);
                sts16(a + (myng & 1) * REC, 5);
                mi[MI_END + lane] = (myng + 1) >> 1;
            }
        }
#pragma unroll
        for (int i = 0; i < 8; i++) {
            const uint32_t p = en[i] < 0xc0000000u ? rk[i] + lds16(hr[i]) : GDUMMY * 4;
            hr[i] = sb + SC_GPOS + (p & ~3u);
            rk[i] = (p & 3) * 0x80004u;
        }
        __syncthreads();
        STAMP(11);
#pragma unroll
        for (int i = 0; i < 8; i++) rk[i] += lds32(hr[i]);
#pragma unroll
        for (int i = 0; i < 8; i++) {
            sts16(sb + SM_REC + (rk[i] & 0xffff), en[i] >> 18);
            sts32(sb + SM_REC + (rk[i] >> 16), em[i]);
        }
    } else {
        if (tid < 4) {
            sts16(sb + SM_REC + tid * UCAP * REC + 48, 5);
            mi[MI_END + tid] = 0;
        }
        generic_path(reinterpret_cast<float*>(smem), x, src, dst, Y, ef, w_rad, cg, xc[0], xc[1]);
    }

    __syncwarp();
    if (warp >= 8) {
        asm volatile("bar.sync 3, 512;" ::: "memory");
        asm volatile("setmaxnreg.dec.sync.aligned.u32 24;");
        const int team = warp & 3;
        if (ovf) {
            asm volatile("bar.sync 2;" ::: "memory");
            if (tid == 256) init_barriers();
            asm volatile("bar.sync 2;" ::: "memory");
        }
        STAMP(5);
        const uint32_t ring = sb + SM_RING + team * NG * STAGE;
        const uint32_t q = lane >> 3, c = lane & 7, rec = sb + SM_REC + team * UCAP * REC;
        __syncwarp();
        producer_loop(reinterpret_cast<const char*>(x) + (ROWMODE == 0 ? c : ROWMODE == 1 ? lane & 15 : lane) * 16, reinterpret_cast<const char*>(ef) + (c & 1) * 16, Y,
                      q * ROWP + ((c ^ (q << 1)) << 4), q * 4 + (c & 2) * 8, (c & 1) * 2 + (c >> 2), ring, rec,
                      rec + (mi[MI_END + team] + 1) * REC, warp - 8, sb + SM_MISC + MI_SHIFT * 4,
                      ROWMODE == 1 ? (lane >> 4) * ROWP + (((lane & 15) ^ ((lane >> 4) << 1)) << 4) : lane * 16);
        uint32_t ln, sb2, cta;
        asm volatile("mov.u32 %0, %%tid.x;\nmov.u32 %1, %%ctaid.x;\nmov.u32 %2, %%dynamic_smem_size;" : "=r"(ln), "=r"(cta), "=r"(sb2));
        if (FEEDBACK && cta == NB - 1 && ln >= NTHR - 32) {
            ln &= 31;
            sb2 += smem_u32(smem) - SM_TOTAL + SM_MISC;
            constexpr int lead = LEAD_CLK >> 2;
            const uint32_t tend = lds32(sb2 + MI_T0 * 4) + 70 * PACE_Q8;
            int sh = 0;
            for (int n = 0; n < 199 && (int)((uint32_t)clock() - tend - (sh >> 14)) < 0; n++) {
                int v;
                asm volatile("ld.relaxed.gpu.global.s32 %0, [%1];" : "=r"(v) : "l"(g_lag[ln * 4]) : "memory");
                const int err = (__reduce_add_sync(~0u, max(v, 0)) >> 5) - lead;
                const int old = sh;
                sh = min(max((sh >> 16) + (err * (err > 0 ? FB_GAIN : FB_DOWN) >> 3), FB_MIN), 2500) << 16;
                if (sh == old) continue;
#pragma unroll
                for (int k = 0; k < 5; k++)
                    asm volatile("st.relaxed.gpu.global.s32 [%0], %1;" ::"l"(g_lag[NB + min(ln + 32 * k, NB - 1u)]), "r"(sh) : "memory");
            }
        }
    } else {
        int team;
        {
            const int n0 = mi[MI_END], n1 = mi[MI_END + 1], n2 = mi[MI_END + 2], n3 = mi[MI_END + 3];
            const int d1 = abs(n0 + n1 - n2 - n3), d2 = abs(n0 + n2 - n1 - n3), d3 = abs(n0 + n3 - n1 - n2);
            const uint32_t perm = PAIRING && d1 < min(d2, d3) ? 0x3120 : PAIRING && d3 < d2 ? 0x2310 : 0x3210;
            team = __shfl_sync(~0u, (perm >> ((warp >> 1) * 4)) & 3, 0);
        }
        const int h = warp & 1;
        asm volatile("bar.arrive 3, 512;" ::: "memory");
        asm volatile("setmaxnreg.inc.sync.aligned.u32 232;");
        uint32_t ring = sb + SM_RING + team * NG * STAGE;
        uint32_t wf[4][4], cgf[4];
#pragma unroll
        for (int m = 0; m < 5; m++) {
            const uint4 v = lds128(ring + (m < 4 ? h * ROWP + m * 512 : 2 * ROWP) + lane * 16);
            uint32_t* f = m < 4 ? wf[m] : cgf;
            f[0] = v.x; f[1] = v.y; f[2] = v.z; f[3] = v.w;
        }
        float acc[5][4][2][4];
        if (!ovf) {
#pragma unroll
            for (int l = 0; l < 5; l++)
#pragma unroll
                for (int m = 0; m < 4; m++)
#pragma unroll
                    for (int p = 0; p < 2; p++)
#pragma unroll
                        for (int r = 0; r < 4; r++) acc[l][m][p][r] = 0.f;
        } else {
            const float* sagg = reinterpret_cast<const float*>(smem);
#pragma unroll
            for (int l = 0; l < 5; l++)
#pragma unroll
                for (int m = 0; m < 4; m++)
#pragma unroll
                    for (int p = 0; p < 2; p++)
#pragma unroll
                        for (int r = 0; r < 4; r++) {
                            int nd = l * 4 + (g >> 2) + (r >> 1) * 2;
                            int ch = h * 64 + m * 16 + 4 * t + (r & 1) * 2 + p;
                            acc[l][m][p][r] = nd < 19 ? sagg[(team * 19 + nd) * 512 + ch * 4 + (g & 3)] : 0.f;
                        }
            asm volatile("bar.sync 2;" ::: "memory");
            asm volatile("bar.sync 2;" ::: "memory");
        }
        const uint32_t xoff = t * ROWP + h * 512 + ((g ^ (t << 1)) << 4);
        const uint32_t mat = lane >> 3, mhi = (lane >> 2) & 1;
        const bool isy = mat < 2;
        const uint32_t ml = isy ? (t & 2) + (mat & 1) : t;
        const uint32_t moff = ml * ROWP + 2048 + (((isy ? 4 + 2 * mhi + (t & 1) : 2 * mhi + mat - 2) ^ (ml << 1)) << 4);
        __syncwarp();
        consumer_loop(acc, wf, cgf, xoff, ring, moff, sb + SM_REC + team * UCAP * REC);
        {
        int lane_;
        asm volatile("mov.u32 %0, %%laneid;" : "=r"(lane_));
        const int lane = lane_, g = lane >> 2, t = lane & 3;
        const uint32_t sb = ring - team * NG * STAGE;
        STAMP(7);
        asm volatile("bar.sync %0, 64;" ::"r"(4 + team) : "memory");
        {
            const int rr = ((g & 3) >> 1) * 8 + (g >> 2) * 2 + (g & 1);
#pragma unroll
            for (int l = 0; l < 5; l++)
#pragma unroll
                for (int hi = 0; hi < 2; hi++) {
                    const int R = l * 16 + rr + hi * 4;
                    const uint32_t a = sb + team * AGGT + h * 10240 + R * 128;
#pragma unroll
                    for (int c = 0; c < 2; c++) {
                        const int m = 2 * c;
                        sts128(a + (((2 * t + c) ^ (R & 7)) << 4),
                               pack_bf16(acc[l][m][0][2 * hi], acc[l][m][1][2 * hi]),
                               pack_bf16(acc[l][m][0][2 * hi + 1], acc[l][m][1][2 * hi + 1]),
                               pack_bf16(acc[l][m + 1][0][2 * hi], acc[l][m + 1][1][2 * hi]),
                               pack_bf16(acc[l][m + 1][0][2 * hi + 1], acc[l][m + 1][1][2 * hi + 1]));
                    }
                }
        }
        asm volatile("fence.proxy.async.shared::cta;" ::: "memory");
        uint32_t wa[8][4];
        {
            const int r = lane & 7, k = (lane >> 4) * 8 + r;
            const int chunk = (2 * warp + ((lane >> 3) & 1)) ^ r;
#pragma unroll
            for (int ks = 0; ks < 8; ks++) {
                const int c = (ks >> 2) * 64 + 16 * (k >> 2) + 4 * (ks & 3) + (k & 3);
                asm volatile("ldmatrix.sync.aligned.m8n8.x4.trans.shared.b16 {%0,%1,%2,%3}, [%4];"
                             : "=r"(wa[ks][0]), "=r"(wa[ks][1]), "=r"(wa[ks][2]), "=r"(wa[ks][3])
                             : "r"(sb + SM_W + c * 256 + (chunk << 4)));
            }
        }
        asm volatile("bar.sync 1, 256;" ::: "memory");
        STAMP(8);
        const int sl = (lane & 7) * 4 + (lane >> 3);
        __nv_bfloat16* op = out + (size_t)(blk * NPB + (lane >> 3)) * 512 + warp * 64 + (lane & 7) * 8;
        const int nleft = N_NODES - blk * NPB - (lane >> 3);
#pragma unroll 1
        for (int tm = 0; tm < 4; tm++) {
            float o[40];
            asm volatile("wgmma.fence.sync.aligned;" ::: "memory");
#pragma unroll
            for (int ks = 0; ks < 8; ks++) {
                const uint32_t a = sb + tm * AGGT + (ks >> 2) * 10240 + (ks & 3) * 32;
                const uint64_t desc = (uint64_t)((a & 0x3ffff) >> 4) | (1ull << 16) | (64ull << 32) | (1ull << 62);
                wgmma_n80(o, wa[ks], desc, ks);
            }
            asm volatile("wgmma.commit_group.sync.aligned;" ::: "memory");
            asm volatile("wgmma.wait_group.sync.aligned 0;" ::: "memory");
#pragma unroll
            for (int i = 0; i < 40; i++) asm volatile("" : "+f"(o[i])::"memory");
#pragma unroll
            for (int l = 0; l < 5; l++) {
                uint4 v;
                v.x = __shfl_sync(~0u, pack_bf16(o[8 * l + 0], o[8 * l + 1]), sl);
                v.y = __shfl_sync(~0u, pack_bf16(o[8 * l + 4], o[8 * l + 5]), sl);
                v.z = __shfl_sync(~0u, pack_bf16(o[8 * l + 2], o[8 * l + 3]), sl);
                v.w = __shfl_sync(~0u, pack_bf16(o[8 * l + 6], o[8 * l + 7]), sl);
                if ((l < 4 || lane < 24) && tm * 19 + l * 4 < nleft)
                    *reinterpret_cast<uint4*>(op + (tm * 19 + l * 4) * 512) = v;
            }
        }
        STAMP(9);
        }
    }
}

}

extern "C" void kernel_launch(void* const* d_in, const int* in_sizes, int n_in, void* d_out, int out_size) {
    (void)in_sizes; (void)n_in; (void)out_size;
    const __nv_bfloat16* x = (const __nv_bfloat16*)d_in[0];
    const int* src = (const int*)d_in[1];
    const int* dst = (const int*)d_in[2];
    const __nv_bfloat16* Y = (const __nv_bfloat16*)d_in[3];
    const __nv_bfloat16* ef = (const __nv_bfloat16*)d_in[4];
    const __nv_bfloat16* w_rad = (const __nv_bfloat16*)d_in[5];
    const __nv_bfloat16* cg = (const __nv_bfloat16*)d_in[6];
    const __nv_bfloat16* w_mix = (const __nv_bfloat16*)d_in[7];
    __nv_bfloat16* out = (__nv_bfloat16*)d_out;

    static int sms = 0;
    if (sms == 0) {
        int dev = 0;
        cudaGetDevice(&dev);
        cudaDeviceGetAttribute(&sms, cudaDevAttrMultiProcessorCount, dev);
        cudaFuncSetAttribute(tfn_kernel<3>, cudaFuncAttributeMaxDynamicSharedMemorySize, SM_TOTAL);
        cudaFuncSetAttribute(tfn_kernel<1>, cudaFuncAttributeMaxDynamicSharedMemorySize, SM_TOTAL);
        cudaFuncSetAttribute(tfn_kernel<2>, cudaFuncAttributeMaxDynamicSharedMemorySize, SM_TOTAL);
    }
    if (sms >= NB) {
        tfn_kernel<3><<<NB, NTHR, SM_TOTAL>>>(x, src, dst, Y, ef, w_rad, cg, w_mix, out);
    } else {
        tfn_kernel<1><<<NB, NTHR, SM_TOTAL>>>(x, src, dst, Y, ef, w_rad, cg, w_mix, out);
        tfn_kernel<2><<<NB, NTHR, SM_TOTAL>>>(x, src, dst, Y, ef, w_rad, cg, w_mix, out);
    }
}
```

```cpp
#include <cuda_runtime.h>
#include <cuda_bf16.h>
#include <stdint.h>

namespace {

constexpr int N_NODES = 10000;
constexpr int N_EDGES = 320000;
constexpr int NB      = 132;
constexpr int NPB     = 76;
constexpr int NSRC    = 128;
constexpr int EPC     = N_EDGES / NSRC;
constexpr int NTHR    = 512;
#define NGS 5
constexpr int NG      = NGS;
constexpr int ROWP    = 2176;
constexpr int STAGE   = 4 * ROWP + 128;
constexpr int UCAP    = 104;
constexpr int REC     = 52;
constexpr int NBK     = 80;
constexpr int HS      = 81;

#define PACE_Q8 635
#define PACE_LEAD 300
#define PACE_HEAD 705
#define HEAD_BK 10
#define PACE_TAIL 610
#define TAIL_BK 66
#define IDLE_EST 900
#define POLL_DELAY 1280
#define LEAD_CLK 140
#define ROWMODE 1
#define PAIRING 1
#define FEEDBACK 1
#define FB_GAIN 24
#define FB_DOWN 4
#define FB_MIN 0
#define START_NS 3150

constexpr int SM_RING  = 0;
constexpr int SM_W     = 4 * NG * STAGE;
constexpr int SM_REC   = SM_W + 32768;
constexpr int SM_MISC  = SM_REC + 4 * UCAP * REC;
constexpr int SM_TOTAL = SM_MISC + 224;
constexpr int SC_MAIL  = 1 * STAGE;
constexpr int SC_CNT   = 3 * STAGE;
constexpr int SC_DUMP  = 3 * STAGE + 1024;
constexpr int SC_XTRA  = 3 * STAGE + 2048;
constexpr int SC_HIST  = 4 * STAGE;
constexpr int SC_GPOS  = 6 * STAGE;
constexpr int SC_WR    = 7 * STAGE;
constexpr int GDUMMY   = 1024;
constexpr int AGGT     = (NG * STAGE + 1023) / 1024 * 1024;
static_assert(3 * AGGT + 20480 <= 4 * NG * STAGE, "agg tile inside the team's ring");
static_assert(NPB * 512 * 4 <= 4 * NG * STAGE, "slow tile");
static_assert(SM_TOTAL <= 232448, "smem");
static_assert(SM_REC % 16 == 0 && (4 * UCAP * REC) % 16 == 0 && SM_MISC % 16 == 0, "align");
constexpr int MI_XN = 0;
constexpr int MI_TMAX = 2;
constexpr int MI_SHIFT = 48;
constexpr int MI_NU = 8;
constexpr int MI_END = 28;
constexpr int MI_T0 = 3;

__device__ uint4 g_mail[NB * NSRC * 8];
__device__ uint32_t g_mail2[NB * NSRC * 32];
__device__ __align__(128) int g_lag[2 * NB][32];
#define STAMP(k)

__device__ __forceinline__ uint32_t smem_u32(const void* p) { return (uint32_t)__cvta_generic_to_shared(p); }
__device__ __forceinline__ uint32_t atoms_inc(uint32_t a) {
    uint32_t r;
    asm volatile("atom.shared.add.u32 %0, [%1], 1;" : "=r"(r) : "r"(a) : "memory");
    return r;
}
__device__ __forceinline__ void sts32(uint32_t a, uint32_t v) { asm volatile("st.shared.u32 [%0], %1;" ::"r"(a), "r"(v) : "memory"); }
__device__ __forceinline__ void sts16(uint32_t a, uint32_t v) { asm volatile("st.shared.u16 [%0], %1;" ::"r"(a), "h"((uint16_t)v) : "memory"); }
__device__ __forceinline__ void sts8(uint32_t a, uint32_t v) { asm volatile("st.shared.u8 [%0], %1;" ::"r"(a), "r"(v) : "memory"); }
__device__ __forceinline__ uint32_t lds32(uint32_t a) { uint32_t v; asm volatile("ld.shared.u32 %0, [%1];" : "=r"(v) : "r"(a)); return v; }
__device__ __forceinline__ uint32_t lds16(uint32_t a) { uint32_t v; asm volatile("ld.shared.u16 %0, [%1];" : "=r"(v) : "r"(a)); return v; }
__device__ __forceinline__ void cp16(uint32_t d, const void* p) {
    asm volatile("cp.async.cg.shared.global [%0], [%1], 16;" ::"r"(d), "l"(p) : "memory");
}
__device__ __forceinline__ uint32_t gtime() {
    uint32_t t;
    asm volatile("mov.u32 %0, %%globaltimer_lo;" : "=r"(t));
    return t;
}
__device__ __forceinline__ void mbar_init(uint32_t bar, int cnt) {
    asm volatile("mbarrier.init.shared.b64 [%0], %1;" ::"r"(bar), "r"(cnt) : "memory");
}
__device__ __forceinline__ void mbar_wait(uint32_t bar, uint32_t parity) {
    asm volatile("{\n.reg .pred p;\n.reg .u32 n;\nmov.u32 n, 0;\n"
                 "WAIT_%=:\nmbarrier.try_wait.parity.shared.b64 p, [%0], %1;\n@p bra DONE_%=;\n"
                 "add.u32 n, n, 1;\nsetp.lt.u32 p, n, 4194304;\n@p bra WAIT_%=;\ntrap;\nDONE_%=:\n}"
                 ::"r"(bar), "r"(parity) : "memory");
}
__device__ __forceinline__ void mbar_arrive_elect(uint32_t bar) {
    asm volatile("{\n.reg .pred p;\nelect.sync _|p, 0xffffffff;\n@p mbarrier.arrive.shared.b64 _, [%0];\n}" ::"r"(bar) : "memory");
}
__device__ __forceinline__ uint4 lds128(uint32_t a) {
    uint4 v;
    asm volatile("ld.shared.v4.u32 {%0,%1,%2,%3}, [%4];" : "=r"(v.x), "=r"(v.y), "=r"(v.z), "=r"(v.w) : "r"(a));
    return v;
}
__device__ __forceinline__ void sts128(uint32_t a, uint32_t x, uint32_t y, uint32_t z, uint32_t w) {
    asm volatile("st.shared.v4.u32 [%0], {%1,%2,%3,%4};" ::"r"(a), "r"(x), "r"(y), "r"(z), "r"(w) : "memory");
}
__device__ __forceinline__ uint32_t pack_bf16(float lo, float hi) {
    uint32_t r;
    asm("cvt.rn.bf16x2.f32 %0, %1, %2;" : "=r"(r) : "f"(hi), "f"(lo));
    return r;
}
__device__ __forceinline__ float tanh_fast(float x) {
    float r;
    asm("tanh.approx.f32 %0, %1;" : "=f"(r) : "f"(x));
    return r;
}
__device__ __forceinline__ uint32_t mul_lo(uint32_t v, uint32_t r) {
    __nv_bfloat162 a = *reinterpret_cast<__nv_bfloat162*>(&v), b = *reinterpret_cast<__nv_bfloat162*>(&r);
    __nv_bfloat162 c = __hmul2(a, __low2bfloat162(b));
    return *reinterpret_cast<uint32_t*>(&c);
}
__device__ __forceinline__ uint32_t mul_hi(uint32_t v, uint32_t r) {
    __nv_bfloat162 a = *reinterpret_cast<__nv_bfloat162*>(&v), b = *reinterpret_cast<__nv_bfloat162*>(&r);
    __nv_bfloat162 c = __hmul2(a, __high2bfloat162(b));
    return *reinterpret_cast<uint32_t*>(&c);
}
__device__ __forceinline__ void mma0(float (&d)[4], uint32_t a0, uint32_t a1, uint32_t a2, uint32_t a3,
                                     uint32_t b0, uint32_t b1) {
    asm("mma.sync.aligned.m16n8k16.row.col.f32.bf16.bf16.f32 {%0,%1,%2,%3}, {%4,%5,%6,%7}, {%8,%9}, {%10,%10,%10,%10};"
        : "=f"(d[0]), "=f"(d[1]), "=f"(d[2]), "=f"(d[3])
        : "r"(a0), "r"(a1), "r"(a2), "r"(a3), "r"(b0), "r"(b1), "f"(0.f));
}
__device__ __forceinline__ void mma0_k8(float (&d)[4], uint32_t a0, uint32_t a1, uint32_t b0) {
    asm("mma.sync.aligned.m16n8k8.row.col.f32.bf16.bf16.f32 {%0,%1,%2,%3}, {%4,%5}, {%6}, {%7,%7,%7,%7};"
        : "=f"(d[0]), "=f"(d[1]), "=f"(d[2]), "=f"(d[3])
        : "r"(a0), "r"(a1), "r"(b0), "f"(0.f));
}
__device__ __forceinline__ void mma_acc(float (&d)[4], const uint32_t (&a)[4], uint32_t b0, uint32_t b1) {
    asm volatile("mma.sync.aligned.m16n8k16.row.col.f32.bf16.bf16.f32 {%0,%1,%2,%3}, {%4,%5,%6,%7}, {%8,%9}, {%0,%1,%2,%3};"
        : "+f"(d[0]), "+f"(d[1]), "+f"(d[2]), "+f"(d[3])
        : "r"(a[0]), "r"(a[1]), "r"(a[2]), "r"(a[3]), "r"(b0), "r"(b1));
}
__device__ __forceinline__ void wgmma_n80(float (&d)[40], const uint32_t (&a)[4], uint64_t desc, int scale_d) {
    asm volatile("{\n.reg .pred p;\nsetp.ne.b32 p, %45, 0;\n"
        "wgmma.mma_async.sync.aligned.m64n80k16.f32.bf16.bf16 "
        "{%0,%1,%2,%3,%4,%5,%6,%7,%8,%9,%10,%11,%12,%13,%14,%15,%16,%17,%18,%19,"
        "%20,%21,%22,%23,%24,%25,%26,%27,%28,%29,%30,%31,%32,%33,%34,%35,%36,%37,%38,%39}, "
        "{%40,%41,%42,%43}, %44, p, 1, 1, 0;\n}"
        : "+f"(d[0]), "+f"(d[1]), "+f"(d[2]), "+f"(d[3]), "+f"(d[4]), "+f"(d[5]), "+f"(d[6]), "+f"(d[7]),
          "+f"(d[8]), "+f"(d[9]), "+f"(d[10]), "+f"(d[11]), "+f"(d[12]), "+f"(d[13]), "+f"(d[14]), "+f"(d[15]),
          "+f"(d[16]), "+f"(d[17]), "+f"(d[18]), "+f"(d[19]), "+f"(d[20]), "+f"(d[21]), "+f"(d[22]), "+f"(d[23]),
          "+f"(d[24]), "+f"(d[25]), "+f"(d[26]), "+f"(d[27]), "+f"(d[28]), "+f"(d[29]), "+f"(d[30]), "+f"(d[31]),
          "+f"(d[32]), "+f"(d[33]), "+f"(d[34]), "+f"(d[35]), "+f"(d[36]), "+f"(d[37]), "+f"(d[38]), "+f"(d[39])
        : "r"(a[0]), "r"(a[1]), "r"(a[2]), "r"(a[3]), "l"(desc), "r"(scale_d));
}

__device__ __forceinline__ void producer_loop(const void* xl, const void* efl, const void* Y, uint32_t xd, uint32_t oef,
                                              uint32_t ysel, uint32_t ring, uint32_t rec, uint32_t rlast, uint32_t odd,
                                              uint32_t lag, uint32_t xh) {
    asm volatile(
        "{\n"
        ".reg .b32 w, em, ey, cu, d, t, u, n, sa, ph, rp, rend, rlast, dy, sv, lag, lv, w2, w3, w4;\n"
        ".reg .b16 tg;\n"
        ".reg .b64 pa, pb, pc, pd;\n"
        ".reg .pred lo, z, q, e, zb, fbk;\n"
        "redux.sync.or.b32 sa, %6, 0xffffffff;\n"
        "redux.sync.or.b32 rp, %7, 0xffffffff;\n"
        "redux.sync.or.b32 rlast, %8, 0xffffffff;\n"
        "redux.sync.or.b32 lag, %11, 0xffffffff;\n"
        "setp.eq.u32 fbk, %9, 0;\n"
        "add.u32 rend, sa, 44160;\n"
        "and.b32 t, %5, 1;\n"
        "setp.eq.u32 lo, t, 0;\n"
        "mov.u32 ph, 1;\n"
        "setp.ge.u32 q, %9, 4;\n"
        "@q bra.uni PODD_%=;\n"
        "add.u32 t, rp, %4;\n"
        "ld.shared.u32 em, [t+16];\n"
        "and.b32 t, em, 0xfffffff8;\n"
        "mad.wide.u32 pa, t, 4, %1;\n"
        "add.u32 d, sa, %3;\n"
        "@lo cp.async.cg.shared.global [d+2048], [pa], 16;\n"
        "cp.async.mbarrier.arrive.noinc.shared.b64 [sa+8704];\n"
        "add.u32 rp, rp, 52;\n"
        "add.u32 sa, sa, 8832;\n"
        "PODD_%=:\n"
        "add.u32 rp, rp, 52;\n"
        "add.u32 sa, sa, 8832;\n"
        "shr.u32 t, %4, 1;\n"
        "and.b32 t, t, 4;\n"
        "add.u32 t, t, rp;\n"
        "ld.shared.u32 w, [t];\n"
        "ld.shared.u32 w2, [t+8];\n"
        "add.u32 t, rp, %4;\n"
        "ld.shared.u32 em, [t+16];\n"
        "ld.shared.u32 ey, [t+-36];\n"
        "ld.shared.u32 cu, [rp+48];\n"
        "ld.volatile.shared.u32 sv, [lag];\n"
        "setp.eq.u32 e, sa, sa;\n"
        "setp.lt.u32 q, rp, rlast;\n"
        "@!q bra.uni PF_%=;\n"
        "PL_%=:\n"
        "add.u32 cu, cu, sv;\n"
        "mov.u32 u, %%clock;\n"
        "shl.b32 u, u, 14;\n"
        "sub.u32 u, u, cu;\n"
        "setp.ge.and.s32 q, u, 0, e;\n"
        "@q bra.uni PGO_%=;\n"
        "mov.u32 n, 0;\n"
        "PW1_%=:\n"
        "@e bra.uni PW2_%=;\n"
        "mbarrier.try_wait.parity.shared.b64 e, [sa+8712], ph;\n"
        "add.u32 n, n, 1;\n"
        "setp.lt.u32 q, n, 4194304;\n"
        "@q bra.uni PW1_%=;\n"
        "trap;\n"
        "PW2_%=:\n"
        "mov.u32 u, %%clock;\n"
        "shl.b32 u, u, 14;\n"
        "sub.u32 u, u, cu;\n"
        "setp.lt.s32 q, u, 0;\n"
        "@q bra.uni PW2_%=;\n"
        "PGO_%=:\n"
        "st.volatile.shared.u32 [lag+24], u;\n"
        "and.b32 t, em, 0xfffffff8;\n"
        "mad.wide.u32 pa, t, 4, %1;\n"
        "and.b32 t, w, 0xffff;\n"
        "mad.wide.u32 pc, t, 1024, %0;\n"
        "shr.u32 t, w, 16;\n"
        "mad.wide.u32 pd, t, 1024, %0;\n"
        "add.u32 d, sa, %3;\n"
        "@lo cp.async.cg.shared.global [d+2048], [pa], 16;\n"
        "xor.b32 t, ey, %5;\n"
        "and.b32 t, t, 7;\n"
        "setp.ne.u32 zb, t, 0;\n"
        "and.b32 t, ey, 0xfffffff8;\n"
        "cvt.u64.u32 pb, t;\n"
        "add.u64 pb, pb, %2;\n"
        "selp.u32 dy, 64, 8, lo;\n"
        "xor.b32 dy, dy, d;\n"
        "cp.async.ca.shared.global [dy+2048], [pb], 8, zb;\n"
        "add.u32 d, sa, %12;\n"
        "cp.async.cg.shared.global [d+0], [pc+0], 16;\n"
        "cp.async.cg.shared.global [d+256], [pc+256], 16;\n"
        "cp.async.cg.shared.global [d+512], [pc+512], 16;\n"
        "cp.async.cg.shared.global [d+768], [pc+768], 16;\n"
        "cp.async.cg.shared.global [d+1024], [pd+0], 16;\n"
        "cp.async.cg.shared.global [d+1280], [pd+256], 16;\n"
        "cp.async.cg.shared.global [d+1536], [pd+512], 16;\n"
        "cp.async.cg.shared.global [d+1792], [pd+768], 16;\n"
        "xor.b32 dy, d, 64;\n"
        "and.b32 t, w2, 0xffff;\n"
        "mad.wide.u32 pa, t, 1024, %0;\n"
        "cp.async.cg.shared.global [dy+4352], [pa+0], 16;\n"
        "cp.async.cg.shared.global [dy+4608], [pa+256], 16;\n"
        "cp.async.cg.shared.global [dy+4864], [pa+512], 16;\n"
        "cp.async.cg.shared.global [dy+5120], [pa+768], 16;\n"
        "shr.u32 t, w2, 16;\n"
        "mad.wide.u32 pb, t, 1024, %0;\n"
        "cp.async.cg.shared.global [dy+5376], [pb+0], 16;\n"
        "cp.async.cg.shared.global [dy+5632], [pb+256], 16;\n"
        "cp.async.cg.shared.global [dy+5888], [pb+512], 16;\n"
        "cp.async.cg.shared.global [dy+6144], [pb+768], 16;\n"
        "add.u32 rp, rp, 104;\n"
        "shr.u32 t, %4, 1;\n"
        "and.b32 t, t, 4;\n"
        "add.u32 t, t, rp;\n"
        "ld.shared.u32 w, [t];\n"
        "ld.shared.u32 w2, [t+8];\n"
        "add.u32 t, rp, %4;\n"
        "ld.shared.u32 em, [t+16];\n"
        "ld.shared.u32 ey, [t+-36];\n"
        "ld.shared.u32 cu, [rp+48];\n"
        "ld.volatile.shared.u32 sv, [lag];\n"
        "cp.async.mbarrier.arrive.noinc.shared.b64 [sa+8704];\n"
        "add.u32 sa, sa, 17664;\n"
        "sub.u32 t, sa, 44160;\n"
        "setp.ge.u32 q, sa, rend;\n"
        "selp.u32 sa, t, sa, q;\n"
        "selp.u32 t, 1, 0, q;\n"
        "xor.b32 ph, ph, t;\n"
        "mbarrier.try_wait.parity.shared.b64 e, [sa+8712], ph;\n"
        "@!fbk bra.uni PC_%=;\n"
        "ld.volatile.shared.u32 u, [lag+24];\n"
        "shr.s32 u, u, 16;\n"
        "ld.volatile.shared.u64 pa, [lag+16];\n"
        "elect.sync _|z, 0xffffffff;\n"
        "@z st.relaxed.gpu.global.u32 [pa], u;\n"
        "@z cp.async.cg.shared.global [lag], [pa+16896], 16;\n"
        "PC_%=:\n"
        "setp.lt.u32 q, rp, rlast;\n"
        "@q bra.uni PL_%=;\n"
        "PF_%=:\n"
        "setp.ne.u32 q, rp, rlast;\n"
        "@q bra.uni PX_%=;\n"
        "mov.u32 n, 0;\n"
        "PE1_%=:\n"
        "@e bra.uni PE2_%=;\n"
        "mbarrier.try_wait.parity.shared.b64 e, [sa+8712], ph;\n"
        "add.u32 n, n, 1;\n"
        "setp.lt.u32 q, n, 4194304;\n"
        "@q bra.uni PE1_%=;\n"
        "trap;\n"
        "PE2_%=:\n"
        "cp.async.mbarrier.arrive.noinc.shared.b64 [sa+8704];\n"
        "PX_%=:\n"
        "}\n"
        ::"l"(xl), "l"(efl), "l"(Y), "r"(xd), "r"(oef), "r"(ysel), "r"(ring), "r"(rec), "r"(rlast), "r"(odd),
          "n"(0), "r"(lag), "r"(xh) : "memory");
}

__device__ __forceinline__ void consumer_loop(float (&acc)[5][4][2][4], const uint32_t (&wf)[4][4], const uint32_t (&cgf)[4],
                                              uint32_t xoff, uint32_t& ring, uint32_t moff, uint32_t rec) {
    asm volatile(
        "{\n"
        ".reg .b32 x<16>, a<4>, b<4>, r<4>, m<4>, rl, rh, tag, la, lb, sa, last, ph, tq, xa, ma, n, ring, sn, ln, yb, zz, k<4>, tp;\n"
        ".reg .b16 lo, hi;\n"
        ".reg .f32 p<16>, d<4>, t0, t1, fz;\n"
        ".reg .pred q, w, el, c<5>;\n"
        "TA_%=: .branchtargets A0_%=, A1_%=, A2_%=, A3_%=, A4_%=, EXIT_%=;\n"
        "TB_%=: .branchtargets B0_%=, B1_%=, B2_%=, B3_%=, B4_%=, SPIN_%=;\n"
        "mov.f32 fz, 0f00000000;\n"
        "redux.sync.or.b32 ring, %160, 0xffffffff;\n"
        "mov.u32 sa, ring;\n"
        "add.u32 last, ring, 35328;\n"
        "mov.u32 ph, 0;\n"
        "redux.sync.xor.b32 zz, %160, 0xffffffff;\n"
        "redux.sync.or.b32 tp, %183, 0xffffffff;\n"
        "elect.sync _|el, 0xffffffff;\n"
        "mov.u32 k0, sa;\n"
        "mov.u32 k1, sa;\n"
        "mov.u32 k2, sa;\n"
        "mov.u32 k3, sa;\n"
        "mov.b32 x0, 0;\n"
        "mov.b32 x1, 0;\n"
        "mov.b32 x2, 0;\n"
        "mov.b32 x3, 0;\n"
        "mov.b32 x4, 0;\n"
        "mov.b32 x5, 0;\n"
        "mov.b32 x6, 0;\n"
        "mov.b32 x7, 0;\n"
        "mov.b32 x8, 0;\n"
        "mov.b32 x9, 0;\n"
        "mov.b32 x10, 0;\n"
        "mov.b32 x11, 0;\n"
        "mov.b32 x12, 0;\n"
        "mov.b32 x13, 0;\n"
        "mov.b32 x14, 0;\n"
        "mov.b32 x15, 0;\n"
        "mov.b32 b0, 0;\n"
        "mov.b32 r0, 0;\n"
        "mov.b32 b1, 0;\n"
        "mov.b32 r1, 0;\n"
        "mov.b32 b2, 0;\n"
        "mov.b32 r2, 0;\n"
        "mov.b32 b3, 0;\n"
        "mov.b32 r3, 0;\n"
        "mov.u32 lb, 0;\n"
        "mov.u32 n, 0;\n"
        "W0_%=:\n"
        "mbarrier.try_wait.parity.shared.b64 w, [sa+8704], 0;\n"
        "@w bra.uni W0D_%=;\n"
        "add.u32 n, n, 1;\n"
        "setp.lt.u32 q, n, 4194304;\n"
        "@q bra.uni W0_%=;\n"
        "trap;\n"
        "W0D_%=:\n"
        "add.u32 ma, sa, %182;\n"
        "ldmatrix.sync.aligned.m8n8.x4.shared.b16 {m0,m1,m2,m3}, [ma];\n"
        "ld.shared.u16 tag, [tp+48];\n"
        "add.u32 tp, tp, 52;\n"
        "add.u32 sn, sa, 8832;\n"
        "setp.eq.u32 q, sa, last;\n"
        "selp.u32 sn, ring, sn, q;\n"
        "selp.u32 tq, 1, 0, q;\n"
        "xor.b32 ph, ph, tq;\n"
        "mbarrier.test_wait.parity.shared.b64 w, [sn+8704], ph;\n"
        "mma.sync.aligned.m16n8k16.row.col.f32.bf16.bf16.f32 {p0,p1,p2,p3}, {%161,%162,%163,%164}, {m2,m3}, {fz,fz,fz,fz};\n"
        "mma.sync.aligned.m16n8k16.row.col.f32.bf16.bf16.f32 {p4,p5,p6,p7}, {%165,%166,%167,%168}, {m2,m3}, {fz,fz,fz,fz};\n"
        "mma.sync.aligned.m16n8k16.row.col.f32.bf16.bf16.f32 {p8,p9,p10,p11}, {%169,%170,%171,%172}, {m2,m3}, {fz,fz,fz,fz};\n"
        "mma.sync.aligned.m16n8k16.row.col.f32.bf16.bf16.f32 {p12,p13,p14,p15}, {%173,%174,%175,%176}, {m2,m3}, {fz,fz,fz,fz};\n"
        "@el mbarrier.arrive.shared.b64 _, [k0+8712];\n"
        "redux.sync.or.b32 ln, tag, 0xffffffff;\n"
        "mov.u32 sa, sn;\n"
        "add.u32 k0, sn, zz;\n"
        "SPIN_%=:\n"
        "mov.u32 n, 0;\n"
        "SP1_%=:\n"
        "mbarrier.try_wait.parity.shared.b64 w, [sa+8704], ph;\n"
        "@w bra.uni SP2_%=;\n"
        "add.u32 n, n, 1;\n"
        "setp.lt.u32 q, n, 4194304;\n"
        "@q bra.uni SP1_%=;\n"
        "trap;\n"
        "SP2_%=:\n"
        "brx.idx.uni lb, TB_%=;\n"
        "A0_%=:\n"
        "add.u32 xa, sa, %181;\n"
        "add.u32 ma, sa, %182;\n"
        "ldmatrix.sync.aligned.m8n8.x4.shared.b16 {m0,m1,m2,m3}, [ma];\n"
        "ld.shared.u16 tag, [tp+48];\n"
        "add.u32 tp, tp, 52;\n"
        "add.u32 sn, sa, 8832;\n"
        "setp.eq.u32 q, sa, last;\n"
        "selp.u32 sn, ring, sn, q;\n"
        "selp.u32 tq, 1, 0, q;\n"
        "xor.b32 ph, ph, tq;\n"
        "mbarrier.test_wait.parity.shared.b64 w, [sn+8704], ph;\n"
        "mma.sync.aligned.m16n8k16.row.col.f32.bf16.bf16.f32 {%0,%1,%2,%3}, {a0,a1,a2,a3}, {x0,x1}, {%0,%1,%2,%3};\n"
        "mma.sync.aligned.m16n8k16.row.col.f32.bf16.bf16.f32 {%4,%5,%6,%7}, {a0,a1,a2,a3}, {x2,x3}, {%4,%5,%6,%7};\n"
        "ld.shared.v4.u32 {x0,x1,x2,x3}, [xa+1024];\n"
        "tanh.approx.f32 t0, p1;\n"
        "tanh.approx.f32 t1, p3;\n"
        "fma.rn.f32 t0, p1, t0, p1;\n"
        "fma.rn.f32 t1, p3, t1, p3;\n"
        "cvt.rn.bf16x2.f32 r0, t1, t0;\n"
        "mma.sync.aligned.m16n8k16.row.col.f32.bf16.bf16.f32 {p0,p1,p2,p3}, {%161,%162,%163,%164}, {m2,m3}, {fz,fz,fz,fz};\n"
        "mma.sync.aligned.m16n8k16.row.col.f32.bf16.bf16.f32 {%8,%9,%10,%11}, {a0,a1,a2,a3}, {x4,x5}, {%8,%9,%10,%11};\n"
        "mma.sync.aligned.m16n8k16.row.col.f32.bf16.bf16.f32 {%12,%13,%14,%15}, {a0,a1,a2,a3}, {x6,x7}, {%12,%13,%14,%15};\n"
        "ld.shared.v4.u32 {x4,x5,x6,x7}, [xa+1152];\n"
        "mma.sync.aligned.m16n8k8.row.col.f32.bf16.bf16.f32 {d0,d1,d2,d3}, {%177,%178}, {m1}, {fz,fz,fz,fz};\n"
        "cvt.rn.bf16x2.f32 b0, d2, d0;\n"
        "cvt.rn.bf16x2.f32 b1, d3, d1;\n"
        "tanh.approx.f32 t0, p5;\n"
        "tanh.approx.f32 t1, p7;\n"
        "fma.rn.f32 t0, p5, t0, p5;\n"
        "fma.rn.f32 t1, p7, t1, p7;\n"
        "cvt.rn.bf16x2.f32 r1, t1, t0;\n"
        "mma.sync.aligned.m16n8k16.row.col.f32.bf16.bf16.f32 {p4,p5,p6,p7}, {%165,%166,%167,%168}, {m2,m3}, {fz,fz,fz,fz};\n"
        "mov.b32 {lo,hi}, r2;\n"
        "mov.b32 rl, {lo,lo};\n"
        "mov.b32 rh, {hi,hi};\n"
        "mul.bf16x2 x8, x8, rl;\n"
        "mul.bf16x2 x9, x9, rl;\n"
        "mul.bf16x2 x10, x10, rh;\n"
        "mul.bf16x2 x11, x11, rh;\n"
        "mma.sync.aligned.m16n8k16.row.col.f32.bf16.bf16.f32 {%16,%17,%18,%19}, {a0,a1,a2,a3}, {x8,x9}, {%16,%17,%18,%19};\n"
        "mma.sync.aligned.m16n8k16.row.col.f32.bf16.bf16.f32 {%20,%21,%22,%23}, {a0,a1,a2,a3}, {x10,x11}, {%20,%21,%22,%23};\n"
        "ld.shared.v4.u32 {x8,x9,x10,x11}, [xa+1280];\n"
        "mma.sync.aligned.m16n8k8.row.col.f32.bf16.bf16.f32 {d0,d1,d2,d3}, {%179,%180}, {m1}, {fz,fz,fz,fz};\n"
        "cvt.rn.bf16x2.f32 b2, d2, d0;\n"
        "cvt.rn.bf16x2.f32 b3, d3, d1;\n"
        "tanh.approx.f32 t0, p9;\n"
        "tanh.approx.f32 t1, p11;\n"
        "fma.rn.f32 t0, p9, t0, p9;\n"
        "fma.rn.f32 t1, p11, t1, p11;\n"
        "cvt.rn.bf16x2.f32 r2, t1, t0;\n"
        "mma.sync.aligned.m16n8k16.row.col.f32.bf16.bf16.f32 {p8,p9,p10,p11}, {%169,%170,%171,%172}, {m2,m3}, {fz,fz,fz,fz};\n"
        "selp.u32 tq, lb, 5, w;\n"
        "mov.b32 {lo,hi}, r3;\n"
        "mov.b32 rl, {lo,lo};\n"
        "mov.b32 rh, {hi,hi};\n"
        "mul.bf16x2 x12, x12, rl;\n"
        "mul.bf16x2 x13, x13, rl;\n"
        "mul.bf16x2 x14, x14, rh;\n"
        "mul.bf16x2 x15, x15, rh;\n"
        "mma.sync.aligned.m16n8k16.row.col.f32.bf16.bf16.f32 {%24,%25,%26,%27}, {a0,a1,a2,a3}, {x12,x13}, {%24,%25,%26,%27};\n"
        "mma.sync.aligned.m16n8k16.row.col.f32.bf16.bf16.f32 {%28,%29,%30,%31}, {a0,a1,a2,a3}, {x14,x15}, {%28,%29,%30,%31};\n"
        "ld.shared.v4.u32 {x12,x13,x14,x15}, [xa+1408];\n"
        "@el mbarrier.arrive.shared.b64 _, [k0+8712];\n"
        "redux.sync.or.b32 ln, tag, 0xffffffff;\n"
        "mov.u32 sa, sn;\n"
        "add.u32 k0, sn, zz;\n"
        "tanh.approx.f32 t0, p13;\n"
        "tanh.approx.f32 t1, p15;\n"
        "fma.rn.f32 t0, p13, t0, p13;\n"
        "fma.rn.f32 t1, p15, t1, p15;\n"
        "cvt.rn.bf16x2.f32 r3, t1, t0;\n"
        "mma.sync.aligned.m16n8k16.row.col.f32.bf16.bf16.f32 {p12,p13,p14,p15}, {%173,%174,%175,%176}, {m2,m3}, {fz,fz,fz,fz};\n"
        "mov.b32 {lo,hi}, r0;\n"
        "mov.b32 rl, {lo,lo};\n"
        "mov.b32 rh, {hi,hi};\n"
        "mul.bf16x2 x0, x0, rl;\n"
        "mul.bf16x2 x1, x1, rl;\n"
        "mul.bf16x2 x2, x2, rh;\n"
        "mul.bf16x2 x3, x3, rh;\n"
        "mov.b32 {lo,hi}, r1;\n"
        "mov.b32 rl, {lo,lo};\n"
        "mov.b32 rh, {hi,hi};\n"
        "mul.bf16x2 x4, x4, rl;\n"
        "mul.bf16x2 x5, x5, rl;\n"
        "mul.bf16x2 x6, x6, rh;\n"
        "mul.bf16x2 x7, x7, rh;\n"
        "brx.idx.uni tq, TB_%=;\n"
        "A1_%=:\n"
        "add.u32 xa, sa, %181;\n"
        "add.u32 ma, sa, %182;\n"
        "ldmatrix.sync.aligned.m8n8.x4.shared.b16 {m0,m1,m2,m3}, [ma];\n"
        "ld.shared.u16 tag, [tp+48];\n"
        "add.u32 tp, tp, 52;\n"
        "add.u32 sn, sa, 8832;\n"
        "setp.eq.u32 q, sa, last;\n"
        "selp.u32 sn, ring, sn, q;\n"
        "selp.u32 tq, 1, 0, q;\n"
        "xor.b32 ph, ph, tq;\n"
        "mbarrier.test_wait.parity.shared.b64 w, [sn+8704], ph;\n"
        "mma.sync.aligned.m16n8k16.row.col.f32.bf16.bf16.f32 {%32,%33,%34,%35}, {a0,a1,a2,a3}, {x0,x1}, {%32,%33,%34,%35};\n"
        "mma.sync.aligned.m16n8k16.row.col.f32.bf16.bf16.f32 {%36,%37,%38,%39}, {a0,a1,a2,a3}, {x2,x3}, {%36,%37,%38,%39};\n"
        "ld.shared.v4.u32 {x0,x1,x2,x3}, [xa+1024];\n"
        "tanh.approx.f32 t0, p1;\n"
        "tanh.approx.f32 t1, p3;\n"
        "fma.rn.f32 t0, p1, t0, p1;\n"
        "fma.rn.f32 t1, p3, t1, p3;\n"
        "cvt.rn.bf16x2.f32 r0, t1, t0;\n"
        "mma.sync.aligned.m16n8k16.row.col.f32.bf16.bf16.f32 {p0,p1,p2,p3}, {%161,%162,%163,%164}, {m2,m3}, {fz,fz,fz,fz};\n"
        "mma.sync.aligned.m16n8k16.row.col.f32.bf16.bf16.f32 {%40,%41,%42,%43}, {a0,a1,a2,a3}, {x4,x5}, {%40,%41,%42,%43};\n"
        "mma.sync.aligned.m16n8k16.row.col.f32.bf16.bf16.f32 {%44,%45,%46,%47}, {a0,a1,a2,a3}, {x6,x7}, {%44,%45,%46,%47};\n"
        "ld.shared.v4.u32 {x4,x5,x6,x7}, [xa+1152];\n"
        "mma.sync.aligned.m16n8k8.row.col.f32.bf16.bf16.f32 {d0,d1,d2,d3}, {%177,%178}, {m1}, {fz,fz,fz,fz};\n"
        "cvt.rn.bf16x2.f32 b0, d2, d0;\n"
        "cvt.rn.bf16x2.f32 b1, d3, d1;\n"
        "tanh.approx.f32 t0, p5;\n"
        "tanh.approx.f32 t1, p7;\n"
        "fma.rn.f32 t0, p5, t0, p5;\n"
        "fma.rn.f32 t1, p7, t1, p7;\n"
        "cvt.rn.bf16x2.f32 r1, t1, t0;\n"
        "mma.sync.aligned.m16n8k16.row.col.f32.bf16.bf16.f32 {p4,p5,p6,p7}, {%165,%166,%167,%168}, {m2,m3}, {fz,fz,fz,fz};\n"
        "mov.b32 {lo,hi}, r2;\n"
        "mov.b32 rl, {lo,lo};\n"
        "mov.b32 rh, {hi,hi};\n"
        "mul.bf16x2 x8, x8, rl;\n"
        "mul.bf16x2 x9, x9, rl;\n"
        "mul.bf16x2 x10, x10, rh;\n"
        "mul.bf16x2 x11, x11, rh;\n"
        "mma.sync.aligned.m16n8k16.row.col.f32.bf16.bf16.f32 {%48,%49,%50,%51}, {a0,a1,a2,a3}, {x8,x9}, {%48,%49,%50,%51};\n"
        "mma.sync.aligned.m16n8k16.row.col.f32.bf16.bf16.f32 {%52,%53,%54,%55}, {a0,a1,a2,a3}, {x10,x11}, {%52,%53,%54,%55};\n"
        "ld.shared.v4.u32 {x8,x9,x10,x11}, [xa+1280];\n"
        "mma.sync.aligned.m16n8k8.row.col.f32.bf16.bf16.f32 {d0,d1,d2,d3}, {%179,%180}, {m1}, {fz,fz,fz,fz};\n"
        "cvt.rn.bf16x2.f32 b2, d2, d0;\n"
        "cvt.rn.bf16x2.f32 b3, d3, d1;\n"
        "tanh.approx.f32 t0, p9;\n"
        "tanh.approx.f32 t1, p11;\n"
        "fma.rn.f32 t0, p9, t0, p9;\n"
        "fma.rn.f32 t1, p11, t1, p11;\n"
        "cvt.rn.bf16x2.f32 r2, t1, t0;\n"
        "mma.sync.aligned.m16n8k16.row.col.f32.bf16.bf16.f32 {p8,p9,p10,p11}, {%169,%170,%171,%172}, {m2,m3}, {fz,fz,fz,fz};\n"
        "selp.u32 tq, lb, 5, w;\n"
        "mov.b32 {lo,hi}, r3;\n"
        "mov.b32 rl, {lo,lo};\n"
        "mov.b32 rh, {hi,hi};\n"
        "mul.bf16x2 x12, x12, rl;\n"
        "mul.bf16x2 x13, x13, rl;\n"
        "mul.bf16x2 x14, x14, rh;\n"
        "mul.bf16x2 x15, x15, rh;\n"
        "mma.sync.aligned.m16n8k16.row.col.f32.bf16.bf16.f32 {%56,%57,%58,%59}, {a0,a1,a2,a3}, {x12,x13}, {%56,%57,%58,%59};\n"
        "mma.sync.aligned.m16n8k16.row.col.f32.bf16.bf16.f32 {%60,%61,%62,%63}, {a0,a1,a2,a3}, {x14,x15}, {%60,%61,%62,%63};\n"
        "ld.shared.v4.u32 {x12,x13,x14,x15}, [xa+1408];\n"
        "@el mbarrier.arrive.shared.b64 _, [k0+8712];\n"
        "redux.sync.or.b32 ln, tag, 0xffffffff;\n"
        "mov.u32 sa, sn;\n"
        "add.u32 k0, sn, zz;\n"
        "tanh.approx.f32 t0, p13;\n"
        "tanh.approx.f32 t1, p15;\n"
        "fma.rn.f32 t0, p13, t0, p13;\n"
        "fma.rn.f32 t1, p15, t1, p15;\n"
        "cvt.rn.bf16x2.f32 r3, t1, t0;\n"
        "mma.sync.aligned.m16n8k16.row.col.f32.bf16.bf16.f32 {p12,p13,p14,p15}, {%173,%174,%175,%176}, {m2,m3}, {fz,fz,fz,fz};\n"
        "mov.b32 {lo,hi}, r0;\n"
        "mov.b32 rl, {lo,lo};\n"
        "mov.b32 rh, {hi,hi};\n"
        "mul.bf16x2 x0, x0, rl;\n"
        "mul.bf16x2 x1, x1, rl;\n"
        "mul.bf16x2 x2, x2, rh;\n"
        "mul.bf16x2 x3, x3, rh;\n"
        "mov.b32 {lo,hi}, r1;\n"
        "mov.b32 rl, {lo,lo};\n"
        "mov.b32 rh, {hi,hi};\n"
        "mul.bf16x2 x4, x4, rl;\n"
        "mul.bf16x2 x5, x5, rl;\n"
        "mul.bf16x2 x6, x6, rh;\n"
        "mul.bf16x2 x7, x7, rh;\n"
        "brx.idx.uni tq, TB_%=;\n"
        "A2_%=:\n"
        "add.u32 xa, sa, %181;\n"
        "add.u32 ma, sa, %182;\n"
        "ldmatrix.sync.aligned.m8n8.x4.shared.b16 {m0,m1,m2,m3}, [ma];\n"
        "ld.shared.u16 tag, [tp+48];\n"
        "add.u32 tp, tp, 52;\n"
        "add.u32 sn, sa, 8832;\n"
        "setp.eq.u32 q, sa, last;\n"
        "selp.u32 sn, ring, sn, q;\n"
        "selp.u32 tq, 1, 0, q;\n"
        "xor.b32 ph, ph, tq;\n"
        "mbarrier.test_wait.parity.shared.b64 w, [sn+8704], ph;\n"
        "mma.sync.aligned.m16n8k16.row.col.f32.bf16.bf16.f32 {%64,%65,%66,%67}, {a0,a1,a2,a3}, {x0,x1}, {%64,%65,%66,%67};\n"
        "mma.sync.aligned.m16n8k16.row.col.f32.bf16.bf16.f32 {%68,%69,%70,%71}, {a0,a1,a2,a3}, {x2,x3}, {%68,%69,%70,%71};\n"
        "ld.shared.v4.u32 {x0,x1,x2,x3}, [xa+1024];\n"
        "tanh.approx.f32 t0, p1;\n"
        "tanh.approx.f32 t1, p3;\n"
        "fma.rn.f32 t0, p1, t0, p1;\n"
        "fma.rn.f32 t1, p3, t1, p3;\n"
        "cvt.rn.bf16x2.f32 r0, t1, t0;\n"
        "mma.sync.aligned.m16n8k16.row.col.f32.bf16.bf16.f32 {p0,p1,p2,p3}, {%161,%162,%163,%164}, {m2,m3}, {fz,fz,fz,fz};\n"
        "mma.sync.aligned.m16n8k16.row.col.f32.bf16.bf16.f32 {%72,%73,%74,%75}, {a0,a1,a2,a3}, {x4,x5}, {%72,%73,%74,%75};\n"
        "mma.sync.aligned.m16n8k16.row.col.f32.bf16.bf16.f32 {%76,%77,%78,%79}, {a0,a1,a2,a3}, {x6,x7}, {%76,%77,%78,%79};\n"
        "ld.shared.v4.u32 {x4,x5,x6,x7}, [xa+1152];\n"
        "mma.sync.aligned.m16n8k8.row.col.f32.bf16.bf16.f32 {d0,d1,d2,d3}, {%177,%178}, {m1}, {fz,fz,fz,fz};\n"
        "cvt.rn.bf16x2.f32 b0, d2, d0;\n"
        "cvt.rn.bf16x2.f32 b1, d3, d1;\n"
        "tanh.approx.f32 t0, p5;\n"
        "tanh.approx.f32 t1, p7;\n"
        "fma.rn.f32 t0, p5, t0, p5;\n"
        "fma.rn.f32 t1, p7, t1, p7;\n"
        "cvt.rn.bf16x2.f32 r1, t1, t0;\n"
        "mma.sync.aligned.m16n8k16.row.col.f32.bf16.bf16.f32 {p4,p5,p6,p7}, {%165,%166,%167,%168}, {m2,m3}, {fz,fz,fz,fz};\n"
        "mov.b32 {lo,hi}, r2;\n"
        "mov.b32 rl, {lo,lo};\n"
        "mov.b32 rh, {hi,hi};\n"
        "mul.bf16x2 x8, x8, rl;\n"
        "mul.bf16x2 x9, x9, rl;\n"
        "mul.bf16x2 x10, x10, rh;\n"
        "mul.bf16x2 x11, x11, rh;\n"
        "mma.sync.aligned.m16n8k16.row.col.f32.bf16.bf16.f32 {%80,%81,%82,%83}, {a0,a1,a2,a3}, {x8,x9}, {%80,%81,%82,%83};\n"
        "mma.sync.aligned.m16n8k16.row.col.f32.bf16.bf16.f32 {%84,%85,%86,%87}, {a0,a1,a2,a3}, {x10,x11}, {%84,%85,%86,%87};\n"
        "ld.shared.v4.u32 {x8,x9,x10,x11}, [xa+1280];\n"
        "mma.sync.aligned.m16n8k8.row.col.f32.bf16.bf16.f32 {d0,d1,d2,d3}, {%179,%180}, {m1}, {fz,fz,fz,fz};\n"
        "cvt.rn.bf16x2.f32 b2, d2, d0;\n"
        "cvt.rn.bf16x2.f32 b3, d3, d1;\n"
        "tanh.approx.f32 t0, p9;\n"
        "tanh.approx.f32 t1, p11;\n"
        "fma.rn.f32 t0, p9, t0, p9;\n"
        "fma.rn.f32 t1, p11, t1, p11;\n"
        "cvt.rn.bf16x2.f32 r2, t1, t0;\n"
        "mma.sync.aligned.m16n8k16.row.col.f32.bf16.bf16.f32 {p8,p9,p10,p11}, {%169,%170,%171,%172}, {m2,m3}, {fz,fz,fz,fz};\n"
        "selp.u32 tq, lb, 5, w;\n"
        "mov.b32 {lo,hi}, r3;\n"
        "mov.b32 rl, {lo,lo};\n"
        "mov.b32 rh, {hi,hi};\n"
        "mul.bf16x2 x12, x12, rl;\n"
        "mul.bf16x2 x13, x13, rl;\n"
        "mul.bf16x2 x14, x14, rh;\n"
        "mul.bf16x2 x15, x15, rh;\n"
        "mma.sync.aligned.m16n8k16.row.col.f32.bf16.bf16.f32 {%88,%89,%90,%91}, {a0,a1,a2,a3}, {x12,x13}, {%88,%89,%90,%91};\n"
        "mma.sync.aligned.m16n8k16.row.col.f32.bf16.bf16.f32 {%92,%93,%94,%95}, {a0,a1,a2,a3}, {x14,x15}, {%92,%93,%94,%95};\n"
        "ld.shared.v4.u32 {x12,x13,x14,x15}, [xa+1408];\n"
        "@el mbarrier.arrive.shared.b64 _, [k0+8712];\n"
        "redux.sync.or.b32 ln, tag, 0xffffffff;\n"
        "mov.u32 sa, sn;\n"
        "add.u32 k0, sn, zz;\n"
        "tanh.approx.f32 t0, p13;\n"
        "tanh.approx.f32 t1, p15;\n"
        "fma.rn.f32 t0, p13, t0, p13;\n"
        "fma.rn.f32 t1, p15, t1, p15;\n"
        "cvt.rn.bf16x2.f32 r3, t1, t0;\n"
        "mma.sync.aligned.m16n8k16.row.col.f32.bf16.bf16.f32 {p12,p13,p14,p15}, {%173,%174,%175,%176}, {m2,m3}, {fz,fz,fz,fz};\n"
        "mov.b32 {lo,hi}, r0;\n"
        "mov.b32 rl, {lo,lo};\n"
        "mov.b32 rh, {hi,hi};\n"
        "mul.bf16x2 x0, x0, rl;\n"
        "mul.bf16x2 x1, x1, rl;\n"
        "mul.bf16x2 x2, x2, rh;\n"
        "mul.bf16x2 x3, x3, rh;\n"
        "mov.b32 {lo,hi}, r1;\n"
        "mov.b32 rl, {lo,lo};\n"
        "mov.b32 rh, {hi,hi};\n"
        "mul.bf16x2 x4, x4, rl;\n"
        "mul.bf16x2 x5, x5, rl;\n"
        "mul.bf16x2 x6, x6, rh;\n"
        "mul.bf16x2 x7, x7, rh;\n"
        "brx.idx.uni tq, TB_%=;\n"
        "A3_%=:\n"
        "add.u32 xa, sa, %181;\n"
        "add.u32 ma, sa, %182;\n"
        "ldmatrix.sync.aligned.m8n8.x4.shared.b16 {m0,m1,m2,m3}, [ma];\n"
        "ld.shared.u16 tag, [tp+48];\n"
        "add.u32 tp, tp, 52;\n"
        "add.u32 sn, sa, 8832;\n"
        "setp.eq.u32 q, sa, last;\n"
        "selp.u32 sn, ring, sn, q;\n"
        "selp.u32 tq, 1, 0, q;\n"
        "xor.b32 ph, ph, tq;\n"
        "mbarrier.test_wait.parity.shared.b64 w, [sn+8704], ph;\n"
        "mma.sync.aligned.m16n8k16.row.col.f32.bf16.bf16.f32 {%96,%97,%98,%99}, {a0,a1,a2,a3}, {x0,x1}, {%96,%97,%98,%99};\n"
        "mma.sync.aligned.m16n8k16.row.col.f32.bf16.bf16.f32 {%100,%101,%102,%103}, {a0,a1,a2,a3}, {x2,x3}, {%100,%101,%102,%103};\n"
        "ld.shared.v4.u32 {x0,x1,x2,x3}, [xa+1024];\n"
        "tanh.approx.f32 t0, p1;\n"
        "tanh.approx.f32 t1, p3;\n"
        "fma.rn.f32 t0, p1, t0, p1;\n"
        "fma.rn.f32 t1, p3, t1, p3;\n"
        "cvt.rn.bf16x2.f32 r0, t1, t0;\n"
        "mma.sync.aligned.m16n8k16.row.col.f32.bf16.bf16.f32 {p0,p1,p2,p3}, {%161,%162,%163,%164}, {m2,m3}, {fz,fz,fz,fz};\n"
        "mma.sync.aligned.m16n8k16.row.col.f32.bf16.bf16.f32 {%104,%105,%106,%107}, {a0,a1,a2,a3}, {x4,x5}, {%104,%105,%106,%107};\n"
        "mma.sync.aligned.m16n8k16.row.col.f32.bf16.bf16.f32 {%108,%109,%110,%111}, {a0,a1,a2,a3}, {x6,x7}, {%108,%109,%110,%111};\n"
        "ld.shared.v4.u32 {x4,x5,x6,x7}, [xa+1152];\n"
        "mma.sync.aligned.m16n8k8.row.col.f32.bf16.bf16.f32 {d0,d1,d2,d3}, {%177,%178}, {m1}, {fz,fz,fz,fz};\n"
        "cvt.rn.bf16x2.f32 b0, d2, d0;\n"
        "cvt.rn.bf16x2.f32 b1, d3, d1;\n"
        "tanh.approx.f32 t0, p5;\n"
        "tanh.approx.f32 t1, p7;\n"
        "fma.rn.f32 t0, p5, t0, p5;\n"
        "fma.rn.f32 t1, p7, t1, p7;\n"
        "cvt.rn.bf16x2.f32 r1, t1, t0;\n"
        "mma.sync.aligned.m16n8k16.row.col.f32.bf16.bf16.f32 {p4,p5,p6,p7}, {%165,%166,%167,%168}, {m2,m3}, {fz,fz,fz,fz};\n"
        "mov.b32 {lo,hi}, r2;\n"
        "mov.b32 rl, {lo,lo};\n"
        "mov.b32 rh, {hi,hi};\n"
        "mul.bf16x2 x8, x8, rl;\n"
        "mul.bf16x2 x9, x9, rl;\n"
        "mul.bf16x2 x10, x10, rh;\n"
        "mul.bf16x2 x11, x11, rh;\n"
        "mma.sync.aligned.m16n8k16.row.col.f32.bf16.bf16.f32 {%112,%113,%114,%115}, {a0,a1,a2,a3}, {x8,x9}, {%112,%113,%114,%115};\n"
        "mma.sync.aligned.m16n8k16.row.col.f32.bf16.bf16.f32 {%116,%117,%118,%119}, {a0,a1,a2,a3}, {x10,x11}, {%116,%117,%118,%119};\n"
        "ld.shared.v4.u32 {x8,x9,x10,x11}, [xa+1280];\n"
        "mma.sync.aligned.m16n8k8.row.col.f32.bf16.bf16.f32 {d0,d1,d2,d3}, {%179,%180}, {m1}, {fz,fz,fz,fz};\n"
        "cvt.rn.bf16x2.f32 b2, d2, d0;\n"
        "cvt.rn.bf16x2.f32 b3, d3, d1;\n"
        "tanh.approx.f32 t0, p9;\n"
        "tanh.approx.f32 t1, p11;\n"
        "fma.rn.f32 t0, p9, t0, p9;\n"
        "fma.rn.f32 t1, p11, t1, p11;\n"
        "cvt.rn.bf16x2.f32 r2, t1, t0;\n"
        "mma.sync.aligned.m16n8k16.row.col.f32.bf16.bf16.f32 {p8,p9,p10,p11}, {%169,%170,%171,%172}, {m2,m3}, {fz,fz,fz,fz};\n"
        "selp.u32 tq, lb, 5, w;\n"
        "mov.b32 {lo,hi}, r3;\n"
        "mov.b32 rl, {lo,lo};\n"
        "mov.b32 rh, {hi,hi};\n"
        "mul.bf16x2 x12, x12, rl;\n"
        "mul.bf16x2 x13, x13, rl;\n"
        "mul.bf16x2 x14, x14, rh;\n"
        "mul.bf16x2 x15, x15, rh;\n"
        "mma.sync.aligned.m16n8k16.row.col.f32.bf16.bf16.f32 {%120,%121,%122,%123}, {a0,a1,a2,a3}, {x12,x13}, {%120,%121,%122,%123};\n"
        "mma.sync.aligned.m16n8k16.row.col.f32.bf16.bf16.f32 {%124,%125,%126,%127}, {a0,a1,a2,a3}, {x14,x15}, {%124,%125,%126,%127};\n"
        "ld.shared.v4.u32 {x12,x13,x14,x15}, [xa+1408];\n"
        "@el mbarrier.arrive.shared.b64 _, [k0+8712];\n"
        "redux.sync.or.b32 ln, tag, 0xffffffff;\n"
        "mov.u32 sa, sn;\n"
        "add.u32 k0, sn, zz;\n"
        "tanh.approx.f32 t0, p13;\n"
        "tanh.approx.f32 t1, p15;\n"
        "fma.rn.f32 t0, p13, t0, p13;\n"
        "fma.rn.f32 t1, p15, t1, p15;\n"
        "cvt.rn.bf16x2.f32 r3, t1, t0;\n"
        "mma.sync.aligned.m16n8k16.row.col.f32.bf16.bf16.f32 {p12,p13,p14,p15}, {%173,%174,%175,%176}, {m2,m3}, {fz,fz,fz,fz};\n"
        "mov.b32 {lo,hi}, r0;\n"
        "mov.b32 rl, {lo,lo};\n"
        "mov.b32 rh, {hi,hi};\n"
        "mul.bf16x2 x0, x0, rl;\n"
        "mul.bf16x2 x1, x1, rl;\n"
        "mul.bf16x2 x2, x2, rh;\n"
        "mul.bf16x2 x3, x3, rh;\n"
        "mov.b32 {lo,hi}, r1;\n"
        "mov.b32 rl, {lo,lo};\n"
        "mov.b32 rh, {hi,hi};\n"
        "mul.bf16x2 x4, x4, rl;\n"
        "mul.bf16x2 x5, x5, rl;\n"
        "mul.bf16x2 x6, x6, rh;\n"
        "mul.bf16x2 x7, x7, rh;\n"
        "brx.idx.uni tq, TB_%=;\n"
        "A4_%=:\n"
        "add.u32 xa, sa, %181;\n"
        "add.u32 ma, sa, %182;\n"
        "ldmatrix.sync.aligned.m8n8.x4.shared.b16 {m0,m1,m2,m3}, [ma];\n"
        "ld.shared.u16 tag, [tp+48];\n"
        "add.u32 tp, tp, 52;\n"
        "add.u32 sn, sa, 8832;\n"
        "setp.eq.u32 q, sa, last;\n"
        "selp.u32 sn, ring, sn, q;\n"
        "selp.u32 tq, 1, 0, q;\n"
        "xor.b32 ph, ph, tq;\n"
        "mbarrier.test_wait.parity.shared.b64 w, [sn+8704], ph;\n"
        "mma.sync.aligned.m16n8k16.row.col.f32.bf16.bf16.f32 {%128,%129,%130,%131}, {a0,a1,a2,a3}, {x0,x1}, {%128,%129,%130,%131};\n"
        "mma.sync.aligned.m16n8k16.row.col.f32.bf16.bf16.f32 {%132,%133,%134,%135}, {a0,a1,a2,a3}, {x2,x3}, {%132,%133,%134,%135};\n"
        "ld.shared.v4.u32 {x0,x1,x2,x3}, [xa+1024];\n"
        "tanh.approx.f32 t0, p1;\n"
        "tanh.approx.f32 t1, p3;\n"
        "fma.rn.f32 t0, p1, t0, p1;\n"
        "fma.rn.f32 t1, p3, t1, p3;\n"
        "cvt.rn.bf16x2.f32 r0, t1, t0;\n"
        "mma.sync.aligned.m16n8k16.row.col.f32.bf16.bf16.f32 {p0,p1,p2,p3}, {%161,%162,%163,%164}, {m2,m3}, {fz,fz,fz,fz};\n"
        "mma.sync.aligned.m16n8k16.row.col.f32.bf16.bf16.f32 {%136,%137,%138,%139}, {a0,a1,a2,a3}, {x4,x5}, {%136,%137,%138,%139};\n"
        "mma.sync.aligned.m16n8k16.row.col.f32.bf16.bf16.f32 {%140,%141,%142,%143}, {a0,a1,a2,a3}, {x6,x7}, {%140,%141,%142,%143};\n"
        "ld.shared.v4.u32 {x4,x5,x6,x7}, [xa+1152];\n"
        "mma.sync.aligned.m16n8k8.row.col.f32.bf16.bf16.f32 {d0,d1,d2,d3}, {%177,%178}, {m1}, {fz,fz,fz,fz};\n"
        "cvt.rn.bf16x2.f32 b0, d2, d0;\n"
        "cvt.rn.bf16x2.f32 b1, d3, d1;\n"
        "tanh.approx.f32 t0, p5;\n"
        "tanh.approx.f32 t1, p7;\n"
        "fma.rn.f32 t0, p5, t0, p5;\n"
        "fma.rn.f32 t1, p7, t1, p7;\n"
        "cvt.rn.bf16x2.f32 r1, t1, t0;\n"
        "mma.sync.aligned.m16n8k16.row.col.f32.bf16.bf16.f32 {p4,p5,p6,p7}, {%165,%166,%167,%168}, {m2,m3}, {fz,fz,fz,fz};\n"
        "mov.b32 {lo,hi}, r2;\n"
        "mov.b32 rl, {lo,lo};\n"
        "mov.b32 rh, {hi,hi};\n"
        "mul.bf16x2 x8, x8, rl;\n"
        "mul.bf16x2 x9, x9, rl;\n"
        "mul.bf16x2 x10, x10, rh;\n"
        "mul.bf16x2 x11, x11, rh;\n"
        "mma.sync.aligned.m16n8k16.row.col.f32.bf16.bf16.f32 {%144,%145,%146,%147}, {a0,a1,a2,a3}, {x8,x9}, {%144,%145,%146,%147};\n"
        "mma.sync.aligned.m16n8k16.row.col.f32.bf16.bf16.f32 {%148,%149,%150,%151}, {a0,a1,a2,a3}, {x10,x11}, {%148,%149,%150,%151};\n"
        "ld.shared.v4.u32 {x8,x9,x10,x11}, [xa+1280];\n"
        "mma.sync.aligned.m16n8k8.row.col.f32.bf16.bf16.f32 {d0,d1,d2,d3}, {%179,%180}, {m1}, {fz,fz,fz,fz};\n"
        "cvt.rn.bf16x2.f32 b2, d2, d0;\n"
        "cvt.rn.bf16x2.f32 b3, d3, d1;\n"
        "tanh.approx.f32 t0, p9;\n"
        "tanh.approx.f32 t1, p11;\n"
        "fma.rn.f32 t0, p9, t0, p9;\n"
        "fma.rn.f32 t1, p11, t1, p11;\n"
        "cvt.rn.bf16x2.f32 r2, t1, t0;\n"
        "mma.sync.aligned.m16n8k16.row.col.f32.bf16.bf16.f32 {p8,p9,p10,p11}, {%169,%170,%171,%172}, {m2,m3}, {fz,fz,fz,fz};\n"
        "selp.u32 tq, lb, 5, w;\n"
        "mov.b32 {lo,hi}, r3;\n"
        "mov.b32 rl, {lo,lo};\n"
        "mov.b32 rh, {hi,hi};\n"
        "mul.bf16x2 x12, x12, rl;\n"
        "mul.bf16x2 x13, x13, rl;\n"
        "mul.bf16x2 x14, x14, rh;\n"
        "mul.bf16x2 x15, x15, rh;\n"
        "mma.sync.aligned.m16n8k16.row.col.f32.bf16.bf16.f32 {%152,%153,%154,%155}, {a0,a1,a2,a3}, {x12,x13}, {%152,%153,%154,%155};\n"
        "mma.sync.aligned.m16n8k16.row.col.f32.bf16.bf16.f32 {%156,%157,%158,%159}, {a0,a1,a2,a3}, {x14,x15}, {%156,%157,%158,%159};\n"
        "ld.shared.v4.u32 {x12,x13,x14,x15}, [xa+1408];\n"
        "@el mbarrier.arrive.shared.b64 _, [k0+8712];\n"
        "redux.sync.or.b32 ln, tag, 0xffffffff;\n"
        "mov.u32 sa, sn;\n"
        "add.u32 k0, sn, zz;\n"
        "tanh.approx.f32 t0, p13;\n"
        "tanh.approx.f32 t1, p15;\n"
        "fma.rn.f32 t0, p13, t0, p13;\n"
        "fma.rn.f32 t1, p15, t1, p15;\n"
        "cvt.rn.bf16x2.f32 r3, t1, t0;\n"
        "mma.sync.aligned.m16n8k16.row.col.f32.bf16.bf16.f32 {p12,p13,p14,p15}, {%173,%174,%175,%176}, {m2,m3}, {fz,fz,fz,fz};\n"
        "mov.b32 {lo,hi}, r0;\n"
        "mov.b32 rl, {lo,lo};\n"
        "mov.b32 rh, {hi,hi};\n"
        "mul.bf16x2 x0, x0, rl;\n"
        "mul.bf16x2 x1, x1, rl;\n"
        "mul.bf16x2 x2, x2, rh;\n"
        "mul.bf16x2 x3, x3, rh;\n"
        "mov.b32 {lo,hi}, r1;\n"
        "mov.b32 rl, {lo,lo};\n"
        "mov.b32 rh, {hi,hi};\n"
        "mul.bf16x2 x4, x4, rl;\n"
        "mul.bf16x2 x5, x5, rl;\n"
        "mul.bf16x2 x6, x6, rh;\n"
        "mul.bf16x2 x7, x7, rh;\n"
        "brx.idx.uni tq, TB_%=;\n"
        "B0_%=:\n"
        "and.b32 la, ln, 255;\n"
        "shr.u32 lb, ln, 8;\n"
        "add.u32 ma, sa, %182;\n"
        "ldmatrix.sync.aligned.m8n8.x1.shared.b16 {yb}, [ma];\n"
        "add.u32 xa, sa, %181;\n"
        "mma.sync.aligned.m16n8k16.row.col.f32.bf16.bf16.f32 {%0,%1,%2,%3}, {b0,b1,b2,b3}, {x0,x1}, {%0,%1,%2,%3};\n"
        "mma.sync.aligned.m16n8k16.row.col.f32.bf16.bf16.f32 {%4,%5,%6,%7}, {b0,b1,b2,b3}, {x2,x3}, {%4,%5,%6,%7};\n"
        "ld.shared.v4.u32 {x0,x1,x2,x3}, [xa+0];\n"
        "tanh.approx.f32 t0, p0;\n"
        "tanh.approx.f32 t1, p2;\n"
        "fma.rn.f32 t0, p0, t0, p0;\n"
        "fma.rn.f32 t1, p2, t1, p2;\n"
        "cvt.rn.bf16x2.f32 r0, t1, t0;\n"
        "mma.sync.aligned.m16n8k16.row.col.f32.bf16.bf16.f32 {%8,%9,%10,%11}, {b0,b1,b2,b3}, {x4,x5}, {%8,%9,%10,%11};\n"
        "mma.sync.aligned.m16n8k16.row.col.f32.bf16.bf16.f32 {%12,%13,%14,%15}, {b0,b1,b2,b3}, {x6,x7}, {%12,%13,%14,%15};\n"
        "ld.shared.v4.u32 {x4,x5,x6,x7}, [xa+128];\n"
        "tanh.approx.f32 t0, p4;\n"
        "tanh.approx.f32 t1, p6;\n"
        "fma.rn.f32 t0, p4, t0, p4;\n"
        "fma.rn.f32 t1, p6, t1, p6;\n"
        "cvt.rn.bf16x2.f32 r1, t1, t0;\n"
        "mma.sync.aligned.m16n8k8.row.col.f32.bf16.bf16.f32 {d0,d1,d2,d3}, {%177,%178}, {yb}, {fz,fz,fz,fz};\n"
        "cvt.rn.bf16x2.f32 a0, d2, d0;\n"
        "cvt.rn.bf16x2.f32 a1, d3, d1;\n"
        "mov.b32 {lo,hi}, r2;\n"
        "mov.b32 rl, {lo,lo};\n"
        "mov.b32 rh, {hi,hi};\n"
        "mul.bf16x2 x8, x8, rl;\n"
        "mul.bf16x2 x9, x9, rl;\n"
        "mul.bf16x2 x10, x10, rh;\n"
        "mul.bf16x2 x11, x11, rh;\n"
        "mma.sync.aligned.m16n8k16.row.col.f32.bf16.bf16.f32 {%16,%17,%18,%19}, {b0,b1,b2,b3}, {x8,x9}, {%16,%17,%18,%19};\n"
        "mma.sync.aligned.m16n8k16.row.col.f32.bf16.bf16.f32 {%20,%21,%22,%23}, {b0,b1,b2,b3}, {x10,x11}, {%20,%21,%22,%23};\n"
        "ld.shared.v4.u32 {x8,x9,x10,x11}, [xa+256];\n"
        "tanh.approx.f32 t0, p8;\n"
        "tanh.approx.f32 t1, p10;\n"
        "fma.rn.f32 t0, p8, t0, p8;\n"
        "fma.rn.f32 t1, p10, t1, p10;\n"
        "cvt.rn.bf16x2.f32 r2, t1, t0;\n"
        "mma.sync.aligned.m16n8k8.row.col.f32.bf16.bf16.f32 {d0,d1,d2,d3}, {%179,%180}, {yb}, {fz,fz,fz,fz};\n"
        "cvt.rn.bf16x2.f32 a2, d2, d0;\n"
        "cvt.rn.bf16x2.f32 a3, d3, d1;\n"
        "mov.b32 {lo,hi}, r3;\n"
        "mov.b32 rl, {lo,lo};\n"
        "mov.b32 rh, {hi,hi};\n"
        "mul.bf16x2 x12, x12, rl;\n"
        "mul.bf16x2 x13, x13, rl;\n"
        "mul.bf16x2 x14, x14, rh;\n"
        "mul.bf16x2 x15, x15, rh;\n"
        "mma.sync.aligned.m16n8k16.row.col.f32.bf16.bf16.f32 {%24,%25,%26,%27}, {b0,b1,b2,b3}, {x12,x13}, {%24,%25,%26,%27};\n"
        "mma.sync.aligned.m16n8k16.row.col.f32.bf16.bf16.f32 {%28,%29,%30,%31}, {b0,b1,b2,b3}, {x14,x15}, {%28,%29,%30,%31};\n"
        "ld.shared.v4.u32 {x12,x13,x14,x15}, [xa+384];\n"
        "tanh.approx.f32 t0, p12;\n"
        "tanh.approx.f32 t1, p14;\n"
        "fma.rn.f32 t0, p12, t0, p12;\n"
        "fma.rn.f32 t1, p14, t1, p14;\n"
        "cvt.rn.bf16x2.f32 r3, t1, t0;\n"
        "mov.b32 {lo,hi}, r0;\n"
        "mov.b32 rl, {lo,lo};\n"
        "mov.b32 rh, {hi,hi};\n"
        "mul.bf16x2 x0, x0, rl;\n"
        "mul.bf16x2 x1, x1, rl;\n"
        "mul.bf16x2 x2, x2, rh;\n"
        "mul.bf16x2 x3, x3, rh;\n"
        "mov.b32 {lo,hi}, r1;\n"
        "mov.b32 rl, {lo,lo};\n"
        "mov.b32 rh, {hi,hi};\n"
        "mul.bf16x2 x4, x4, rl;\n"
        "mul.bf16x2 x5, x5, rl;\n"
        "mul.bf16x2 x6, x6, rh;\n"
        "mul.bf16x2 x7, x7, rh;\n"
        "brx.idx.uni la, TA_%=;\n"
        "B1_%=:\n"
        "and.b32 la, ln, 255;\n"
        "shr.u32 lb, ln, 8;\n"
        "add.u32 ma, sa, %182;\n"
        "ldmatrix.sync.aligned.m8n8.x1.shared.b16 {yb}, [ma];\n"
        "add.u32 xa, sa, %181;\n"
        "mma.sync.aligned.m16n8k16.row.col.f32.bf16.bf16.f32 {%32,%33,%34,%35}, {b0,b1,b2,b3}, {x0,x1}, {%32,%33,%34,%35};\n"
        "mma.sync.aligned.m16n8k16.row.col.f32.bf16.bf16.f32 {%36,%37,%38,%39}, {b0,b1,b2,b3}, {x2,x3}, {%36,%37,%38,%39};\n"
        "ld.shared.v4.u32 {x0,x1,x2,x3}, [xa+0];\n"
        "tanh.approx.f32 t0, p0;\n"
        "tanh.approx.f32 t1, p2;\n"
        "fma.rn.f32 t0, p0, t0, p0;\n"
        "fma.rn.f32 t1, p2, t1, p2;\n"
        "cvt.rn.bf16x2.f32 r0, t1, t0;\n"
        "mma.sync.aligned.m16n8k16.row.col.f32.bf16.bf16.f32 {%40,%41,%42,%43}, {b0,b1,b2,b3}, {x4,x5}, {%40,%41,%42,%43};\n"
        "mma.sync.aligned.m16n8k16.row.col.f32.bf16.bf16.f32 {%44,%45,%46,%47}, {b0,b1,b2,b3}, {x6,x7}, {%44,%45,%46,%47};\n"
        "ld.shared.v4.u32 {x4,x5,x6,x7}, [xa+128];\n"
        "tanh.approx.f32 t0, p4;\n"
        "tanh.approx.f32 t1, p6;\n"
        "fma.rn.f32 t0, p4, t0, p4;\n"
        "fma.rn.f32 t1, p6, t1, p6;\n"
        "cvt.rn.bf16x2.f32 r1, t1, t0;\n"
        "mma.sync.aligned.m16n8k8.row.col.f32.bf16.bf16.f32 {d0,d1,d2,d3}, {%177,%178}, {yb}, {fz,fz,fz,fz};\n"
        "cvt.rn.bf16x2.f32 a0, d2, d0;\n"
        "cvt.rn.bf16x2.f32 a1, d3, d1;\n"
        "mov.b32 {lo,hi}, r2;\n"
        "mov.b32 rl, {lo,lo};\n"
        "mov.b32 rh, {hi,hi};\n"
        "mul.bf16x2 x8, x8, rl;\n"
        "mul.bf16x2 x9, x9, rl;\n"
        "mul.bf16x2 x10, x10, rh;\n"
        "mul.bf16x2 x11, x11, rh;\n"
        "mma.sync.aligned.m16n8k16.row.col.f32.bf16.bf16.f32 {%48,%49,%50,%51}, {b0,b1,b2,b3}, {x8,x9}, {%48,%49,%50,%51};\n"
        "mma.sync.aligned.m16n8k16.row.col.f32.bf16.bf16.f32 {%52,%53,%54,%55}, {b0,b1,b2,b3}, {x10,x11}, {%52,%53,%54,%55};\n"
        "ld.shared.v4.u32 {x8,x9,x10,x11}, [xa+256];\n"
        "tanh.approx.f32 t0, p8;\n"
        "tanh.approx.f32 t1, p10;\n"
        "fma.rn.f32 t0, p8, t0, p8;\n"
        "fma.rn.f32 t1, p10, t1, p10;\n"
        "cvt.rn.bf16x2.f32 r2, t1, t0;\n"
        "mma.sync.aligned.m16n8k8.row.col.f32.bf16.bf16.f32 {d0,d1,d2,d3}, {%179,%180}, {yb}, {fz,fz,fz,fz};\n"
        "cvt.rn.bf16x2.f32 a2, d2, d0;\n"
        "cvt.rn.bf16x2.f32 a3, d3, d1;\n"
        "mov.b32 {lo,hi}, r3;\n"
        "mov.b32 rl, {lo,lo};\n"
        "mov.b32 rh, {hi,hi};\n"
        "mul.bf16x2 x12, x12, rl;\n"
        "mul.bf16x2 x13, x13, rl;\n"
        "mul.bf16x2 x14, x14, rh;\n"
        "mul.bf16x2 x15, x15, rh;\n"
        "mma.sync.aligned.m16n8k16.row.col.f32.bf16.bf16.f32 {%56,%57,%58,%59}, {b0,b1,b2,b3}, {x12,x13}, {%56,%57,%58,%59};\n"
        "mma.sync.aligned.m16n8k16.row.col.f32.bf16.bf16.f32 {%60,%61,%62,%63}, {b0,b1,b2,b3}, {x14,x15}, {%60,%61,%62,%63};\n"
        "ld.shared.v4.u32 {x12,x13,x14,x15}, [xa+384];\n"
        "tanh.approx.f32 t0, p12;\n"
        "tanh.approx.f32 t1, p14;\n"
        "fma.rn.f32 t0, p12, t0, p12;\n"
        "fma.rn.f32 t1, p14, t1, p14;\n"
        "cvt.rn.bf16x2.f32 r3, t1, t0;\n"
        "mov.b32 {lo,hi}, r0;\n"
        "mov.b32 rl, {lo,lo};\n"
        "mov.b32 rh, {hi,hi};\n"
        "mul.bf16x2 x0, x0, rl;\n"
        "mul.bf16x2 x1, x1, rl;\n"
        "mul.bf16x2 x2, x2, rh;\n"
        "mul.bf16x2 x3, x3, rh;\n"
        "mov.b32 {lo,hi}, r1;\n"
        "mov.b32 rl, {lo,lo};\n"
        "mov.b32 rh, {hi,hi};\n"
        "mul.bf16x2 x4, x4, rl;\n"
        "mul.bf16x2 x5, x5, rl;\n"
        "mul.bf16x2 x6, x6, rh;\n"
        "mul.bf16x2 x7, x7, rh;\n"
        "brx.idx.uni la, TA_%=;\n"
        "B2_%=:\n"
        "and.b32 la, ln, 255;\n"
        "shr.u32 lb, ln, 8;\n"
        "add.u32 ma, sa, %182;\n"
        "ldmatrix.sync.aligned.m8n8.x1.shared.b16 {yb}, [ma];\n"
        "add.u32 xa, sa, %181;\n"
        "mma.sync.aligned.m16n8k16.row.col.f32.bf16.bf16.f32 {%64,%65,%66,%67}, {b0,b1,b2,b3}, {x0,x1}, {%64,%65,%66,%67};\n"
        "mma.sync.aligned.m16n8k16.row.col.f32.bf16.bf16.f32 {%68,%69,%70,%71}, {b0,b1,b2,b3}, {x2,x3}, {%68,%69,%70,%71};\n"
        "ld.shared.v4.u32 {x0,x1,x2,x3}, [xa+0];\n"
        "tanh.approx.f32 t0, p0;\n"
        "tanh.approx.f32 t1, p2;\n"
        "fma.rn.f32 t0, p0, t0, p0;\n"
        "fma.rn.f32 t1, p2, t1, p2;\n"
        "cvt.rn.bf16x2.f32 r0, t1, t0;\n"
        "mma.sync.aligned.m16n8k16.row.col.f32.bf16.bf16.f32 {%72,%73,%74,%75}, {b0,b1,b2,b3}, {x4,x5}, {%72,%73,%74,%75};\n"
        "mma.sync.aligned.m16n8k16.row.col.f32.bf16.bf16.f32 {%76,%77,%78,%79}, {b0,b1,b2,b3}, {x6,x7}, {%76,%77,%78,%79};\n"
        "ld.shared.v4.u32 {x4,x5,x6,x7}, [xa+128];\n"
        "tanh.approx.f32 t0, p4;\n"
        "tanh.approx.f32 t1, p6;\n"
        "fma.rn.f32 t0, p4, t0, p4;\n"
        "fma.rn.f32 t1, p6, t1, p6;\n"
        "cvt.rn.bf16x2.f32 r1, t1, t0;\n"
        "mma.sync.aligned.m16n8k8.row.col.f32.bf16.bf16.f32 {d0,d1,d2,d3}, {%177,%178}, {yb}, {fz,fz,fz,fz};\n"
        "cvt.rn.bf16x2.f32 a0, d2, d0;\n"
        "cvt.rn.bf16x2.f32 a1, d3, d1;\n"
        "mov.b32 {lo,hi}, r2;\n"
        "mov.b32 rl, {lo,lo};\n"
        "mov.b32 rh, {hi,hi};\n"
        "mul.bf16x2 x8, x8, rl;\n"
        "mul.bf16x2 x9, x9, rl;\n"
        "mul.bf16x2 x10, x10, rh;\n"
        "mul.bf16x2 x11, x11, rh;\n"
        "mma.sync.aligned.m16n8k16.row.col.f32.bf16.bf16.f32 {%80,%81,%82,%83}, {b0,b1,b2,b3}, {x8,x9}, {%80,%81,%82,%83};\n"
        "mma.sync.aligned.m16n8k16.row.col.f32.bf16.bf16.f32 {%84,%85,%86,%87}, {b0,b1,b2,b3}, {x10,x11}, {%84,%85,%86,%87};\n"
        "ld.shared.v4.u32 {x8,x9,x10,x11}, [xa+256];\n"
        "tanh.approx.f32 t0, p8;\n"
        "tanh.approx.f32 t1, p10;\n"
        "fma.rn.f32 t0, p8, t0, p8;\n"
        "fma.rn.f32 t1, p10, t1, p10;\n"
        "cvt.rn.bf16x2.f32 r2, t1, t0;\n"
        "mma.sync.aligned.m16n8k8.row.col.f32.bf16.bf16.f32 {d0,d1,d2,d3}, {%179,%180}, {yb}, {fz,fz,fz,fz};\n"
        "cvt.rn.bf16x2.f32 a2, d2, d0;\n"
        "cvt.rn.bf16x2.f32 a3, d3, d1;\n"
        "mov.b32 {lo,hi}, r3;\n"
        "mov.b32 rl, {lo,lo};\n"
        "mov.b32 rh, {hi,hi};\n"
        "mul.bf16x2 x12, x12, rl;\n"
        "mul.bf16x2 x13, x13, rl;\n"
        "mul.bf16x2 x14, x14, rh;\n"
        "mul.bf16x2 x15, x15, rh;\n"
        "mma.sync.aligned.m16n8k16.row.col.f32.bf16.bf16.f32 {%88,%89,%90,%91}, {b0,b1,b2,b3}, {x12,x13}, {%88,%89,%90,%91};\n"
        "mma.sync.aligned.m16n8k16.row.col.f32.bf16.bf16.f32 {%92,%93,%94,%95}, {b0,b1,b2,b3}, {x14,x15}, {%92,%93,%94,%95};\n"
        "ld.shared.v4.u32 {x12,x13,x14,x15}, [xa+384];\n"
        "tanh.approx.f32 t0, p12;\n"
        "tanh.approx.f32 t1, p14;\n"
        "fma.rn.f32 t0, p12, t0, p12;\n"
        "fma.rn.f32 t1, p14, t1, p14;\n"
        "cvt.rn.bf16x2.f32 r3, t1, t0;\n"
        "mov.b32 {lo,hi}, r0;\n"
        "mov.b32 rl, {lo,lo};\n"
        "mov.b32 rh, {hi,hi};\n"
        "mul.bf16x2 x0, x0, rl;\n"
        "mul.bf16x2 x1, x1, rl;\n"
        "mul.bf16x2 x2, x2, rh;\n"
        "mul.bf16x2 x3, x3, rh;\n"
        "mov.b32 {lo,hi}, r1;\n"
        "mov.b32 rl, {lo,lo};\n"
        "mov.b32 rh, {hi,hi};\n"
        "mul.bf16x2 x4, x4, rl;\n"
        "mul.bf16x2 x5, x5, rl;\n"
        "mul.bf16x2 x6, x6, rh;\n"
        "mul.bf16x2 x7, x7, rh;\n"
        "brx.idx.uni la, TA_%=;\n"
        "B3_%=:\n"
        "and.b32 la, ln, 255;\n"
        "shr.u32 lb, ln, 8;\n"
        "add.u32 ma, sa, %182;\n"
        "ldmatrix.sync.aligned.m8n8.x1.shared.b16 {yb}, [ma];\n"
        "add.u32 xa, sa, %181;\n"
        "mma.sync.aligned.m16n8k16.row.col.f32.bf16.bf16.f32 {%96,%97,%98,%99}, {b0,b1,b2,b3}, {x0,x1}, {%96,%97,%98,%99};\n"
        "mma.sync.aligned.m16n8k16.row.col.f32.bf16.bf16.f32 {%100,%101,%102,%103}, {b0,b1,b2,b3}, {x2,x3}, {%100,%101,%102,%103};\n"
        "ld.shared.v4.u32 {x0,x1,x2,x3}, [xa+0];\n"
        "tanh.approx.f32 t0, p0;\n"
        "tanh.approx.f32 t1, p2;\n"
        "fma.rn.f32 t0, p0, t0, p0;\n"
        "fma.rn.f32 t1, p2, t1, p2;\n"
        "cvt.rn.bf16x2.f32 r0, t1, t0;\n"
        "mma.sync.aligned.m16n8k16.row.col.f32.bf16.bf16.f32 {%104,%105,%106,%107}, {b0,b1,b2,b3}, {x4,x5}, {%104,%105,%106,%107};\n"
        "mma.sync.aligned.m16n8k16.row.col.f32.bf16.bf16.f32 {%108,%109,%110,%111}, {b0,b1,b2,b3}, {x6,x7}, {%108,%109,%110,%111};\n"
        "ld.shared.v4.u32 {x4,x5,x6,x7}, [xa+128];\n"
        "tanh.approx.f32 t0, p4;\n"
        "tanh.approx.f32 t1, p6;\n"
        "fma.rn.f32 t0, p4, t0, p4;\n"
        "fma.rn.f32 t1, p6, t1, p6;\n"
        "cvt.rn.bf16x2.f32 r1, t1, t0;\n"
        "mma.sync.aligned.m16n8k8.row.col.f32.bf16.bf16.f32 {d0,d1,d2,d3}, {%177,%178}, {yb}, {fz,fz,fz,fz};\n"
        "cvt.rn.bf16x2.f32 a0, d2, d0;\n"
        "cvt.rn.bf16x2.f32 a1, d3, d1;\n"
        "mov.b32 {lo,hi}, r2;\n"
        "mov.b32 rl, {lo,lo};\n"
        "mov.b32 rh, {hi,hi};\n"
        "mul.bf16x2 x8, x8, rl;\n"
        "mul.bf16x2 x9, x9, rl;\n"
        "mul.bf16x2 x10, x10, rh;\n"
        "mul.bf16x2 x11, x11, rh;\n"
        "mma.sync.aligned.m16n8k16.row.col.f32.bf16.bf16.f32 {%112,%113,%114,%115}, {b0,b1,b2,b3}, {x8,x9}, {%112,%113,%114,%115};\n"
        "mma.sync.aligned.m16n8k16.row.col.f32.bf16.bf16.f32 {%116,%117,%118,%119}, {b0,b1,b2,b3}, {x10,x11}, {%116,%117,%118,%119};\n"
        "ld.shared.v4.u32 {x8,x9,x10,x11}, [xa+256];\n"
        "tanh.approx.f32 t0, p8;\n"
        "tanh.approx.f32 t1, p10;\n"
        "fma.rn.f32 t0, p8, t0, p8;\n"
        "fma.rn.f32 t1, p10, t1, p10;\n"
        "cvt.rn.bf16x2.f32 r2, t1, t0;\n"
        "mma.sync.aligned.m16n8k8.row.col.f32.bf16.bf16.f32 {d0,d1,d2,d3}, {%179,%180}, {yb}, {fz,fz,fz,fz};\n"
        "cvt.rn.bf16x2.f32 a2, d2, d0;\n"
        "cvt.rn.bf16x2.f32 a3, d3, d1;\n"
        "mov.b32 {lo,hi}, r3;\n"
        "mov.b32 rl, {lo,lo};\n"
        "mov.b32 rh, {hi,hi};\n"
        "mul.bf16x2 x12, x12, rl;\n"
        "mul.bf16x2 x13, x13, rl;\n"
        "mul.bf16x2 x14, x14, rh;\n"
        "mul.bf16x2 x15, x15, rh;\n"
        "mma.sync.aligned.m16n8k16.row.col.f32.bf16.bf16.f32 {%120,%121,%122,%123}, {b0,b1,b2,b3}, {x12,x13}, {%120,%121,%122,%123};\n"
        "mma.sync.aligned.m16n8k16.row.col.f32.bf16.bf16.f32 {%124,%125,%126,%127}, {b0,b1,b2,b3}, {x14,x15}, {%124,%125,%126,%127};\n"
        "ld.shared.v4.u32 {x12,x13,x14,x15}, [xa+384];\n"
        "tanh.approx.f32 t0, p12;\n"
        "tanh.approx.f32 t1, p14;\n"
        "fma.rn.f32 t0, p12, t0, p12;\n"
        "fma.rn.f32 t1, p14, t1, p14;\n"
        "cvt.rn.bf16x2.f32 r3, t1, t0;\n"
        "mov.b32 {lo,hi}, r0;\n"
        "mov.b32 rl, {lo,lo};\n"
        "mov.b32 rh, {hi,hi};\n"
        "mul.bf16x2 x0, x0, rl;\n"
        "mul.bf16x2 x1, x1, rl;\n"
        "mul.bf16x2 x2, x2, rh;\n"
        "mul.bf16x2 x3, x3, rh;\n"
        "mov.b32 {lo,hi}, r1;\n"
        "mov.b32 rl, {lo,lo};\n"
        "mov.b32 rh, {hi,hi};\n"
        "mul.bf16x2 x4, x4, rl;\n"
        "mul.bf16x2 x5, x5, rl;\n"
        "mul.bf16x2 x6, x6, rh;\n"
        "mul.bf16x2 x7, x7, rh;\n"
        "brx.idx.uni la, TA_%=;\n"
        "B4_%=:\n"
        "and.b32 la, ln, 255;\n"
        "shr.u32 lb, ln, 8;\n"
        "add.u32 ma, sa, %182;\n"
        "ldmatrix.sync.aligned.m8n8.x1.shared.b16 {yb}, [ma];\n"
        "add.u32 xa, sa, %181;\n"
        "mma.sync.aligned.m16n8k16.row.col.f32.bf16.bf16.f32 {%128,%129,%130,%131}, {b0,b1,b2,b3}, {x0,x1}, {%128,%129,%130,%131};\n"
        "mma.sync.aligned.m16n8k16.row.col.f32.bf16.bf16.f32 {%132,%133,%134,%135}, {b0,b1,b2,b3}, {x2,x3}, {%132,%133,%134,%135};\n"
        "ld.shared.v4.u32 {x0,x1,x2,x3}, [xa+0];\n"
        "tanh.approx.f32 t0, p0;\n"
        "tanh.approx.f32 t1, p2;\n"
        "fma.rn.f32 t0, p0, t0, p0;\n"
        "fma.rn.f32 t1, p2, t1, p2;\n"
        "cvt.rn.bf16x2.f32 r0, t1, t0;\n"
        "mma.sync.aligned.m16n8k16.row.col.f32.bf16.bf16.f32 {%136,%137,%138,%139}, {b0,b1,b2,b3}, {x4,x5}, {%136,%137,%138,%139};\n"
        "mma.sync.aligned.m16n8k16.row.col.f32.bf16.bf16.f32 {%140,%141,%142,%143}, {b0,b1,b2,b3}, {x6,x7}, {%140,%141,%142,%143};\n"
        "ld.shared.v4.u32 {x4,x5,x6,x7}, [xa+128];\n"
        "tanh.approx.f32 t0, p4;\n"
        "tanh.approx.f32 t1, p6;\n"
        "fma.rn.f32 t0, p4, t0, p4;\n"
        "fma.rn.f32 t1, p6, t1, p6;\n"
        "cvt.rn.bf16x2.f32 r1, t1, t0;\n"
        "mma.sync.aligned.m16n8k8.row.col.f32.bf16.bf16.f32 {d0,d1,d2,d3}, {%177,%178}, {yb}, {fz,fz,fz,fz};\n"
        "cvt.rn.bf16x2.f32 a0, d2, d0;\n"
        "cvt.rn.bf16x2.f32 a1, d3, d1;\n"
        "mov.b32 {lo,hi}, r2;\n"
        "mov.b32 rl, {lo,lo};\n"
        "mov.b32 rh, {hi,hi};\n"
        "mul.bf16x2 x8, x8, rl;\n"
        "mul.bf16x2 x9, x9, rl;\n"
        "mul.bf16x2 x10, x10, rh;\n"
        "mul.bf16x2 x11, x11, rh;\n"
        "mma.sync.aligned.m16n8k16.row.col.f32.bf16.bf16.f32 {%144,%145,%146,%147}, {b0,b1,b2,b3}, {x8,x9}, {%144,%145,%146,%147};\n"
        "mma.sync.aligned.m16n8k16.row.col.f32.bf16.bf16.f32 {%148,%149,%150,%151}, {b0,b1,b2,b3}, {x10,x11}, {%148,%149,%150,%151};\n"
        "ld.shared.v4.u32 {x8,x9,x10,x11}, [xa+256];\n"
        "tanh.approx.f32 t0, p8;\n"
        "tanh.approx.f32 t1, p10;\n"
        "fma.rn.f32 t0, p8, t0, p8;\n"
        "fma.rn.f32 t1, p10, t1, p10;\n"
        "cvt.rn.bf16x2.f32 r2, t1, t0;\n"
        "mma.sync.aligned.m16n8k8.row.col.f32.bf16.bf16.f32 {d0,d1,d2,d3}, {%179,%180}, {yb}, {fz,fz,fz,fz};\n"
        "cvt.rn.bf16x2.f32 a2, d2, d0;\n"
        "cvt.rn.bf16x2.f32 a3, d3, d1;\n"
        "mov.b32 {lo,hi}, r3;\n"
        "mov.b32 rl, {lo,lo};\n"
        "mov.b32 rh, {hi,hi};\n"
        "mul.bf16x2 x12, x12, rl;\n"
        "mul.bf16x2 x13, x13, rl;\n"
        "mul.bf16x2 x14, x14, rh;\n"
        "mul.bf16x2 x15, x15, rh;\n"
        "mma.sync.aligned.m16n8k16.row.col.f32.bf16.bf16.f32 {%152,%153,%154,%155}, {b0,b1,b2,b3}, {x12,x13}, {%152,%153,%154,%155};\n"
        "mma.sync.aligned.m16n8k16.row.col.f32.bf16.bf16.f32 {%156,%157,%158,%159}, {b0,b1,b2,b3}, {x14,x15}, {%156,%157,%158,%159};\n"
        "ld.shared.v4.u32 {x12,x13,x14,x15}, [xa+384];\n"
        "tanh.approx.f32 t0, p12;\n"
        "tanh.approx.f32 t1, p14;\n"
        "fma.rn.f32 t0, p12, t0, p12;\n"
        "fma.rn.f32 t1, p14, t1, p14;\n"
        "cvt.rn.bf16x2.f32 r3, t1, t0;\n"
        "mov.b32 {lo,hi}, r0;\n"
        "mov.b32 rl, {lo,lo};\n"
        "mov.b32 rh, {hi,hi};\n"
        "mul.bf16x2 x0, x0, rl;\n"
        "mul.bf16x2 x1, x1, rl;\n"
        "mul.bf16x2 x2, x2, rh;\n"
        "mul.bf16x2 x3, x3, rh;\n"
        "mov.b32 {lo,hi}, r1;\n"
        "mov.b32 rl, {lo,lo};\n"
        "mov.b32 rh, {hi,hi};\n"
        "mul.bf16x2 x4, x4, rl;\n"
        "mul.bf16x2 x5, x5, rl;\n"
        "mul.bf16x2 x6, x6, rh;\n"
        "mul.bf16x2 x7, x7, rh;\n"
        "brx.idx.uni la, TA_%=;\n"
        "EXIT_%=:\n"
        "mov.u32 %160, ring;\n"
        "}\n"
        : "+f"(acc[0][0][0][0]), "+f"(acc[0][0][0][1]), "+f"(acc[0][0][0][2]), "+f"(acc[0][0][0][3]), "+f"(acc[0][0][1][0]),
          "+f"(acc[0][0][1][1]), "+f"(acc[0][0][1][2]), "+f"(acc[0][0][1][3]), "+f"(acc[0][1][0][0]), "+f"(acc[0][1][0][1]),
          "+f"(acc[0][1][0][2]), "+f"(acc[0][1][0][3]), "+f"(acc[0][1][1][0]), "+f"(acc[0][1][1][1]), "+f"(acc[0][1][1][2]),
          "+f"(acc[0][1][1][3]), "+f"(acc[0][2][0][0]), "+f"(acc[0][2][0][1]), "+f"(acc[0][2][0][2]), "+f"(acc[0][2][0][3]),
          "+f"(acc[0][2][1][0]), "+f"(acc[0][2][1][1]), "+f"(acc[0][2][1][2]), "+f"(acc[0][2][1][3]), "+f"(acc[0][3][0][0]),
          "+f"(acc[0][3][0][1]), "+f"(acc[0][3][0][2]), "+f"(acc[0][3][0][3]), "+f"(acc[0][3][1][0]), "+f"(acc[0][3][1][1]),
          "+f"(acc[0][3][1][2]), "+f"(acc[0][3][1][3]), "+f"(acc[1][0][0][0]), "+f"(acc[1][0][0][1]), "+f"(acc[1][0][0][2]),
          "+f"(acc[1][0][0][3]), "+f"(acc[1][0][1][0]), "+f"(acc[1][0][1][1]), "+f"(acc[1][0][1][2]), "+f"(acc[1][0][1][3]),
          "+f"(acc[1][1][0][0]), "+f"(acc[1][1][0][1]), "+f"(acc[1][1][0][2]), "+f"(acc[1][1][0][3]), "+f"(acc[1][1][1][0]),
          "+f"(acc[1][1][1][1]), "+f"(acc[1][1][1][2]), "+f"(acc[1][1][1][3]), "+f"(acc[1][2][0][0]), "+f"(acc[1][2][0][1]),
          "+f"(acc[1][2][0][2]), "+f"(acc[1][2][0][3]), "+f"(acc[1][2][1][0]), "+f"(acc[1][2][1][1]), "+f"(acc[1][2][1][2]),
          "+f"(acc[1][2][1][3]), "+f"(acc[1][3][0][0]), "+f"(acc[1][3][0][1]), "+f"(acc[1][3][0][2]), "+f"(acc[1][3][0][3]),
          "+f"(acc[1][3][1][0]), "+f"(acc[1][3][1][1]), "+f"(acc[1][3][1][2]), "+f"(acc[1][3][1][3]), "+f"(acc[2][0][0][0]),
          "+f"(acc[2][0][0][1]), "+f"(acc[2][0][0][2]), "+f"(acc[2][0][0][3]), "+f"(acc[2][0][1][0]), "+f"(acc[2][0][1][1]),
          "+f"(acc[2][0][1][2]), "+f"(acc[2][0][1][3]), "+f"(acc[2][1][0][0]), "+f"(acc[2][1][0][1]), "+f"(acc[2][1][0][2]),
          "+f"(acc[2][1][0][3]), "+f"(acc[2][1][1][0]), "+f"(acc[2][1][1][1]), "+f"(acc[2][1][1][2]), "+f"(acc[2][1][1][3]),
          "+f"(acc[2][2][0][0]), "+f"(acc[2][2][0][1]), "+f"(acc[2][2][0][2]), "+f"(acc[2][2][0][3]), "+f"(acc[2][2][1][0]),
          "+f"(acc[2][2][1][1]), "+f"(acc[2][2][1][2]), "+f"(acc[2][2][1][3]), "+f"(acc[2][3][0][0]), "+f"(acc[2][3][0][1]),
          "+f"(acc[2][3][0][2]), "+f"(acc[2][3][0][3]), "+f"(acc[2][3][1][0]), "+f"(acc[2][3][1][1]), "+f"(acc[2][3][1][2]),
          "+f"(acc[2][3][1][3]), "+f"(acc[3][0][0][0]), "+f"(acc[3][0][0][1]), "+f"(acc[3][0][0][2]), "+f"(acc[3][0][0][3]),
          "+f"(acc[3][0][1][0]), "+f"(acc[3][0][1][1]), "+f"(acc[3][0][1][2]), "+f"(acc[3][0][1][3]), "+f"(acc[3][1][0][0]),
          "+f"(acc[3][1][0][1]), "+f"(acc[3][1][0][2]), "+f"(acc[3][1][0][3]), "+f"(acc[3][1][1][0]), "+f"(acc[3][1][1][1]),
          "+f"(acc[3][1][1][2]), "+f"(acc[3][1][1][3]), "+f"(acc[3][2][0][0]), "+f"(acc[3][2][0][1]), "+f"(acc[3][2][0][2]),
          "+f"(acc[3][2][0][3]), "+f"(acc[3][2][1][0]), "+f"(acc[3][2][1][1]), "+f"(acc[3][2][1][2]), "+f"(acc[3][2][1][3]),
          "+f"(acc[3][3][0][0]), "+f"(acc[3][3][0][1]), "+f"(acc[3][3][0][2]), "+f"(acc[3][3][0][3]), "+f"(acc[3][3][1][0]),
          "+f"(acc[3][3][1][1]), "+f"(acc[3][3][1][2]), "+f"(acc[3][3][1][3]), "+f"(acc[4][0][0][0]), "+f"(acc[4][0][0][1]),
          "+f"(acc[4][0][0][2]), "+f"(acc[4][0][0][3]), "+f"(acc[4][0][1][0]), "+f"(acc[4][0][1][1]), "+f"(acc[4][0][1][2]),
          "+f"(acc[4][0][1][3]), "+f"(acc[4][1][0][0]), "+f"(acc[4][1][0][1]), "+f"(acc[4][1][0][2]), "+f"(acc[4][1][0][3]),
          "+f"(acc[4][1][1][0]), "+f"(acc[4][1][1][1]), "+f"(acc[4][1][1][2]), "+f"(acc[4][1][1][3]), "+f"(acc[4][2][0][0]),
          "+f"(acc[4][2][0][1]), "+f"(acc[4][2][0][2]), "+f"(acc[4][2][0][3]), "+f"(acc[4][2][1][0]), "+f"(acc[4][2][1][1]),
          "+f"(acc[4][2][1][2]), "+f"(acc[4][2][1][3]), "+f"(acc[4][3][0][0]), "+f"(acc[4][3][0][1]), "+f"(acc[4][3][0][2]),
          "+f"(acc[4][3][0][3]), "+f"(acc[4][3][1][0]), "+f"(acc[4][3][1][1]), "+f"(acc[4][3][1][2]), "+f"(acc[4][3][1][3]),
          "+r"(ring)
        : "r"(wf[0][0]), "r"(wf[0][1]), "r"(wf[0][2]), "r"(wf[0][3]), "r"(wf[1][0]), "r"(wf[1][1]), "r"(wf[1][2]), "r"(wf[1][3]),
          "r"(wf[2][0]), "r"(wf[2][1]), "r"(wf[2][2]), "r"(wf[2][3]), "r"(wf[3][0]), "r"(wf[3][1]), "r"(wf[3][2]), "r"(wf[3][3]),
          "r"(cgf[0]), "r"(cgf[1]), "r"(cgf[2]), "r"(cgf[3]), "r"(xoff), "r"(moff), "r"(rec)
        : "memory");
}

__device__ __noinline__ void generic_path(float* sagg, const __nv_bfloat16* x, const int* src, const int* dst,
                                          const __nv_bfloat16* Y, const __nv_bfloat16* ef, const __nv_bfloat16* w_rad,
                                          const __nv_bfloat16* cg, int x0, int x1) {
    const int tid = threadIdx.x, lane = tid & 31, blk = blockIdx.x;
    for (int k = 0; k < 2; k++)
        for (int r = 0; r < min(k == 0 ? x0 : x1, 32); r++) {
            uint32_t* p2 = g_mail2 + (blk * NSRC + ((tid + k * NTHR) >> 3)) * 32 + r;
            uint32_t v;
            int it = 0;
            do {
                asm volatile("ld.relaxed.gpu.global.u32 %0, [%1];" : "=r"(v) : "l"(p2) : "memory");
                if (++it > (1 << 20)) __trap();
            } while (v == 0);
            *p2 = 0;
        }
    __syncthreads();
    for (int i = tid; i < NPB * 512; i += NTHR) sagg[i] = 0.f;
    __syncthreads();
    for (int e0 = tid & ~31; e0 < N_EDGES; e0 += NTHR) {
        uint32_t bm = __ballot_sync(~0u, dst[e0 + lane] / NPB == blk);
        while (bm) {
            const int e = e0 + __ffs(bm) - 1, s = src[e], loc = dst[e] - blk * NPB;
            bm &= bm - 1;
            float a[4][4];
            for (int i = 0; i < 4; i++)
                for (int o = 0; o < 4; o++) {
                    a[i][o] = 0.f;
                    for (int f = 0; f < 4; f++)
                        a[i][o] += __bfloat162float(Y[e * 4 + f]) * __bfloat162float(cg[i * 16 + f * 4 + o]);
                }
#pragma unroll 1
            for (int c = lane; c < 128; c += 32) {
                float pre = 0.f;
                for (int k = 0; k < 16; k++)
                    pre += __bfloat162float(ef[e * 16 + k]) * __bfloat162float(w_rad[k * 128 + c]);
                const float R = pre / (1.f + __expf(-pre));
                for (int o = 0; o < 4; o++) {
                    float acc = 0.f;
                    for (int i = 0; i < 4; i++) acc += __bfloat162float(x[(size_t)s * 512 + c * 4 + i]) * a[i][o];
                    atomicAdd(&sagg[loc * 512 + c * 4 + o], R * acc);
                }
            }
        }
    }
    __syncthreads();
}

__device__ __forceinline__ void init_barriers() {
    extern __shared__ __align__(1024) uint8_t smem[];
    const uint32_t sb = smem_u32(smem);
#pragma unroll
    for (int i = 0; i < 4 * NG; i++) {
        mbar_init(sb + i * STAGE + 4 * ROWP, 32);
        mbar_init(sb + i * STAGE + 4 * ROWP + 8, 2);
    }
}

template <int PHASES>
__global__ void __launch_bounds__(NTHR, 1)
tfn_kernel(const __nv_bfloat16* __restrict__ x, const int* __restrict__ src, const int* __restrict__ dst,
           const __nv_bfloat16* __restrict__ Y, const __nv_bfloat16* __restrict__ ef,
           const __nv_bfloat16* __restrict__ w_rad, const __nv_bfloat16* __restrict__ cg,
           const __nv_bfloat16* __restrict__ w_mix, __nv_bfloat16* __restrict__ out) {
    extern __shared__ __align__(1024) uint8_t smem[];
    const int tid = threadIdx.x, lane = tid & 31;
    const int warp = __shfl_sync(~0u, tid >> 5, 0);
    const int blk = blockIdx.x;
    uint32_t sb = smem_u32(smem);
    asm volatile("" : "+r"(sb));
    int* mi = reinterpret_cast<int*>(smem + SM_MISC);

    const int g = lane >> 2, t = lane & 3;
    const uint32_t dump = sb + SC_DUMP + lane * 4;
    int4 d1[2], s1[2];
    constexpr int nq = EPC / 4;
    const bool binner = (PHASES & 1) && blk < NSRC;
    if (binner) {
#pragma unroll
        for (int k = 0; k < 2; k++) {
            const int q = tid + k * NTHR;
            if (q < nq) {
                d1[k] = __ldg(reinterpret_cast<const int4*>(dst + blk * EPC) + q);
                s1[k] = __ldg(reinterpret_cast<const int4*>(src + blk * EPC) + q);
            }
        }
    }
    if (binner) {
        const uint32_t dmy = ((((blk & 3) * 8 + (tid & 7)) << 25) | (80 * 2560 + 1));
#pragma unroll
        for (int k = 0; k < 3; k++)
            if (k < 2 || warp < 1) sts128(sb + SC_MAIL + (tid + k * NTHR) * 16, dmy, dmy + (1u << 30), dmy, dmy + (1u << 30));
        if (tid <= NB / 4) sts128(sb + SC_CNT + tid * 16, 0, 0, 0, 0);
    }
    if (PHASES & 2) {
        if (tid == 160) { sts128(sb + SM_MISC, 0, 0, 0, 0); sts128(sb + SM_MISC + MI_NU * 4, 0, 0, 0, 0); }
        if (tid == 161) {
            mi[MI_SHIFT] = 0;
            *reinterpret_cast<int**>(mi + MI_SHIFT + 4) = g_lag[blk];
        }
        if (tid == 162) g_lag[blk][0] = g_lag[NB + blk][0] = 0;
        if (tid <= 21 * HS / 4) sts128(sb + SC_HIST + tid * 16, 0, 0, 0, 0);
        const uint32_t pad = (uint32_t)(lane * 0x10008 + 7);
#pragma unroll
        for (int k = 0; k < 3; k++)
            if (tid + k * NTHR < 4 * UCAP * REC / 16) sts128(sb + SM_REC + (tid + k * NTHR) * 16, pad, pad, pad, pad);
    }
    __syncthreads();
    if (PHASES & 2) {
        if (warp >= 8) cp16(sb + SC_WR + ((tid - 256) ^ ((tid >> 4) & 6)) * 16, w_rad + (tid - 256) * 8);
        if (tid < 8) cp16(sb + SC_WR + 4096 + tid * 16, cg + tid * 8);
        asm volatile("cp.async.commit_group;" ::: "memory");
#pragma unroll
        for (int k = 0; k < 4; k++) {
            const int i = tid + k * NTHR, c = i >> 4;
            cp16(sb + SM_W + c * 256 + (((i & 15) ^ ((c & 2) | (((c >> 4) & 1) << 2))) << 4), w_mix + i * 8);
        }
    }
    if (binner) {
#pragma unroll
        for (int k = 0; k < 2; k++) {
            if (tid + k * NTHR < nq) {
                const uint32_t dd[4] = {(uint32_t)d1[k].x, (uint32_t)d1[k].y, (uint32_t)d1[k].z, (uint32_t)d1[k].w};
                const uint32_t ss[4] = {(uint32_t)s1[k].x, (uint32_t)s1[k].y, (uint32_t)s1[k].z, (uint32_t)s1[k].w};
                uint32_t own[4], rk[4], v[4];
#pragma unroll
                for (int j = 0; j < 4; j++) { own[j] = dd[j] / NPB; rk[j] = atoms_inc(sb + SC_CNT + own[j] * 4); }
#pragma unroll
                for (int j = 0; j < 4; j++) {
                    const uint32_t loc = dd[j] - own[j] * NPB, code = loc + ((loc * 216) >> 12);
                    v[j] = (ss[j] << 18) + code * 2560 + (tid + k * NTHR) * 4 + j + 1;
                    sts32(sb + SC_MAIL + own[j] * 128 + ((min(rk[j], 31u) * 4) ^ ((own[j] & 7) << 4)), v[j]);
                }
                if (max(max(rk[0], rk[1]), max(rk[2], rk[3])) >= 31) {
#pragma unroll
                    for (int j = 0; j < 4; j++)
                        if (rk[j] - 31 < 32)
                            asm volatile("st.relaxed.gpu.global.u32 [%0], %1;" ::"l"(g_mail2 + (own[j] * NSRC + blk) * 32 + rk[j] - 31), "r"(v[j]) : "memory");
                }
            }
        }
        __syncwarp();
        asm volatile("red.shared.max.u32 [%0], %1;" ::"r"(lane == 0 ? sb + SC_CNT + NB * 4 : dump), "r"(gtime()) : "memory");
        STAMP(1);
    }
    asm volatile("cp.async.wait_group 0;" ::: "memory");
    __syncthreads();
    if (binner) {
        const uint32_t hdr = 0xc0000000u | ((lds32(sb + SC_CNT + NB * 4) << 7) & 0x3ffff000u);
        uint4 mv[3];
        uint32_t mc[3];
#pragma unroll
        for (int k = 0; k < 3; k++)
            if (k < 2 || warp < 1) {
                const int j = tid + k * NTHR, own = j >> 3;
                mv[k] = lds128(sb + SC_MAIL + own * 128 + (((j ^ own) & 7) << 4));
                mc[k] = lds32(sb + SC_CNT + own * 4);
            }
#pragma unroll
        for (int k = 0; k < 3; k++)
            if (k < 2 || warp < 1) {
                const int j = tid + k * NTHR;
                asm volatile("st.relaxed.gpu.global.v4.u32 [%0], {%1,%2,%3,%4};" ::"l"(g_mail + ((j >> 3) * NSRC + blk) * 8 + (j & 7)),
                             "r"(mv[k].x), "r"(mv[k].y), "r"(mv[k].z), "r"((j & 7) == 7 ? hdr | mc[k] : mv[k].w) : "memory");
            }
        STAMP(2);
    }
    if (!(PHASES & 2)) return;
    const uint32_t tpub = (uint32_t)clock() + (blk < NSRC ? 0 : IDLE_EST);
    if (warp >= 7) {
        uint32_t f[4];
        if (warp >= 8) {
            uint32_t w[4];
#pragma unroll
            for (int j = 0; j < 4; j++)
                w[j] = mul_lo(lds32(sb + SC_WR + (2 * t + (j & 1) + (j >> 1) * 8) * 256 + ((((warp - 8) * 8 + g) * 4) ^ (t << 5))), 0x3f003f00u);
            f[0] = __byte_perm(w[0], w[1], 0x5410); f[1] = __byte_perm(w[0], w[1], 0x7632);
            f[2] = __byte_perm(w[2], w[3], 0x5410); f[3] = __byte_perm(w[2], w[3], 0x7632);
        } else {
#pragma unroll
            for (int i = 0; i < 4; i++) {
                const uint32_t ca = sb + SC_WR + 4096 + (i * 16 + (t & 1) * 8 + (g & 3)) * 2;
                f[i] = (lds16(ca) | (lds16(ca + 8) << 16)) & ((t >> 1) == (g >> 2) ? ~0u : 0u);
            }
        }
        const uint32_t d = sb + (warp == 7 ? 2 * ROWP : ((warp - 8) >> 2) * ROWP + (warp & 3) * 512) + lane * 16;
#pragma unroll
        for (int k = 0; k < 4; k++) sts128(d + k * NG * STAGE, f[0], f[1], f[2], f[3]);
    }
    asm volatile("cp.async.wait_all;" ::: "memory");
    __syncwarp();
#pragma unroll
    for (int k = 0; k < 2; k++) {
        const int i = (tid & ~1) + ((tid & 1) * 2 + k) * NTHR, c = i >> 4;
        const uint32_t a0 = sb + SM_W + c * 256 + (((i & 15) ^ ((c & 3) | (((c >> 4) & 1) << 2))) << 4);
        const uint32_t o = (tid & 1) << 4;
        uint4 u = lds128((a0 & ~16u) ^ o), v = lds128((a0 | 16u) ^ o);
        if (tid & 1) { const uint4 w = u; u = v; v = w; }
        const uint32_t s0 = (tid & 1) ? 0x7632 : 0x5410, s1 = s0 ^ 0x2222;
        sts128(a0 ^ o, __byte_perm(u.x, u.y, s0), __byte_perm(u.z, u.w, s0), __byte_perm(v.x, v.y, s0), __byte_perm(v.z, v.w, s0));
        sts128(a0 ^ o ^ 16, __byte_perm(u.x, u.y, s1), __byte_perm(u.z, u.w, s1), __byte_perm(v.x, v.y, s1), __byte_perm(v.z, v.w, s1));
    }

    uint32_t en[8], hr[8], rk[8], em[8];
    int xc[2];
    const uint32_t tref = __shfl_sync(~0u, gtime() >> 5, 0);
    {
        uint4* mp = g_mail + blk * NSRC * 8 + tid;
        int it = 0;
        bool ok;
        while ((int)((uint32_t)clock() - tpub) < POLL_DELAY) {}
        do {
#pragma unroll
            for (int k = 0; k < 2; k++)
                    asm volatile("ld.relaxed.gpu.global.v4.u32 {%0,%1,%2,%3}, [%4];"
                                 : "=r"(en[4 * k]), "=r"(en[4 * k + 1]), "=r"(en[4 * k + 2]), "=r"(en[4 * k + 3])
                                 : "l"(mp + k * NTHR) : "memory");
            uint32_t m = ~0u;
#pragma unroll
            for (int i = 0; i < 8; i++) m = min(m, en[i]);
            ok = __all_sync(~0u, m != 0);
            if (++it > (1 << 20)) __trap();
        } while (!ok);
        STAMP(3);
        const bool hd = (lane & 7) == 7;
        const uint32_t h0 = en[3], h1 = en[7];
        if (hd) en[3] = en[7] = ((64 + (tid >> 5)) << 25) | (80 * 2560 + 1);
        const uint32_t e0 = (tid >> 3) * EPC * 8 - 8;
#pragma unroll
        for (int i = 0; i < 8; i++) {
            const uint32_t w = en[i] & 0x3ffff, code = ((w >> 9) * 13108) >> 16;
            hr[i] = sb + SC_HIST + ((code >> 2) * HS + (en[i] >> 25)) * 4;
            rk[i] = atoms_inc(hr[i]);
            em[i] = (e0 + (i >> 2) * (NTHR / 8 * EPC * 8) + (w - code * 2560) * 8) | (code & 3);
        }
        int dt = hd ? max((int)(((h0 >> 12) - tref) << 14), (int)(((h1 >> 12) - tref) << 14)) >> 14 : -(1 << 20);
        xc[0] = hd ? max((int)(h0 & 0xfff) - 31, 0) : 0;
        xc[1] = hd ? max((int)(h1 & 0xfff) - 31, 0) : 0;
        dt = __reduce_max_sync(~0u, dt);
        asm volatile("red.shared.max.u32 [%0], %1;" ::"r"(lane == 0 ? sb + SM_MISC + MI_TMAX * 4 : dump + 128), "r"(tref + dt + (1u << 27)) : "memory");
        if (xc[0] | xc[1]) {
#pragma unroll
            for (int k = 0; k < 2; k++) {
                const int slot = atomicAdd(&mi[MI_XN], xc[k]);
                for (int r = 0; r < xc[k] && slot + r < 32; r++)
                    reinterpret_cast<uint32_t*>(smem + SC_XTRA)[slot + r] = ((tid + k * NTHR) >> 3) * 32 + r;
            }
        }
#pragma unroll
        for (int k = 0; k < 2; k++)
            mp[k * NTHR] = make_uint4(0, 0, 0, 0);
    }
    __syncthreads();
    STAMP(4);
    uint32_t* hist = reinterpret_cast<uint32_t*>(smem + SC_HIST);
    const int xn = mi[MI_XN];
    uint32_t xi = 0, xv = 1;
    if (warp < 10) {
        uint32_t* hp = hist + (warp * 2 + (lane >> 4)) * HS + (lane & 15) * 5;
        int c[5], s = 0;
#pragma unroll
        for (int j = 0; j < 5; j++) { c[j] = hp[j]; s += c[j]; }
        int inc = s;
#pragma unroll
        for (int o = 1; o < 16; o <<= 1) { int v = __shfl_up_sync(~0u, inc, o, 16); if ((lane & 15) >= o) inc += v; }
        int base = 0;
        if ((lane & 15) == 15) {
            const int tm = (warp * 2 + (lane >> 4)) / 5;
            base = tm * 256 + atomicAdd(&mi[MI_NU + tm], (inc + 3) >> 2);
            hp[5] = (base + ((inc + 3) >> 2)) << 16;
        }
        const int tot = __shfl_sync(~0u, inc, 15, 16);
        base = __shfl_sync(~0u, base, 15, 16);
        int ex = inc - s;
#pragma unroll
        for (int j = 0; j < 5; j++) {
            hp[j] = (base * 4 + ex) | ((base + ((ex == tot ? ex + 3 : ex + 1) >> 2)) << 16);
            ex += c[j];
        }
    } else if (warp == 10) {
        if (lane < xn) {
            xi = reinterpret_cast<const uint32_t*>(smem + SC_XTRA)[lane];
            asm volatile("ld.relaxed.gpu.global.u32 %0, [%1];" : "=r"(xv) : "l"(g_mail2 + blk * NSRC * 32 + xi) : "memory");
        }
    } else if (warp == 12) {
        if (lane == 0) init_barriers();
    } else if (warp == 11) {
        sts32(sb + SC_GPOS + (GDUMMY + lane) * 4, (uint32_t)(4 * UCAP * REC + 128) * 0x10001u);
#pragma unroll
        for (int k = 0; k < 3; k++) hist[20 * HS + min(lane + 32 * k, NBK)] = GDUMMY * 4;
        constexpr int start_ns = START_NS;
        if (lane == 0) mi[MI_T0] = (uint32_t)clock() + (((int)(((uint32_t)mi[MI_TMAX] << 5) + start_ns - gtime()) * 31) >> 4);
    }
    constexpr int pace = PACE_Q8, p1 = PACE_HEAD, b1 = HEAD_BK, p2 = PACE_TAIL, b2 = TAIL_BK, lead = PACE_LEAD;
    auto sched = [&](int b) { return b * pace - min(b, b1) * (pace - p1) - max(b - b2, 0) * (pace - p2) - lead; };
    const int mteam = tid / NBK, mb = tid - mteam * NBK;
    int tb0 = sched(mb);
    float tbw = (float)(sched(mb + 1) - tb0);
    uint32_t mh = sb + SC_HIST + (mteam * 5 * HS + mb) * 4 + 2, mh0 = sb + SC_HIST + mteam * 5 * HS * 4 + 2;
    asm volatile("" : "+r"(tb0), "+f"(tbw), "+r"(mh), "+r"(mh0));
    __syncthreads();
    STAMP(10);
    int myng = mi[MI_NU + (lane & 3)];
    const bool ovf = __any_sync(~0u, myng + xn > 2 * (UCAP - 4) || xn > 32);
    if (!ovf) {
        if (warp < 10) {
            int lo[5], n[5], pos = mteam * UCAP * 2, nsum = 0;
#pragma unroll
            for (int q = 0; q < 5; q++) {
                lo[q] = lds16(mh + q * HS * 4);
                n[q] = lds16(mh + q * HS * 4 + 4) - lo[q];
                pos += lo[q] - lds16(mh0 + q * HS * 4);
                nsum += n[q];
            }
            const int step = __float2int_rz(__fdividef(tbw, (float)max(nsum, 1)));
            const int tb = tb0 + (step >> 1) - pos * step;
            const uint32_t t0 = mi[MI_T0];
            auto emit = [&](int q, int r, int pq) {
                const uint32_t ro = (pq >> 1) * REC, par = pq & 1;
                asm volatile("{\n.reg .pred p, e;\nsetp.lt.s32 p, %0, %1;\nsetp.eq.and.u32 e, %2, 0, p;\n"
                             "@p st.shared.u32 [%3], %4;\n@p st.shared.u8 [%5+48], %6;\n@e st.shared.u16 [%5+102], %7;\n}"
                             ::"r"(r), "r"(n[q]), "r"(par), "r"(sb + SC_GPOS + (lo[q] + r) * 4),
                               "r"(ro * 0x10001u + par * 0x40002u + (REC | (16 << 16))), "r"(sb + SM_REC + ro + par), "r"(q),
                               "h"((uint16_t)((t0 + max(tb + pq * step, 0)) >> 2)) : "memory");
            };
#pragma unroll
            for (int q = 0, pq = pos; q < 5; pq += n[q], q++) emit(q, 0, pq);
#pragma unroll
            for (int q = 0; q < 5; pos += n[q], q++)
#pragma unroll 1
                for (int r = 1; __any_sync(~0u, r < n[q]); r++) emit(q, r, pos + r);
        } else if (warp == 10) {
            for (int n = 0; __any_sync(~0u, xv == 0); n++) {
                if (xv == 0) asm volatile("ld.relaxed.gpu.global.u32 %0, [%1];" : "=r"(xv) : "l"(g_mail2 + blk * NSRC * 32 + xi) : "memory");
                if (n > (1 << 20)) __trap();
            }
            const uint32_t w = xv & 0x3ffff, code = ((w >> 9) * 13108) >> 16, xt = lane < xn ? code / 20 : 4;
            const uint32_t same = __match_any_sync(~0u, xt);
            const int pq = __shfl_sync(~0u, myng, xt & 3) + __popc(same & ((1u << lane) - 1));
#pragma unroll
            for (int q = 0; q < 4; q++) {
                const int c = __popc(__ballot_sync(~0u, xt == q));
                if (lane == q) myng += c;
            }
            if (lane < xn) {
                g_mail2[blk * NSRC * 32 + xi] = 0;
                const uint32_t a = sb + SM_REC + (xt * UCAP + (pq >> 1)) * REC;
                sts16(a + REC + (pq & 1) * 2, xv >> 18);
                sts32(a + 16 + (pq & 1) * 4, (((xi >> 5) * EPC + w - code * 2560 - 1) * 8) | (code & 3));
                sts8(a + 48 + (pq & 1), (code >> 2) - xt * 5);
                if (!(pq & 1)) sts16(a + REC + 50, ((uint32_t)mi[MI_T0] + sched(NBK - 2)) >> 2);
            }
            if (lane < 4) {
                const uint32_t a = sb + SM_REC + (lane * UCAP + (myng >> 1)) * REC + 48;
                if (myng & 1) sts8(a + 1, 0);
                sts16(a + (myng & 1) * REC, 5);
                mi[MI_END + lane] = (myng + 1) >> 1;
            }
        }
#pragma unroll
        for (int i = 0; i < 8; i++) {
            const uint32_t p = rk[i] + lds16(hr[i]);
            hr[i] = sb + SC_GPOS + (p & ~3u);
            rk[i] = (p & 3) * 0x80004u;
        }
        __syncthreads();
        STAMP(11);
#pragma unroll
        for (int i = 0; i < 8; i++) rk[i] += lds32(hr[i]);
#pragma unroll
        for (int i = 0; i < 8; i++) {
            sts16(sb + SM_REC + (rk[i] & 0xffff), en[i] >> 18);
            sts32(sb + SM_REC + (rk[i] >> 16), em[i]);
        }
    } else {
        if (tid < 4) {
            sts16(sb + SM_REC + tid * UCAP * REC + 48, 5);
            mi[MI_END + tid] = 0;
        }
        generic_path(reinterpret_cast<float*>(smem), x, src, dst, Y, ef, w_rad, cg, xc[0], xc[1]);
    }

    __syncwarp();
    if (warp >= 8) {
        asm volatile("bar.sync 3, 512;" ::: "memory");
        asm volatile("setmaxnreg.dec.sync.aligned.u32 24;");
        const int team = warp & 3;
        if (ovf) {
            asm volatile("bar.sync 2;" ::: "memory");
            if (tid == 256) init_barriers();
            asm volatile("bar.sync 2;" ::: "memory");
        }
        STAMP(5);
        const uint32_t ring = sb + SM_RING + team * NG * STAGE;
        const uint32_t q = lane >> 3, c = lane & 7, rec = sb + SM_REC + team * UCAP * REC;
        __syncwarp();
        producer_loop(reinterpret_cast<const char*>(x) + (ROWMODE == 0 ? c : ROWMODE == 1 ? lane & 15 : lane) * 16, reinterpret_cast<const char*>(ef) + (c & 1) * 16, Y,
                      q * ROWP + ((c ^ (q << 1)) << 4), q * 4 + (c & 2) * 8, (c & 1) * 2 + (c >> 2), ring, rec,
                      rec + (mi[MI_END + team] + 1) * REC, warp - 8, sb + SM_MISC + MI_SHIFT * 4,
                      ROWMODE == 1 ? (lane >> 4) * ROWP + (((lane & 15) ^ ((lane >> 4) << 1)) << 4) : lane * 16);
        uint32_t ln, sb2, cta;
        asm volatile("mov.u32 %0, %%tid.x;\nmov.u32 %1, %%ctaid.x;\nmov.u32 %2, %%dynamic_smem_size;" : "=r"(ln), "=r"(cta), "=r"(sb2));
        if (FEEDBACK && cta == NB - 1 && ln >= NTHR - 32) {
            ln &= 31;
            sb2 += smem_u32(smem) - SM_TOTAL + SM_MISC;
            constexpr int lead = LEAD_CLK >> 2;
            const uint32_t tend = lds32(sb2 + MI_T0 * 4) + 70 * PACE_Q8;
            int sh = 0;
            for (int n = 0; n < 199 && (int)((uint32_t)clock() - tend - (sh >> 14)) < 0; n++) {
                int v;
                asm volatile("ld.relaxed.gpu.global.s32 %0, [%1];" : "=r"(v) : "l"(g_lag[ln * 4]) : "memory");
                const int err = (__reduce_add_sync(~0u, max(v, 0)) >> 5) - lead;
                const int old = sh;
                sh = min(max((sh >> 16) + (err * (err > 0 ? FB_GAIN : FB_DOWN) >> 3), FB_MIN), 2500) << 16;
                if (sh == old) continue;
#pragma unroll
                for (int k = 0; k < 5; k++)
                    asm volatile("st.relaxed.gpu.global.s32 [%0], %1;" ::"l"(g_lag[NB + min(ln + 32 * k, NB - 1u)]), "r"(sh) : "memory");
            }
        }
    } else {
        asm volatile("bar.arrive 3, 512;" ::: "memory");
        int team;
        {
            const int n0 = mi[MI_END], n1 = mi[MI_END + 1], n2 = mi[MI_END + 2], n3 = mi[MI_END + 3];
            const int d1 = abs(n0 + n1 - n2 - n3), d2 = abs(n0 + n2 - n1 - n3), d3 = abs(n0 + n3 - n1 - n2);
            const uint32_t perm = PAIRING && d1 < min(d2, d3) ? 0x3120 : PAIRING && d3 < d2 ? 0x2310 : 0x3210;
            team = __shfl_sync(~0u, (perm >> ((warp >> 1) * 4)) & 3, 0);
        }
        const int h = warp & 1;
        asm volatile("setmaxnreg.inc.sync.aligned.u32 232;");
        uint32_t ring = sb + SM_RING + team * NG * STAGE;
        uint32_t wf[4][4], cgf[4];
#pragma unroll
        for (int m = 0; m < 5; m++) {
            const uint4 v = lds128(ring + (m < 4 ? h * ROWP + m * 512 : 2 * ROWP) + lane * 16);
            uint32_t* f = m < 4 ? wf[m] : cgf;
            f[0] = v.x; f[1] = v.y; f[2] = v.z; f[3] = v.w;
        }
        float acc[5][4][2][4];
        if (!ovf) {
#pragma unroll
            for (int l = 0; l < 5; l++)
#pragma unroll
                for (int m = 0; m < 4; m++)
#pragma unroll
                    for (int p = 0; p < 2; p++)
#pragma unroll
                        for (int r = 0; r < 4; r++) acc[l][m][p][r] = 0.f;
        } else {
            const float* sagg = reinterpret_cast<const float*>(smem);
#pragma unroll
            for (int l = 0; l < 5; l++)
#pragma unroll
                for (int m = 0; m < 4; m++)
#pragma unroll
                    for (int p = 0; p < 2; p++)
#pragma unroll
                        for (int r = 0; r < 4; r++) {
                            int nd = l * 4 + (g >> 2) + (r >> 1) * 2;
                            int ch = h * 64 + m * 16 + 4 * t + (r & 1) * 2 + p;
                            acc[l][m][p][r] = nd < 19 ? sagg[(team * 19 + nd) * 512 + ch * 4 + (g & 3)] : 0.f;
                        }
            asm volatile("bar.sync 2;" ::: "memory");
            asm volatile("bar.sync 2;" ::: "memory");
        }
        const uint32_t xoff = t * ROWP + h * 512 + ((g ^ (t << 1)) << 4);
        const uint32_t mat = lane >> 3, mhi = (lane >> 2) & 1;
        const bool isy = mat < 2;
        const uint32_t ml = isy ? (t & 2) + (mat & 1) : t;
        const uint32_t moff = ml * ROWP + 2048 + (((isy ? 4 + 2 * mhi + (t & 1) : 2 * mhi + mat - 2) ^ (ml << 1)) << 4);
        __syncwarp();
        consumer_loop(acc, wf, cgf, xoff, ring, moff, sb + SM_REC + team * UCAP * REC);
        {
        int lane_;
        asm volatile("mov.u32 %0, %%laneid;" : "=r"(lane_));
        const int lane = lane_, g = lane >> 2, t = lane & 3;
        const uint32_t sb = ring - team * NG * STAGE;
        STAMP(7);
        asm volatile("bar.sync %0, 64;" ::"r"(4 + team) : "memory");
        {
            const int rr = ((g & 3) >> 1) * 8 + (g >> 2) * 2 + (g & 1);
#pragma unroll
            for (int l = 0; l < 5; l++)
#pragma unroll
                for (int hi = 0; hi < 2; hi++) {
                    const int R = l * 16 + rr + hi * 4;
                    const uint32_t a = sb + team * AGGT + h * 10240 + R * 128;
#pragma unroll
                    for (int c = 0; c < 2; c++) {
                        const int m = 2 * c;
                        sts128(a + (((2 * t + c) ^ (R & 7)) << 4),
                               pack_bf16(acc[l][m][0][2 * hi], acc[l][m][1][2 * hi]),
                               pack_bf16(acc[l][m][0][2 * hi + 1], acc[l][m][1][2 * hi + 1]),
                               pack_bf16(acc[l][m + 1][0][2 * hi], acc[l][m + 1][1][2 * hi]),
                               pack_bf16(acc[l][m + 1][0][2 * hi + 1], acc[l][m + 1][1][2 * hi + 1]));
                    }
                }
        }
        asm volatile("fence.proxy.async.shared::cta;" ::: "memory");
        uint32_t wa[8][4];
        {
            const int r = lane & 7, k = (lane >> 4) * 8 + r;
            const int chunk = (2 * warp + ((lane >> 3) & 1)) ^ r;
#pragma unroll
            for (int ks = 0; ks < 8; ks++) {
                const int c = (ks >> 2) * 64 + 16 * (k >> 2) + 4 * (ks & 3) + (k & 3);
                asm volatile("ldmatrix.sync.aligned.m8n8.x4.trans.shared.b16 {%0,%1,%2,%3}, [%4];"
                             : "=r"(wa[ks][0]), "=r"(wa[ks][1]), "=r"(wa[ks][2]), "=r"(wa[ks][3])
                             : "r"(sb + SM_W + c * 256 + (chunk << 4)));
            }
        }
        asm volatile("bar.sync 1, 256;" ::: "memory");
        STAMP(8);
        const int sl = (lane & 7) * 4 + (lane >> 3);
        __nv_bfloat16* op = out + (size_t)(blk * NPB + (lane >> 3)) * 512 + warp * 64 + (lane & 7) * 8;
        const int nleft = N_NODES - blk * NPB - (lane >> 3);
#pragma unroll 1
        for (int tm = 0; tm < 4; tm++) {
            float o[40];
            asm volatile("wgmma.fence.sync.aligned;" ::: "memory");
#pragma unroll
            for (int ks = 0; ks < 8; ks++) {
                const uint32_t a = sb + tm * AGGT + (ks >> 2) * 10240 + (ks & 3) * 32;
                const uint64_t desc = (uint64_t)((a & 0x3ffff) >> 4) | (1ull << 16) | (64ull << 32) | (1ull << 62);
                wgmma_n80(o, wa[ks], desc, ks);
            }
            asm volatile("wgmma.commit_group.sync.aligned;" ::: "memory");
            asm volatile("wgmma.wait_group.sync.aligned 0;" ::: "memory");
#pragma unroll
            for (int i = 0; i < 40; i++) asm volatile("" : "+f"(o[i])::"memory");
#pragma unroll
            for (int l = 0; l < 5; l++) {
                uint4 v;
                v.x = __shfl_sync(~0u, pack_bf16(o[8 * l + 0], o[8 * l + 1]), sl);
                v.y = __shfl_sync(~0u, pack_bf16(o[8 * l + 4], o[8 * l + 5]), sl);
                v.z = __shfl_sync(~0u, pack_bf16(o[8 * l + 2], o[8 * l + 3]), sl);
                v.w = __shfl_sync(~0u, pack_bf16(o[8 * l + 6], o[8 * l + 7]), sl);
                if ((l < 4 || lane < 24) && tm * 19 + l * 4 < nleft)
                    *reinterpret_cast<uint4*>(op + (tm * 19 + l * 4) * 512) = v;
            }
        }
        STAMP(9);
        }
    }
}

}

extern "C" void kernel_launch(void* const* d_in, const int* in_sizes, int n_in, void* d_out, int out_size) {
    (void)in_sizes; (void)n_in; (void)out_size;
    const __nv_bfloat16* x = (const __nv_bfloat16*)d_in[0];
    const int* src = (const int*)d_in[1];
    const int* dst = (const int*)d_in[2];
    const __nv_bfloat16* Y = (const __nv_bfloat16*)d_in[3];
    const __nv_bfloat16* ef = (const __nv_bfloat16*)d_in[4];
    const __nv_bfloat16* w_rad = (const __nv_bfloat16*)d_in[5];
    const __nv_bfloat16* cg = (const __nv_bfloat16*)d_in[6];
    const __nv_bfloat16* w_mix = (const __nv_bfloat16*)d_in[7];
    __nv_bfloat16* out = (__nv_bfloat16*)d_out;

    static int sms = 0;
    if (sms == 0) {
        int dev = 0;
        cudaGetDevice(&dev);
        cudaDeviceGetAttribute(&sms, cudaDevAttrMultiProcessorCount, dev);
        cudaFuncSetAttribute(tfn_kernel<3>, cudaFuncAttributeMaxDynamicSharedMemorySize, SM_TOTAL);
        cudaFuncSetAttribute(tfn_kernel<1>, cudaFuncAttributeMaxDynamicSharedMemorySize, SM_TOTAL);
        cudaFuncSetAttribute(tfn_kernel<2>, cudaFuncAttributeMaxDynamicSharedMemorySize, SM_TOTAL);
    }
    if (sms >= NB) {
        tfn_kernel<3><<<NB, NTHR, SM_TOTAL>>>(x, src, dst, Y, ef, w_rad, cg, w_mix, out);
    } else {
        tfn_kernel<1><<<NB, NTHR, SM_TOTAL>>>(x, src, dst, Y, ef, w_rad, cg, w_mix, out);
        tfn_kernel<2><<<NB, NTHR, SM_TOTAL>>>(x, src, dst, Y, ef, w_rad, cg, w_mix, out);
    }
}
```

```cpp
#include <cuda_runtime.h>
#include <cuda_bf16.h>
#include <stdint.h>

namespace {

constexpr int N_NODES = 10000;
constexpr int N_EDGES = 320000;
constexpr int NB      = 132;
constexpr int NPB     = 76;
constexpr int NSRC    = 128;
constexpr int EPC     = N_EDGES / NSRC;
constexpr int NTHR    = 512;
constexpr int NG      = 5;
constexpr int ROWP    = 2176;
constexpr int STAGE   = 4 * ROWP + 128;
constexpr int UCAP    = 104;
constexpr int REC     = 52;
constexpr int NBK     = 80;
constexpr int HS      = 81;

#define PACE_Q8 635
#define PACE_LEAD 300
#define PACE_HEAD 705
#define HEAD_BK 10
#define PACE_TAIL 610
#define TAIL_BK 66
#define IDLE_EST 900
#define POLL_DELAY 1280
#define LEAD_CLK 140
#define FB_GAIN 24
#define FB_DOWN 4
#define FB_MIN 0
#define START_NS 3150

constexpr int SM_RING  = 0;
constexpr int SM_W     = 4 * NG * STAGE;
constexpr int SM_REC   = SM_W + 32768;
constexpr int SM_MISC  = SM_REC + 4 * UCAP * REC;
constexpr int SM_TOTAL = SM_MISC + 224;
constexpr int SC_MAIL  = 1 * STAGE;
constexpr int SC_CNT   = 3 * STAGE;
constexpr int SC_DUMP  = 3 * STAGE + 1024;
constexpr int SC_XTRA  = 3 * STAGE + 2048;
constexpr int SC_HIST  = 4 * STAGE;
constexpr int SC_GPOS  = 6 * STAGE;
constexpr int SC_WR    = 7 * STAGE;
constexpr int GDUMMY   = 1024;
constexpr int AGGT     = (NG * STAGE + 1023) / 1024 * 1024;
static_assert(3 * AGGT + 20480 <= 4 * NG * STAGE, "agg tile inside the team's ring");
static_assert(NPB * 512 * 4 <= 4 * NG * STAGE, "slow tile");
static_assert(SM_TOTAL <= 232448, "smem");
static_assert(SM_REC % 16 == 0 && (4 * UCAP * REC) % 16 == 0 && SM_MISC % 16 == 0, "align");
constexpr int MI_XN = 0;
constexpr int MI_TMAX = 2;
constexpr int MI_SHIFT = 48;
constexpr int MI_NU = 8;
constexpr int MI_END = 28;
constexpr int MI_T0 = 3;

__device__ __align__(128) uint4 g_mail[NB * NSRC * 8];
__device__ __align__(128) uint32_t g_mail2[NB * NSRC * 32];
__device__ __align__(128) int g_lag[2 * NB][32];
#define STAMP(k)

__device__ __forceinline__ uint32_t smem_u32(const void* p) { return (uint32_t)__cvta_generic_to_shared(p); }
__device__ __forceinline__ uint32_t atoms_inc(uint32_t a) {
    uint32_t r;
    asm volatile("atom.shared.add.u32 %0, [%1], 1;" : "=r"(r) : "r"(a) : "memory");
    return r;
}
__device__ __forceinline__ void sts32(uint32_t a, uint32_t v) { asm volatile("st.shared.u32 [%0], %1;" ::"r"(a), "r"(v) : "memory"); }
__device__ __forceinline__ void sts16(uint32_t a, uint32_t v) { asm volatile("st.shared.u16 [%0], %1;" ::"r"(a), "h"((uint16_t)v) : "memory"); }
__device__ __forceinline__ void sts8(uint32_t a, uint32_t v) { asm volatile("st.shared.u8 [%0], %1;" ::"r"(a), "r"(v) : "memory"); }
__device__ __forceinline__ uint32_t lds32(uint32_t a) { uint32_t v; asm volatile("ld.shared.u32 %0, [%1];" : "=r"(v) : "r"(a)); return v; }
__device__ __forceinline__ uint32_t lds16(uint32_t a) { uint32_t v; asm volatile("ld.shared.u16 %0, [%1];" : "=r"(v) : "r"(a)); return v; }
__device__ __forceinline__ void cp16(uint32_t d, const void* p) {
    asm volatile("cp.async.cg.shared.global [%0], [%1], 16;" ::"r"(d), "l"(p) : "memory");
}
__device__ __forceinline__ uint32_t gtime() {
    uint32_t t;
    asm volatile("mov.u32 %0, %%globaltimer_lo;" : "=r"(t));
    return t;
}
__device__ __forceinline__ void mbar_init(uint32_t bar, int cnt) {
    asm volatile("mbarrier.init.shared.b64 [%0], %1;" ::"r"(bar), "r"(cnt) : "memory");
}
__device__ __forceinline__ uint4 lds128(uint32_t a) {
    uint4 v;
    asm volatile("ld.shared.v4.u32 {%0,%1,%2,%3}, [%4];" : "=r"(v.x), "=r"(v.y), "=r"(v.z), "=r"(v.w) : "r"(a));
    return v;
}
__device__ __forceinline__ void sts128(uint32_t a, uint32_t x, uint32_t y, uint32_t z, uint32_t w) {
    asm volatile("st.shared.v4.u32 [%0], {%1,%2,%3,%4};" ::"r"(a), "r"(x), "r"(y), "r"(z), "r"(w) : "memory");
}
__device__ __forceinline__ uint32_t pack_bf16(float lo, float hi) {
    uint32_t r;
    asm("cvt.rn.bf16x2.f32 %0, %1, %2;" : "=r"(r) : "f"(hi), "f"(lo));
    return r;
}
__device__ __forceinline__ uint32_t mul_lo(uint32_t v, uint32_t r) {
    __nv_bfloat162 a = *reinterpret_cast<__nv_bfloat162*>(&v), b = *reinterpret_cast<__nv_bfloat162*>(&r);
    __nv_bfloat162 c = __hmul2(a, __low2bfloat162(b));
    return *reinterpret_cast<uint32_t*>(&c);
}
__device__ __forceinline__ void wgmma_n80(float (&d)[40], const uint32_t (&a)[4], uint64_t desc, int scale_d) {
    asm volatile("{\n.reg .pred p;\nsetp.ne.b32 p, %45, 0;\n"
        "wgmma.mma_async.sync.aligned.m64n80k16.f32.bf16.bf16 "
        "{%0,%1,%2,%3,%4,%5,%6,%7,%8,%9,%10,%11,%12,%13,%14,%15,%16,%17,%18,%19,"
        "%20,%21,%22,%23,%24,%25,%26,%27,%28,%29,%30,%31,%32,%33,%34,%35,%36,%37,%38,%39}, "
        "{%40,%41,%42,%43}, %44, p, 1, 1, 0;\n}"
        : "+f"(d[0]), "+f"(d[1]), "+f"(d[2]), "+f"(d[3]), "+f"(d[4]), "+f"(d[5]), "+f"(d[6]), "+f"(d[7]),
          "+f"(d[8]), "+f"(d[9]), "+f"(d[10]), "+f"(d[11]), "+f"(d[12]), "+f"(d[13]), "+f"(d[14]), "+f"(d[15]),
          "+f"(d[16]), "+f"(d[17]), "+f"(d[18]), "+f"(d[19]), "+f"(d[20]), "+f"(d[21]), "+f"(d[22]), "+f"(d[23]),
          "+f"(d[24]), "+f"(d[25]), "+f"(d[26]), "+f"(d[27]), "+f"(d[28]), "+f"(d[29]), "+f"(d[30]), "+f"(d[31]),
          "+f"(d[32]), "+f"(d[33]), "+f"(d[34]), "+f"(d[35]), "+f"(d[36]), "+f"(d[37]), "+f"(d[38]), "+f"(d[39])
        : "r"(a[0]), "r"(a[1]), "r"(a[2]), "r"(a[3]), "l"(desc), "r"(scale_d));
}

__device__ __forceinline__ void producer_loop(const void* xl, const void* efl, const void* Y, uint32_t xd, uint32_t oef,
                                              uint32_t ysel, uint32_t ring, uint32_t rec, uint32_t rlast, uint32_t odd,
                                              uint32_t lag, uint32_t xh) {
    asm volatile(
        "{\n"
        ".reg .b32 w, em, ey, cu, d, t, u, n, sa, ph, rp, rend, rlast, dy, sv, lag, lv, w2, w3, w4;\n"
        ".reg .b16 tg;\n"
        ".reg .b64 pa, pb, pc, pd;\n"
        ".reg .pred lo, z, q, e, zb, fbk;\n"
        "redux.sync.or.b32 sa, %6, 0xffffffff;\n"
        "redux.sync.or.b32 rp, %7, 0xffffffff;\n"
        "redux.sync.or.b32 rlast, %8, 0xffffffff;\n"
        "redux.sync.or.b32 lag, %11, 0xffffffff;\n"
        "setp.eq.u32 fbk, %9, 0;\n"
        "add.u32 rend, sa, 44160;\n"
        "and.b32 t, %5, 1;\n"
        "setp.eq.u32 lo, t, 0;\n"
        "mov.u32 ph, 1;\n"
        "setp.ge.u32 q, %9, 4;\n"
        "@q bra.uni PODD_%=;\n"
        "add.u32 t, rp, %4;\n"
        "ld.shared.u32 em, [t+16];\n"
        "and.b32 t, em, 0xfffffff8;\n"
        "mad.wide.u32 pa, t, 4, %1;\n"
        "add.u32 d, sa, %3;\n"
        "@lo cp.async.cg.shared.global [d+2048], [pa], 16;\n"
        "cp.async.mbarrier.arrive.noinc.shared.b64 [sa+8704];\n"
        "add.u32 rp, rp, 52;\n"
        "add.u32 sa, sa, 8832;\n"
        "PODD_%=:\n"
        "add.u32 rp, rp, 52;\n"
        "add.u32 sa, sa, 8832;\n"
        "shr.u32 t, %4, 1;\n"
        "and.b32 t, t, 4;\n"
        "add.u32 t, t, rp;\n"
        "ld.shared.u32 w, [t];\n"
        "ld.shared.u32 w2, [t+8];\n"
        "add.u32 t, rp, %4;\n"
        "ld.shared.u32 em, [t+16];\n"
        "ld.shared.u32 ey, [t+-36];\n"
        "ld.shared.u32 cu, [rp+48];\n"
        "ld.volatile.shared.u32 sv, [lag];\n"
        "setp.eq.u32 e, sa, sa;\n"
        "setp.lt.u32 q, rp, rlast;\n"
        "@!q bra.uni PF_%=;\n"
        "PL_%=:\n"
        "add.u32 cu, cu, sv;\n"
        "mov.u32 u, %%clock;\n"
        "shl.b32 u, u, 14;\n"
        "sub.u32 u, u, cu;\n"
        "setp.ge.and.s32 q, u, 0, e;\n"
        "@q bra.uni PGO_%=;\n"
        "mov.u32 n, 0;\n"
        "PW1_%=:\n"
        "@e bra.uni PW2_%=;\n"
        "mbarrier.try_wait.parity.shared.b64 e, [sa+8712], ph;\n"
        "add.u32 n, n, 1;\n"
        "setp.lt.u32 q, n, 4194304;\n"
        "@q bra.uni PW1_%=;\n"
        "trap;\n"
        "PW2_%=:\n"
        "mov.u32 u, %%clock;\n"
        "shl.b32 u, u, 14;\n"
        "sub.u32 u, u, cu;\n"
        "setp.lt.s32 q, u, 0;\n"
        "@q bra.uni PW2_%=;\n"
        "PGO_%=:\n"
        "st.volatile.shared.u32 [lag+24], u;\n"
        "and.b32 t, em, 0xfffffff8;\n"
        "mad.wide.u32 pa, t, 4, %1;\n"
        "and.b32 t, w, 0xffff;\n"
        "mad.wide.u32 pc, t, 1024, %0;\n"
        "shr.u32 t, w, 16;\n"
        "mad.wide.u32 pd, t, 1024, %0;\n"
        "add.u32 d, sa, %3;\n"
        "@lo cp.async.cg.shared.global [d+2048], [pa], 16;\n"
        "xor.b32 t, ey, %5;\n"
        "and.b32 t, t, 7;\n"
        "setp.ne.u32 zb, t, 0;\n"
        "and.b32 t, ey, 0xfffffff8;\n"
        "cvt.u64.u32 pb, t;\n"
        "add.u64 pb, pb, %2;\n"
        "selp.u32 dy, 64, 8, lo;\n"
        "xor.b32 dy, dy, d;\n"
        "cp.async.ca.shared.global [dy+2048], [pb], 8, zb;\n"
        "add.u32 d, sa, %12;\n"
        "and.b32 t, w, 0xffff;\n"
        "setp.eq.u32 zb, t, 0xffff;\n"
        "cp.async.cg.shared.global [d+0], [pc+0], 16, zb;\n"
        "cp.async.cg.shared.global [d+256], [pc+256], 16, zb;\n"
        "cp.async.cg.shared.global [d+512], [pc+512], 16, zb;\n"
        "cp.async.cg.shared.global [d+768], [pc+768], 16, zb;\n"
        "setp.lt.s32 zb, w, 0;\n"
        "cp.async.cg.shared.global [d+1024], [pd+0], 16, zb;\n"
        "cp.async.cg.shared.global [d+1280], [pd+256], 16, zb;\n"
        "cp.async.cg.shared.global [d+1536], [pd+512], 16, zb;\n"
        "cp.async.cg.shared.global [d+1792], [pd+768], 16, zb;\n"
        "xor.b32 dy, d, 64;\n"
        "and.b32 t, w2, 0xffff;\n"
        "mad.wide.u32 pa, t, 1024, %0;\n"
        "and.b32 t, w2, 0xffff;\n"
        "setp.eq.u32 zb, t, 0xffff;\n"
        "cp.async.cg.shared.global [dy+4352], [pa+0], 16, zb;\n"
        "cp.async.cg.shared.global [dy+4608], [pa+256], 16, zb;\n"
        "cp.async.cg.shared.global [dy+4864], [pa+512], 16, zb;\n"
        "cp.async.cg.shared.global [dy+5120], [pa+768], 16, zb;\n"
        "shr.u32 t, w2, 16;\n"
        "mad.wide.u32 pb, t, 1024, %0;\n"
        "setp.lt.s32 zb, w2, 0;\n"
        "cp.async.cg.shared.global [dy+5376], [pb+0], 16, zb;\n"
        "cp.async.cg.shared.global [dy+5632], [pb+256], 16, zb;\n"
        "cp.async.cg.shared.global [dy+5888], [pb+512], 16, zb;\n"
        "cp.async.cg.shared.global [dy+6144], [pb+768], 16, zb;\n"
        "add.u32 rp, rp, 104;\n"
        "shr.u32 t, %4, 1;\n"
        "and.b32 t, t, 4;\n"
        "add.u32 t, t, rp;\n"
        "ld.shared.u32 w, [t];\n"
        "ld.shared.u32 w2, [t+8];\n"
        "add.u32 t, rp, %4;\n"
        "ld.shared.u32 em, [t+16];\n"
        "ld.shared.u32 ey, [t+-36];\n"
        "ld.shared.u32 cu, [rp+48];\n"
        "ld.volatile.shared.u32 sv, [lag];\n"
        "cp.async.mbarrier.arrive.noinc.shared.b64 [sa+8704];\n"
        "add.u32 sa, sa, 17664;\n"
        "sub.u32 t, sa, 44160;\n"
        "setp.ge.u32 q, sa, rend;\n"
        "selp.u32 sa, t, sa, q;\n"
        "selp.u32 t, 1, 0, q;\n"
        "xor.b32 ph, ph, t;\n"
        "mbarrier.try_wait.parity.shared.b64 e, [sa+8712], ph;\n"
        "@!fbk bra.uni PC_%=;\n"
        "ld.volatile.shared.u32 u, [lag+24];\n"
        "shr.s32 u, u, 16;\n"
        "ld.volatile.shared.u64 pa, [lag+16];\n"
        "elect.sync _|z, 0xffffffff;\n"
        "@z st.relaxed.gpu.global.u32 [pa], u;\n"
        "@z cp.async.cg.shared.global [lag], [pa+16896], 16;\n"
        "PC_%=:\n"
        "setp.lt.u32 q, rp, rlast;\n"
        "@q bra.uni PL_%=;\n"
        "PF_%=:\n"
        "setp.ne.u32 q, rp, rlast;\n"
        "@q bra.uni PX_%=;\n"
        "mov.u32 n, 0;\n"
        "PE1_%=:\n"
        "@e bra.uni PE2_%=;\n"
        "mbarrier.try_wait.parity.shared.b64 e, [sa+8712], ph;\n"
        "add.u32 n, n, 1;\n"
        "setp.lt.u32 q, n, 4194304;\n"
        "@q bra.uni PE1_%=;\n"
        "trap;\n"
        "PE2_%=:\n"
        "cp.async.mbarrier.arrive.noinc.shared.b64 [sa+8704];\n"
        "PX_%=:\n"
        "}\n"
        ::"l"(xl), "l"(efl), "l"(Y), "r"(xd), "r"(oef), "r"(ysel), "r"(ring), "r"(rec), "r"(rlast), "r"(odd),
          "n"(0), "r"(lag), "r"(xh) : "memory");
}

__device__ __forceinline__ void consumer_loop(float (&acc)[5][4][2][4], const uint32_t (&wf)[4][4], const uint32_t (&cgf)[4],
                                              uint32_t xoff, uint32_t& ring, uint32_t moff, uint32_t rec) {
    asm volatile(
        "{\n"
        ".reg .b32 x<16>, a<4>, b<4>, r<4>, m<4>, rl, rh, tag, la, lb, sa, last, ph, tq, xa, ma, n, ring, sn, ln, yb, zz, k<4>, tp, s<4>;\n"
        ".reg .b16 lo, hi;\n"
        ".reg .f32 p<16>, d<4>, t0, t1, fz;\n"
        ".reg .pred q, w, el, c<5>;\n"
        "TA_%=: .branchtargets A0_%=, A1_%=, A2_%=, A3_%=, A4_%=, EXIT_%=;\n"
        "TB_%=: .branchtargets B0_%=, B1_%=, B2_%=, B3_%=, B4_%=, SPIN_%=;\n"
        "mov.f32 fz, 0f00000000;\n"
        "redux.sync.or.b32 ring, %160, 0xffffffff;\n"
        "mov.u32 sa, ring;\n"
        "add.u32 last, ring, 35328;\n"
        "mov.u32 ph, 0;\n"
        "redux.sync.xor.b32 zz, %160, 0xffffffff;\n"
        "redux.sync.or.b32 tp, %183, 0xffffffff;\n"
        "elect.sync _|el, 0xffffffff;\n"
        "mov.u32 k0, sa;\n"
        "mov.u32 k1, sa;\n"
        "mov.u32 k2, sa;\n"
        "mov.u32 k3, sa;\n"
        "mov.b32 x0, 0;\n"
        "mov.b32 x1, 0;\n"
        "mov.b32 x2, 0;\n"
        "mov.b32 x3, 0;\n"
        "mov.b32 x4, 0;\n"
        "mov.b32 x5, 0;\n"
        "mov.b32 x6, 0;\n"
        "mov.b32 x7, 0;\n"
        "mov.b32 x8, 0;\n"
        "mov.b32 x9, 0;\n"
        "mov.b32 x10, 0;\n"
        "mov.b32 x11, 0;\n"
        "mov.b32 x12, 0;\n"
        "mov.b32 x13, 0;\n"
        "mov.b32 x14, 0;\n"
        "mov.b32 x15, 0;\n"
        "mov.b32 b0, 0;\n"
        "mov.b32 r0, 0;\n"
        "mov.b32 b1, 0;\n"
        "mov.b32 r1, 0;\n"
        "mov.b32 b2, 0;\n"
        "mov.b32 r2, 0;\n"
        "mov.b32 b3, 0;\n"
        "mov.b32 r3, 0;\n"
        "mov.u32 lb, 0;\n"
        "mov.u32 n, 0;\n"
        "W0_%=:\n"
        "mbarrier.try_wait.parity.shared.b64 w, [sa+8704], 0;\n"
        "@w bra.uni W0D_%=;\n"
        "add.u32 n, n, 1;\n"
        "setp.lt.u32 q, n, 4194304;\n"
        "@q bra.uni W0_%=;\n"
        "trap;\n"
        "W0D_%=:\n"
        "add.u32 ma, sa, %182;\n"
        "ldmatrix.sync.aligned.m8n8.x4.shared.b16 {m0,m1,m2,m3}, [ma];\n"
        "ld.shared.u16 tag, [tp+48];\n"
        "add.u32 tp, tp, 52;\n"
        "add.u32 sn, sa, 8832;\n"
        "setp.eq.u32 q, sa, last;\n"
        "selp.u32 sn, ring, sn, q;\n"
        "selp.u32 tq, 1, 0, q;\n"
        "xor.b32 ph, ph, tq;\n"
        "mbarrier.test_wait.parity.shared.b64 w, [sn+8704], ph;\n"
        "mma.sync.aligned.m16n8k16.row.col.f32.bf16.bf16.f32 {p0,p1,p2,p3}, {%161,%162,%163,%164}, {m2,m3}, {fz,fz,fz,fz};\n"
        "mma.sync.aligned.m16n8k16.row.col.f32.bf16.bf16.f32 {p4,p5,p6,p7}, {%165,%166,%167,%168}, {m2,m3}, {fz,fz,fz,fz};\n"
        "mma.sync.aligned.m16n8k16.row.col.f32.bf16.bf16.f32 {p8,p9,p10,p11}, {%169,%170,%171,%172}, {m2,m3}, {fz,fz,fz,fz};\n"
        "mma.sync.aligned.m16n8k16.row.col.f32.bf16.bf16.f32 {p12,p13,p14,p15}, {%173,%174,%175,%176}, {m2,m3}, {fz,fz,fz,fz};\n"
        "@el mbarrier.arrive.shared.b64 _, [k0+8712];\n"
        "redux.sync.or.b32 ln, tag, 0xffffffff;\n"
        "mov.u32 sa, sn;\n"
        "add.u32 k0, sn, zz;\n"
        "SPIN_%=:\n"
        "mov.u32 n, 0;\n"
        "SP1_%=:\n"
        "mbarrier.try_wait.parity.shared.b64 w, [sa+8704], ph;\n"
        "@w bra.uni SP2_%=;\n"
        "add.u32 n, n, 1;\n"
        "setp.lt.u32 q, n, 4194304;\n"
        "@q bra.uni SP1_%=;\n"
        "trap;\n"
        "SP2_%=:\n"
        "brx.idx.uni lb, TB_%=;\n"
        "A0_%=:\n"
        "add.u32 xa, sa, %181;\n"
        "add.u32 ma, sa, %182;\n"
        "ldmatrix.sync.aligned.m8n8.x4.shared.b16 {m0,m1,m2,m3}, [ma];\n"
        "ld.shared.u16 tag, [tp+48];\n"
        "add.u32 tp, tp, 52;\n"
        "add.u32 sn, sa, 8832;\n"
        "setp.eq.u32 q, sa, last;\n"
        "selp.u32 sn, ring, sn, q;\n"
        "selp.u32 tq, 1, 0, q;\n"
        "xor.b32 ph, ph, tq;\n"
        "mbarrier.test_wait.parity.shared.b64 w, [sn+8704], ph;\n"
        "mma.sync.aligned.m16n8k16.row.col.f32.bf16.bf16.f32 {%0,%1,%2,%3}, {a0,a1,a2,a3}, {x0,x1}, {%0,%1,%2,%3};\n"
        "mma.sync.aligned.m16n8k16.row.col.f32.bf16.bf16.f32 {%4,%5,%6,%7}, {a0,a1,a2,a3}, {x2,x3}, {%4,%5,%6,%7};\n"
        "ld.shared.v4.u32 {x0,x1,x2,x3}, [xa+1024];\n"
        "tanh.approx.f32 t0, p1;\n"
        "tanh.approx.f32 t1, p3;\n"
        "fma.rn.f32 t0, p1, t0, p1;\n"
        "fma.rn.f32 t1, p3, t1, p3;\n"
        "cvt.rn.bf16x2.f32 r0, t1, t0;\n"
        "mma.sync.aligned.m16n8k16.row.col.f32.bf16.bf16.f32 {p0,p1,p2,p3}, {%161,%162,%163,%164}, {m2,m3}, {fz,fz,fz,fz};\n"
        "mma.sync.aligned.m16n8k16.row.col.f32.bf16.bf16.f32 {%8,%9,%10,%11}, {a0,a1,a2,a3}, {x4,x5}, {%8,%9,%10,%11};\n"
        "mma.sync.aligned.m16n8k16.row.col.f32.bf16.bf16.f32 {%12,%13,%14,%15}, {a0,a1,a2,a3}, {x6,x7}, {%12,%13,%14,%15};\n"
        "ld.shared.v4.u32 {x4,x5,x6,x7}, [xa+1152];\n"
        "mma.sync.aligned.m16n8k8.row.col.f32.bf16.bf16.f32 {d0,d1,d2,d3}, {%177,%178}, {m1}, {fz,fz,fz,fz};\n"
        "cvt.rn.bf16x2.f32 b0, d2, d0;\n"
        "cvt.rn.bf16x2.f32 b1, d3, d1;\n"
        "tanh.approx.f32 t0, p5;\n"
        "tanh.approx.f32 t1, p7;\n"
        "fma.rn.f32 t0, p5, t0, p5;\n"
        "fma.rn.f32 t1, p7, t1, p7;\n"
        "cvt.rn.bf16x2.f32 r1, t1, t0;\n"
        "mma.sync.aligned.m16n8k16.row.col.f32.bf16.bf16.f32 {p4,p5,p6,p7}, {%165,%166,%167,%168}, {m2,m3}, {fz,fz,fz,fz};\n"
        "mov.b32 {lo,hi}, r2;\n"
        "mov.b32 rl, {lo,lo};\n"
        "mov.b32 rh, {hi,hi};\n"
        "mul.bf16x2 x8, x8, rl;\n"
        "mul.bf16x2 x9, x9, rl;\n"
        "mul.bf16x2 x10, x10, rh;\n"
        "mul.bf16x2 x11, x11, rh;\n"
        "mma.sync.aligned.m16n8k16.row.col.f32.bf16.bf16.f32 {%16,%17,%18,%19}, {a0,a1,a2,a3}, {x8,x9}, {%16,%17,%18,%19};\n"
        "mma.sync.aligned.m16n8k16.row.col.f32.bf16.bf16.f32 {%20,%21,%22,%23}, {a0,a1,a2,a3}, {x10,x11}, {%20,%21,%22,%23};\n"
        "ld.shared.v4.u32 {x8,x9,x10,x11}, [xa+1280];\n"
        "mma.sync.aligned.m16n8k8.row.col.f32.bf16.bf16.f32 {d0,d1,d2,d3}, {%179,%180}, {m1}, {fz,fz,fz,fz};\n"
        "cvt.rn.bf16x2.f32 b2, d2, d0;\n"
        "cvt.rn.bf16x2.f32 b3, d3, d1;\n"
        "tanh.approx.f32 t0, p9;\n"
        "tanh.approx.f32 t1, p11;\n"
        "fma.rn.f32 t0, p9, t0, p9;\n"
        "fma.rn.f32 t1, p11, t1, p11;\n"
        "cvt.rn.bf16x2.f32 r2, t1, t0;\n"
        "mma.sync.aligned.m16n8k16.row.col.f32.bf16.bf16.f32 {p8,p9,p10,p11}, {%169,%170,%171,%172}, {m2,m3}, {fz,fz,fz,fz};\n"
        "mov.b32 {lo,hi}, r3;\n"
        "mov.b32 rl, {lo,lo};\n"
        "mov.b32 rh, {hi,hi};\n"
        "mul.bf16x2 x12, x12, rl;\n"
        "mul.bf16x2 x13, x13, rl;\n"
        "mul.bf16x2 x14, x14, rh;\n"
        "mul.bf16x2 x15, x15, rh;\n"
        "mma.sync.aligned.m16n8k16.row.col.f32.bf16.bf16.f32 {%24,%25,%26,%27}, {a0,a1,a2,a3}, {x12,x13}, {%24,%25,%26,%27};\n"
        "mma.sync.aligned.m16n8k16.row.col.f32.bf16.bf16.f32 {%28,%29,%30,%31}, {a0,a1,a2,a3}, {x14,x15}, {%28,%29,%30,%31};\n"
        "ld.shared.v4.u32 {x12,x13,x14,x15}, [xa+1408];\n"
        "@el mbarrier.arrive.shared.b64 _, [k0+8712];\n"
        "redux.sync.or.b32 ln, tag, 0xffffffff;\n"
        "mov.u32 sa, sn;\n"
        "add.u32 k0, sn, zz;\n"
        "tanh.approx.f32 t0, p13;\n"
        "tanh.approx.f32 t1, p15;\n"
        "fma.rn.f32 t0, p13, t0, p13;\n"
        "fma.rn.f32 t1, p15, t1, p15;\n"
        "cvt.rn.bf16x2.f32 r3, t1, t0;\n"
        "mma.sync.aligned.m16n8k16.row.col.f32.bf16.bf16.f32 {p12,p13,p14,p15}, {%173,%174,%175,%176}, {m2,m3}, {fz,fz,fz,fz};\n"
        "selp.u32 tq, lb, 5, w;\n"
        "brx.idx.uni tq, TB_%=;\n"
        "A1_%=:\n"
        "add.u32 xa, sa, %181;\n"
        "add.u32 ma, sa, %182;\n"
        "ldmatrix.sync.aligned.m8n8.x4.shared.b16 {m0,m1,m2,m3}, [ma];\n"
        "ld.shared.u16 tag, [tp+48];\n"
        "add.u32 tp, tp, 52;\n"
        "add.u32 sn, sa, 8832;\n"
        "setp.eq.u32 q, sa, last;\n"
        "selp.u32 sn, ring, sn, q;\n"
        "selp.u32 tq, 1, 0, q;\n"
        "xor.b32 ph, ph, tq;\n"
        "mbarrier.test_wait.parity.shared.b64 w, [sn+8704], ph;\n"
        "mma.sync.aligned.m16n8k16.row.col.f32.bf16.bf16.f32 {%32,%33,%34,%35}, {a0,a1,a2,a3}, {x0,x1}, {%32,%33,%34,%35};\n"
        "mma.sync.aligned.m16n8k16.row.col.f32.bf16.bf16.f32 {%36,%37,%38,%39}, {a0,a1,a2,a3}, {x2,x3}, {%36,%37,%38,%39};\n"
        "ld.shared.v4.u32 {x0,x1,x2,x3}, [xa+1024];\n"
        "tanh.approx.f32 t0, p1;\n"
        "tanh.approx.f32 t1, p3;\n"
        "fma.rn.f32 t0, p1, t0, p1;\n"
        "fma.rn.f32 t1, p3, t1, p3;\n"
        "cvt.rn.bf16x2.f32 r0, t1, t0;\n"
        "mma.sync.aligned.m16n8k16.row.col.f32.bf16.bf16.f32 {p0,p1,p2,p3}, {%161,%162,%163,%164}, {m2,m3}, {fz,fz,fz,fz};\n"
        "mma.sync.aligned.m16n8k16.row.col.f32.bf16.bf16.f32 {%40,%41,%42,%43}, {a0,a1,a2,a3}, {x4,x5}, {%40,%41,%42,%43};\n"
        "mma.sync.aligned.m16n8k16.row.col.f32.bf16.bf16.f32 {%44,%45,%46,%47}, {a0,a1,a2,a3}, {x6,x7}, {%44,%45,%46,%47};\n"
        "ld.shared.v4.u32 {x4,x5,x6,x7}, [xa+1152];\n"
        "mma.sync.aligned.m16n8k8.row.col.f32.bf16.bf16.f32 {d0,d1,d2,d3}, {%177,%178}, {m1}, {fz,fz,fz,fz};\n"
        "cvt.rn.bf16x2.f32 b0, d2, d0;\n"
        "cvt.rn.bf16x2.f32 b1, d3, d1;\n"
        "tanh.approx.f32 t0, p5;\n"
        "tanh.approx.f32 t1, p7;\n"
        "fma.rn.f32 t0, p5, t0, p5;\n"
        "fma.rn.f32 t1, p7, t1, p7;\n"
        "cvt.rn.bf16x2.f32 r1, t1, t0;\n"
        "mma.sync.aligned.m16n8k16.row.col.f32.bf16.bf16.f32 {p4,p5,p6,p7}, {%165,%166,%167,%168}, {m2,m3}, {fz,fz,fz,fz};\n"
        "mov.b32 {lo,hi}, r2;\n"
        "mov.b32 rl, {lo,lo};\n"
        "mov.b32 rh, {hi,hi};\n"
        "mul.bf16x2 x8, x8, rl;\n"
        "mul.bf16x2 x9, x9, rl;\n"
        "mul.bf16x2 x10, x10, rh;\n"
        "mul.bf16x2 x11, x11, rh;\n"
        "mma.sync.aligned.m16n8k16.row.col.f32.bf16.bf16.f32 {%48,%49,%50,%51}, {a0,a1,a2,a3}, {x8,x9}, {%48,%49,%50,%51};\n"
        "mma.sync.aligned.m16n8k16.row.col.f32.bf16.bf16.f32 {%52,%53,%54,%55}, {a0,a1,a2,a3}, {x10,x11}, {%52,%53,%54,%55};\n"
        "ld.shared.v4.u32 {x8,x9,x10,x11}, [xa+1280];\n"
        "mma.sync.aligned.m16n8k8.row.col.f32.bf16.bf16.f32 {d0,d1,d2,d3}, {%179,%180}, {m1}, {fz,fz,fz,fz};\n"
        "cvt.rn.bf16x2.f32 b2, d2, d0;\n"
        "cvt.rn.bf16x2.f32 b3, d3, d1;\n"
        "tanh.approx.f32 t0, p9;\n"
        "tanh.approx.f32 t1, p11;\n"
        "fma.rn.f32 t0, p9, t0, p9;\n"
        "fma.rn.f32 t1, p11, t1, p11;\n"
        "cvt.rn.bf16x2.f32 r2, t1, t0;\n"
        "mma.sync.aligned.m16n8k16.row.col.f32.bf16.bf16.f32 {p8,p9,p10,p11}, {%169,%170,%171,%172}, {m2,m3}, {fz,fz,fz,fz};\n"
        "mov.b32 {lo,hi}, r3;\n"
        "mov.b32 rl, {lo,lo};\n"
        "mov.b32 rh, {hi,hi};\n"
        "mul.bf16x2 x12, x12, rl;\n"
        "mul.bf16x2 x13, x13, rl;\n"
        "mul.bf16x2 x14, x14, rh;\n"
        "mul.bf16x2 x15, x15, rh;\n"
        "mma.sync.aligned.m16n8k16.row.col.f32.bf16.bf16.f32 {%56,%57,%58,%59}, {a0,a1,a2,a3}, {x12,x13}, {%56,%57,%58,%59};\n"
        "mma.sync.aligned.m16n8k16.row.col.f32.bf16.bf16.f32 {%60,%61,%62,%63}, {a0,a1,a2,a3}, {x14,x15}, {%60,%61,%62,%63};\n"
        "ld.shared.v4.u32 {x12,x13,x14,x15}, [xa+1408];\n"
        "@el mbarrier.arrive.shared.b64 _, [k0+8712];\n"
        "redux.sync.or.b32 ln, tag, 0xffffffff;\n"
        "mov.u32 sa, sn;\n"
        "add.u32 k0, sn, zz;\n"
        "tanh.approx.f32 t0, p13;\n"
        "tanh.approx.f32 t1, p15;\n"
        "fma.rn.f32 t0, p13, t0, p13;\n"
        "fma.rn.f32 t1, p15, t1, p15;\n"
        "cvt.rn.bf16x2.f32 r3, t1, t0;\n"
        "mma.sync.aligned.m16n8k16.row.col.f32.bf16.bf16.f32 {p12,p13,p14,p15}, {%173,%174,%175,%176}, {m2,m3}, {fz,fz,fz,fz};\n"
        "selp.u32 tq, lb, 5, w;\n"
        "brx.idx.uni tq, TB_%=;\n"
        "A2_%=:\n"
        "add.u32 xa, sa, %181;\n"
        "add.u32 ma, sa, %182;\n"
        "ldmatrix.sync.aligned.m8n8.x4.shared.b16 {m0,m1,m2,m3}, [ma];\n"
        "ld.shared.u16 tag, [tp+48];\n"
        "add.u32 tp, tp, 52;\n"
        "add.u32 sn, sa, 8832;\n"
        "setp.eq.u32 q, sa, last;\n"
        "selp.u32 sn, ring, sn, q;\n"
        "selp.u32 tq, 1, 0, q;\n"
        "xor.b32 ph, ph, tq;\n"
        "mbarrier.test_wait.parity.shared.b64 w, [sn+8704], ph;\n"
        "mma.sync.aligned.m16n8k16.row.col.f32.bf16.bf16.f32 {%64,%65,%66,%67}, {a0,a1,a2,a3}, {x0,x1}, {%64,%65,%66,%67};\n"
        "mma.sync.aligned.m16n8k16.row.col.f32.bf16.bf16.f32 {%68,%69,%70,%71}, {a0,a1,a2,a3}, {x2,x3}, {%68,%69,%70,%71};\n"
        "ld.shared.v4.u32 {x0,x1,x2,x3}, [xa+1024];\n"
        "tanh.approx.f32 t0, p1;\n"
        "tanh.approx.f32 t1, p3;\n"
        "fma.rn.f32 t0, p1, t0, p1;\n"
        "fma.rn.f32 t1, p3, t1, p3;\n"
        "cvt.rn.bf16x2.f32 r0, t1, t0;\n"
        "mma.sync.aligned.m16n8k16.row.col.f32.bf16.bf16.f32 {p0,p1,p2,p3}, {%161,%162,%163,%164}, {m2,m3}, {fz,fz,fz,fz};\n"
        "mma.sync.aligned.m16n8k16.row.col.f32.bf16.bf16.f32 {%72,%73,%74,%75}, {a0,a1,a2,a3}, {x4,x5}, {%72,%73,%74,%75};\n"
        "mma.sync.aligned.m16n8k16.row.col.f32.bf16.bf16.f32 {%76,%77,%78,%79}, {a0,a1,a2,a3}, {x6,x7}, {%76,%77,%78,%79};\n"
        "ld.shared.v4.u32 {x4,x5,x6,x7}, [xa+1152];\n"
        "mma.sync.aligned.m16n8k8.row.col.f32.bf16.bf16.f32 {d0,d1,d2,d3}, {%177,%178}, {m1}, {fz,fz,fz,fz};\n"
        "cvt.rn.bf16x2.f32 b0, d2, d0;\n"
        "cvt.rn.bf16x2.f32 b1, d3, d1;\n"
        "tanh.approx.f32 t0, p5;\n"
        "tanh.approx.f32 t1, p7;\n"
        "fma.rn.f32 t0, p5, t0, p5;\n"
        "fma.rn.f32 t1, p7, t1, p7;\n"
        "cvt.rn.bf16x2.f32 r1, t1, t0;\n"
        "mma.sync.aligned.m16n8k16.row.col.f32.bf16.bf16.f32 {p4,p5,p6,p7}, {%165,%166,%167,%168}, {m2,m3}, {fz,fz,fz,fz};\n"
        "mov.b32 {lo,hi}, r2;\n"
        "mov.b32 rl, {lo,lo};\n"
        "mov.b32 rh, {hi,hi};\n"
        "mul.bf16x2 x8, x8, rl;\n"
        "mul.bf16x2 x9, x9, rl;\n"
        "mul.bf16x2 x10, x10, rh;\n"
        "mul.bf16x2 x11, x11, rh;\n"
        "mma.sync.aligned.m16n8k16.row.col.f32.bf16.bf16.f32 {%80,%81,%82,%83}, {a0,a1,a2,a3}, {x8,x9}, {%80,%81,%82,%83};\n"
        "mma.sync.aligned.m16n8k16.row.col.f32.bf16.bf16.f32 {%84,%85,%86,%87}, {a0,a1,a2,a3}, {x10,x11}, {%84,%85,%86,%87};\n"
        "ld.shared.v4.u32 {x8,x9,x10,x11}, [xa+1280];\n"
        "mma.sync.aligned.m16n8k8.row.col.f32.bf16.bf16.f32 {d0,d1,d2,d3}, {%179,%180}, {m1}, {fz,fz,fz,fz};\n"
        "cvt.rn.bf16x2.f32 b2, d2, d0;\n"
        "cvt.rn.bf16x2.f32 b3, d3, d1;\n"
        "tanh.approx.f32 t0, p9;\n"
        "tanh.approx.f32 t1, p11;\n"
        "fma.rn.f32 t0, p9, t0, p9;\n"
        "fma.rn.f32 t1, p11, t1, p11;\n"
        "cvt.rn.bf16x2.f32 r2, t1, t0;\n"
        "mma.sync.aligned.m16n8k16.row.col.f32.bf16.bf16.f32 {p8,p9,p10,p11}, {%169,%170,%171,%172}, {m2,m3}, {fz,fz,fz,fz};\n"
        "mov.b32 {lo,hi}, r3;\n"
        "mov.b32 rl, {lo,lo};\n"
        "mov.b32 rh, {hi,hi};\n"
        "mul.bf16x2 x12, x12, rl;\n"
        "mul.bf16x2 x13, x13, rl;\n"
        "mul.bf16x2 x14, x14, rh;\n"
        "mul.bf16x2 x15, x15, rh;\n"
        "mma.sync.aligned.m16n8k16.row.col.f32.bf16.bf16.f32 {%88,%89,%90,%91}, {a0,a1,a2,a3}, {x12,x13}, {%88,%89,%90,%91};\n"
        "mma.sync.aligned.m16n8k16.row.col.f32.bf16.bf16.f32 {%92,%93,%94,%95}, {a0,a1,a2,a3}, {x14,x15}, {%92,%93,%94,%95};\n"
        "ld.shared.v4.u32 {x12,x13,x14,x15}, [xa+1408];\n"
        "@el mbarrier.arrive.shared.b64 _, [k0+8712];\n"
        "redux.sync.or.b32 ln, tag, 0xffffffff;\n"
        "mov.u32 sa, sn;\n"
        "add.u32 k0, sn, zz;\n"
        "tanh.approx.f32 t0, p13;\n"
        "tanh.approx.f32 t1, p15;\n"
        "fma.rn.f32 t0, p13, t0, p13;\n"
        "fma.rn.f32 t1, p15, t1, p15;\n"
        "cvt.rn.bf16x2.f32 r3, t1, t0;\n"
        "mma.sync.aligned.m16n8k16.row.col.f32.bf16.bf16.f32 {p12,p13,p14,p15}, {%173,%174,%175,%176}, {m2,m3}, {fz,fz,fz,fz};\n"
        "selp.u32 tq, lb, 5, w;\n"
        "brx.idx.uni tq, TB_%=;\n"
        "A3_%=:\n"
        "add.u32 xa, sa, %181;\n"
        "add.u32 ma, sa, %182;\n"
        "ldmatrix.sync.aligned.m8n8.x4.shared.b16 {m0,m1,m2,m3}, [ma];\n"
        "ld.shared.u16 tag, [tp+48];\n"
        "add.u32 tp, tp, 52;\n"
        "add.u32 sn, sa, 8832;\n"
        "setp.eq.u32 q, sa, last;\n"
        "selp.u32 sn, ring, sn, q;\n"
        "selp.u32 tq, 1, 0, q;\n"
        "xor.b32 ph, ph, tq;\n"
        "mbarrier.test_wait.parity.shared.b64 w, [sn+8704], ph;\n"
        "mma.sync.aligned.m16n8k16.row.col.f32.bf16.bf16.f32 {%96,%97,%98,%99}, {a0,a1,a2,a3}, {x0,x1}, {%96,%97,%98,%99};\n"
        "mma.sync.aligned.m16n8k16.row.col.f32.bf16.bf16.f32 {%100,%101,%102,%103}, {a0,a1,a2,a3}, {x2,x3}, {%100,%101,%102,%103};\n"
        "ld.shared.v4.u32 {x0,x1,x2,x3}, [xa+1024];\n"
        "tanh.approx.f32 t0, p1;\n"
        "tanh.approx.f32 t1, p3;\n"
        "fma.rn.f32 t0, p1, t0, p1;\n"
        "fma.rn.f32 t1, p3, t1, p3;\n"
        "cvt.rn.bf16x2.f32 r0, t1, t0;\n"
        "mma.sync.aligned.m16n8k16.row.col.f32.bf16.bf16.f32 {p0,p1,p2,p3}, {%161,%162,%163,%164}, {m2,m3}, {fz,fz,fz,fz};\n"
        "mma.sync.aligned.m16n8k16.row.col.f32.bf16.bf16.f32 {%104,%105,%106,%107}, {a0,a1,a2,a3}, {x4,x5}, {%104,%105,%106,%107};\n"
        "mma.sync.aligned.m16n8k16.row.col.f32.bf16.bf16.f32 {%108,%109,%110,%111}, {a0,a1,a2,a3}, {x6,x7}, {%108,%109,%110,%111};\n"
        "ld.shared.v4.u32 {x4,x5,x6,x7}, [xa+1152];\n"
        "mma.sync.aligned.m16n8k8.row.col.f32.bf16.bf16.f32 {d0,d1,d2,d3}, {%177,%178}, {m1}, {fz,fz,fz,fz};\n"
        "cvt.rn.bf16x2.f32 b0, d2, d0;\n"
        "cvt.rn.bf16x2.f32 b1, d3, d1;\n"
        "tanh.approx.f32 t0, p5;\n"
        "tanh.approx.f32 t1, p7;\n"
        "fma.rn.f32 t0, p5, t0, p5;\n"
        "fma.rn.f32 t1, p7, t1, p7;\n"
        "cvt.rn.bf16x2.f32 r1, t1, t0;\n"
        "mma.sync.aligned.m16n8k16.row.col.f32.bf16.bf16.f32 {p4,p5,p6,p7}, {%165,%166,%167,%168}, {m2,m3}, {fz,fz,fz,fz};\n"
        "mov.b32 {lo,hi}, r2;\n"
        "mov.b32 rl, {lo,lo};\n"
        "mov.b32 rh, {hi,hi};\n"
        "mul.bf16x2 x8, x8, rl;\n"
        "mul.bf16x2 x9, x9, rl;\n"
        "mul.bf16x2 x10, x10, rh;\n"
        "mul.bf16x2 x11, x11, rh;\n"
        "mma.sync.aligned.m16n8k16.row.col.f32.bf16.bf16.f32 {%112,%113,%114,%115}, {a0,a1,a2,a3}, {x8,x9}, {%112,%113,%114,%115};\n"
        "mma.sync.aligned.m16n8k16.row.col.f32.bf16.bf16.f32 {%116,%117,%118,%119}, {a0,a1,a2,a3}, {x10,x11}, {%116,%117,%118,%119};\n"
        "ld.shared.v4.u32 {x8,x9,x10,x11}, [xa+1280];\n"
        "mma.sync.aligned.m16n8k8.row.col.f32.bf16.bf16.f32 {d0,d1,d2,d3}, {%179,%180}, {m1}, {fz,fz,fz,fz};\n"
        "cvt.rn.bf16x2.f32 b2, d2, d0;\n"
        "cvt.rn.bf16x2.f32 b3, d3, d1;\n"
        "tanh.approx.f32 t0, p9;\n"
        "tanh.approx.f32 t1, p11;\n"
        "fma.rn.f32 t0, p9, t0, p9;\n"
        "fma.rn.f32 t1, p11, t1, p11;\n"
        "cvt.rn.bf16x2.f32 r2, t1, t0;\n"
        "mma.sync.aligned.m16n8k16.row.col.f32.bf16.bf16.f32 {p8,p9,p10,p11}, {%169,%170,%171,%172}, {m2,m3}, {fz,fz,fz,fz};\n"
        "mov.b32 {lo,hi}, r3;\n"
        "mov.b32 rl, {lo,lo};\n"
        "mov.b32 rh, {hi,hi};\n"
        "mul.bf16x2 x12, x12, rl;\n"
        "mul.bf16x2 x13, x13, rl;\n"
        "mul.bf16x2 x14, x14, rh;\n"
        "mul.bf16x2 x15, x15, rh;\n"
        "mma.sync.aligned.m16n8k16.row.col.f32.bf16.bf16.f32 {%120,%121,%122,%123}, {a0,a1,a2,a3}, {x12,x13}, {%120,%121,%122,%123};\n"
        "mma.sync.aligned.m16n8k16.row.col.f32.bf16.bf16.f32 {%124,%125,%126,%127}, {a0,a1,a2,a3}, {x14,x15}, {%124,%125,%126,%127};\n"
        "ld.shared.v4.u32 {x12,x13,x14,x15}, [xa+1408];\n"
        "@el mbarrier.arrive.shared.b64 _, [k0+8712];\n"
        "redux.sync.or.b32 ln, tag, 0xffffffff;\n"
        "mov.u32 sa, sn;\n"
        "add.u32 k0, sn, zz;\n"
        "tanh.approx.f32 t0, p13;\n"
        "tanh.approx.f32 t1, p15;\n"
        "fma.rn.f32 t0, p13, t0, p13;\n"
        "fma.rn.f32 t1, p15, t1, p15;\n"
        "cvt.rn.bf16x2.f32 r3, t1, t0;\n"
        "mma.sync.aligned.m16n8k16.row.col.f32.bf16.bf16.f32 {p12,p13,p14,p15}, {%173,%174,%175,%176}, {m2,m3}, {fz,fz,fz,fz};\n"
        "selp.u32 tq, lb, 5, w;\n"
        "brx.idx.uni tq, TB_%=;\n"
        "A4_%=:\n"
        "add.u32 xa, sa, %181;\n"
        "add.u32 ma, sa, %182;\n"
        "ldmatrix.sync.aligned.m8n8.x4.shared.b16 {m0,m1,m2,m3}, [ma];\n"
        "ld.shared.u16 tag, [tp+48];\n"
        "add.u32 tp, tp, 52;\n"
        "add.u32 sn, sa, 8832;\n"
        "setp.eq.u32 q, sa, last;\n"
        "selp.u32 sn, ring, sn, q;\n"
        "selp.u32 tq, 1, 0, q;\n"
        "xor.b32 ph, ph, tq;\n"
        "mbarrier.test_wait.parity.shared.b64 w, [sn+8704], ph;\n"
        "mma.sync.aligned.m16n8k16.row.col.f32.bf16.bf16.f32 {%128,%129,%130,%131}, {a0,a1,a2,a3}, {x0,x1}, {%128,%129,%130,%131};\n"
        "mma.sync.aligned.m16n8k16.row.col.f32.bf16.bf16.f32 {%132,%133,%134,%135}, {a0,a1,a2,a3}, {x2,x3}, {%132,%133,%134,%135};\n"
        "ld.shared.v4.u32 {x0,x1,x2,x3}, [xa+1024];\n"
        "tanh.approx.f32 t0, p1;\n"
        "tanh.approx.f32 t1, p3;\n"
        "fma.rn.f32 t0, p1, t0, p1;\n"
        "fma.rn.f32 t1, p3, t1, p3;\n"
        "cvt.rn.bf16x2.f32 r0, t1, t0;\n"
        "mma.sync.aligned.m16n8k16.row.col.f32.bf16.bf16.f32 {p0,p1,p2,p3}, {%161,%162,%163,%164}, {m2,m3}, {fz,fz,fz,fz};\n"
        "mma.sync.aligned.m16n8k16.row.col.f32.bf16.bf16.f32 {%136,%137,%138,%139}, {a0,a1,a2,a3}, {x4,x5}, {%136,%137,%138,%139};\n"
        "mma.sync.aligned.m16n8k16.row.col.f32.bf16.bf16.f32 {%140,%141,%142,%143}, {a0,a1,a2,a3}, {x6,x7}, {%140,%141,%142,%143};\n"
        "ld.shared.v4.u32 {x4,x5,x6,x7}, [xa+1152];\n"
        "mma.sync.aligned.m16n8k8.row.col.f32.bf16.bf16.f32 {d0,d1,d2,d3}, {%177,%178}, {m1}, {fz,fz,fz,fz};\n"
        "cvt.rn.bf16x2.f32 b0, d2, d0;\n"
        "cvt.rn.bf16x2.f32 b1, d3, d1;\n"
        "tanh.approx.f32 t0, p5;\n"
        "tanh.approx.f32 t1, p7;\n"
        "fma.rn.f32 t0, p5, t0, p5;\n"
        "fma.rn.f32 t1, p7, t1, p7;\n"
        "cvt.rn.bf16x2.f32 r1, t1, t0;\n"
        "mma.sync.aligned.m16n8k16.row.col.f32.bf16.bf16.f32 {p4,p5,p6,p7}, {%165,%166,%167,%168}, {m2,m3}, {fz,fz,fz,fz};\n"
        "mov.b32 {lo,hi}, r2;\n"
        "mov.b32 rl, {lo,lo};\n"
        "mov.b32 rh, {hi,hi};\n"
        "mul.bf16x2 x8, x8, rl;\n"
        "mul.bf16x2 x9, x9, rl;\n"
        "mul.bf16x2 x10, x10, rh;\n"
        "mul.bf16x2 x11, x11, rh;\n"
        "mma.sync.aligned.m16n8k16.row.col.f32.bf16.bf16.f32 {%144,%145,%146,%147}, {a0,a1,a2,a3}, {x8,x9}, {%144,%145,%146,%147};\n"
        "mma.sync.aligned.m16n8k16.row.col.f32.bf16.bf16.f32 {%148,%149,%150,%151}, {a0,a1,a2,a3}, {x10,x11}, {%148,%149,%150,%151};\n"
        "ld.shared.v4.u32 {x8,x9,x10,x11}, [xa+1280];\n"
        "mma.sync.aligned.m16n8k8.row.col.f32.bf16.bf16.f32 {d0,d1,d2,d3}, {%179,%180}, {m1}, {fz,fz,fz,fz};\n"
        "cvt.rn.bf16x2.f32 b2, d2, d0;\n"
        "cvt.rn.bf16x2.f32 b3, d3, d1;\n"
        "tanh.approx.f32 t0, p9;\n"
        "tanh.approx.f32 t1, p11;\n"
        "fma.rn.f32 t0, p9, t0, p9;\n"
        "fma.rn.f32 t1, p11, t1, p11;\n"
        "cvt.rn.bf16x2.f32 r2, t1, t0;\n"
        "mma.sync.aligned.m16n8k16.row.col.f32.bf16.bf16.f32 {p8,p9,p10,p11}, {%169,%170,%171,%172}, {m2,m3}, {fz,fz,fz,fz};\n"
        "mov.b32 {lo,hi}, r3;\n"
        "mov.b32 rl, {lo,lo};\n"
        "mov.b32 rh, {hi,hi};\n"
        "mul.bf16x2 x12, x12, rl;\n"
        "mul.bf16x2 x13, x13, rl;\n"
        "mul.bf16x2 x14, x14, rh;\n"
        "mul.bf16x2 x15, x15, rh;\n"
        "mma.sync.aligned.m16n8k16.row.col.f32.bf16.bf16.f32 {%152,%153,%154,%155}, {a0,a1,a2,a3}, {x12,x13}, {%152,%153,%154,%155};\n"
        "mma.sync.aligned.m16n8k16.row.col.f32.bf16.bf16.f32 {%156,%157,%158,%159}, {a0,a1,a2,a3}, {x14,x15}, {%156,%157,%158,%159};\n"
        "ld.shared.v4.u32 {x12,x13,x14,x15}, [xa+1408];\n"
        "@el mbarrier.arrive.shared.b64 _, [k0+8712];\n"
        "redux.sync.or.b32 ln, tag, 0xffffffff;\n"
        "mov.u32 sa, sn;\n"
        "add.u32 k0, sn, zz;\n"
        "tanh.approx.f32 t0, p13;\n"
        "tanh.approx.f32 t1, p15;\n"
        "fma.rn.f32 t0, p13, t0, p13;\n"
        "fma.rn.f32 t1, p15, t1, p15;\n"
        "cvt.rn.bf16x2.f32 r3, t1, t0;\n"
        "mma.sync.aligned.m16n8k16.row.col.f32.bf16.bf16.f32 {p12,p13,p14,p15}, {%173,%174,%175,%176}, {m2,m3}, {fz,fz,fz,fz};\n"
        "selp.u32 tq, lb, 5, w;\n"
        "brx.idx.uni tq, TB_%=;\n"
        "B0_%=:\n"
        "and.b32 la, ln, 255;\n"
        "shr.u32 lb, ln, 8;\n"
        "add.u32 ma, sa, %182;\n"
        "ldmatrix.sync.aligned.m8n8.x1.shared.b16 {yb}, [ma];\n"
        "add.u32 xa, sa, %181;\n"
        "mov.b32 {lo,hi}, r0;\n"
        "mov.b32 rl, {lo,lo};\n"
        "mov.b32 rh, {hi,hi};\n"
        "mul.bf16x2 x0, x0, rl;\n"
        "mul.bf16x2 x1, x1, rl;\n"
        "mul.bf16x2 x2, x2, rh;\n"
        "mul.bf16x2 x3, x3, rh;\n"
        "mma.sync.aligned.m16n8k16.row.col.f32.bf16.bf16.f32 {%0,%1,%2,%3}, {b0,b1,b2,b3}, {x0,x1}, {%0,%1,%2,%3};\n"
        "mma.sync.aligned.m16n8k16.row.col.f32.bf16.bf16.f32 {%4,%5,%6,%7}, {b0,b1,b2,b3}, {x2,x3}, {%4,%5,%6,%7};\n"
        "ld.shared.v4.u32 {x0,x1,x2,x3}, [xa+0];\n"
        "tanh.approx.f32 t0, p0;\n"
        "tanh.approx.f32 t1, p2;\n"
        "fma.rn.f32 t0, p0, t0, p0;\n"
        "fma.rn.f32 t1, p2, t1, p2;\n"
        "cvt.rn.bf16x2.f32 r0, t1, t0;\n"
        "mov.b32 {lo,hi}, r1;\n"
        "mov.b32 rl, {lo,lo};\n"
        "mov.b32 rh, {hi,hi};\n"
        "mul.bf16x2 x4, x4, rl;\n"
        "mul.bf16x2 x5, x5, rl;\n"
        "mul.bf16x2 x6, x6, rh;\n"
        "mul.bf16x2 x7, x7, rh;\n"
        "mma.sync.aligned.m16n8k16.row.col.f32.bf16.bf16.f32 {%8,%9,%10,%11}, {b0,b1,b2,b3}, {x4,x5}, {%8,%9,%10,%11};\n"
        "mma.sync.aligned.m16n8k16.row.col.f32.bf16.bf16.f32 {%12,%13,%14,%15}, {b0,b1,b2,b3}, {x6,x7}, {%12,%13,%14,%15};\n"
        "ld.shared.v4.u32 {x4,x5,x6,x7}, [xa+128];\n"
        "tanh.approx.f32 t0, p4;\n"
        "tanh.approx.f32 t1, p6;\n"
        "fma.rn.f32 t0, p4, t0, p4;\n"
        "fma.rn.f32 t1, p6, t1, p6;\n"
        "cvt.rn.bf16x2.f32 r1, t1, t0;\n"
        "mma.sync.aligned.m16n8k8.row.col.f32.bf16.bf16.f32 {d0,d1,d2,d3}, {%177,%178}, {yb}, {fz,fz,fz,fz};\n"
        "cvt.rn.bf16x2.f32 a0, d2, d0;\n"
        "cvt.rn.bf16x2.f32 a1, d3, d1;\n"
        "mov.b32 {lo,hi}, r2;\n"
        "mov.b32 rl, {lo,lo};\n"
        "mov.b32 rh, {hi,hi};\n"
        "mul.bf16x2 x8, x8, rl;\n"
        "mul.bf16x2 x9, x9, rl;\n"
        "mul.bf16x2 x10, x10, rh;\n"
        "mul.bf16x2 x11, x11, rh;\n"
        "mma.sync.aligned.m16n8k16.row.col.f32.bf16.bf16.f32 {%16,%17,%18,%19}, {b0,b1,b2,b3}, {x8,x9}, {%16,%17,%18,%19};\n"
        "mma.sync.aligned.m16n8k16.row.col.f32.bf16.bf16.f32 {%20,%21,%22,%23}, {b0,b1,b2,b3}, {x10,x11}, {%20,%21,%22,%23};\n"
        "ld.shared.v4.u32 {x8,x9,x10,x11}, [xa+256];\n"
        "tanh.approx.f32 t0, p8;\n"
        "tanh.approx.f32 t1, p10;\n"
        "fma.rn.f32 t0, p8, t0, p8;\n"
        "fma.rn.f32 t1, p10, t1, p10;\n"
        "cvt.rn.bf16x2.f32 r2, t1, t0;\n"
        "mma.sync.aligned.m16n8k8.row.col.f32.bf16.bf16.f32 {d0,d1,d2,d3}, {%179,%180}, {yb}, {fz,fz,fz,fz};\n"
        "cvt.rn.bf16x2.f32 a2, d2, d0;\n"
        "cvt.rn.bf16x2.f32 a3, d3, d1;\n"
        "mov.b32 {lo,hi}, r3;\n"
        "mov.b32 rl, {lo,lo};\n"
        "mov.b32 rh, {hi,hi};\n"
        "mul.bf16x2 x12, x12, rl;\n"
        "mul.bf16x2 x13, x13, rl;\n"
        "mul.bf16x2 x14, x14, rh;\n"
        "mul.bf16x2 x15, x15, rh;\n"
        "mma.sync.aligned.m16n8k16.row.col.f32.bf16.bf16.f32 {%24,%25,%26,%27}, {b0,b1,b2,b3}, {x12,x13}, {%24,%25,%26,%27};\n"
        "mma.sync.aligned.m16n8k16.row.col.f32.bf16.bf16.f32 {%28,%29,%30,%31}, {b0,b1,b2,b3}, {x14,x15}, {%28,%29,%30,%31};\n"
        "ld.shared.v4.u32 {x12,x13,x14,x15}, [xa+384];\n"
        "tanh.approx.f32 t0, p12;\n"
        "tanh.approx.f32 t1, p14;\n"
        "fma.rn.f32 t0, p12, t0, p12;\n"
        "fma.rn.f32 t1, p14, t1, p14;\n"
        "cvt.rn.bf16x2.f32 r3, t1, t0;\n"
        "mov.b32 {lo,hi}, r0;\n"
        "mov.b32 rl, {lo,lo};\n"
        "mov.b32 rh, {hi,hi};\n"
        "mul.bf16x2 x0, x0, rl;\n"
        "mul.bf16x2 x1, x1, rl;\n"
        "mul.bf16x2 x2, x2, rh;\n"
        "mul.bf16x2 x3, x3, rh;\n"
        "mov.b32 {lo,hi}, r1;\n"
        "mov.b32 rl, {lo,lo};\n"
        "mov.b32 rh, {hi,hi};\n"
        "mul.bf16x2 x4, x4, rl;\n"
        "mul.bf16x2 x5, x5, rl;\n"
        "mul.bf16x2 x6, x6, rh;\n"
        "mul.bf16x2 x7, x7, rh;\n"
        "brx.idx.uni la, TA_%=;\n"
        "B1_%=:\n"
        "and.b32 la, ln, 255;\n"
        "shr.u32 lb, ln, 8;\n"
        "add.u32 ma, sa, %182;\n"
        "ldmatrix.sync.aligned.m8n8.x1.shared.b16 {yb}, [ma];\n"
        "add.u32 xa, sa, %181;\n"
        "mov.b32 {lo,hi}, r0;\n"
        "mov.b32 rl, {lo,lo};\n"
        "mov.b32 rh, {hi,hi};\n"
        "mul.bf16x2 x0, x0, rl;\n"
        "mul.bf16x2 x1, x1, rl;\n"
        "mul.bf16x2 x2, x2, rh;\n"
        "mul.bf16x2 x3, x3, rh;\n"
        "mma.sync.aligned.m16n8k16.row.col.f32.bf16.bf16.f32 {%32,%33,%34,%35}, {b0,b1,b2,b3}, {x0,x1}, {%32,%33,%34,%35};\n"
        "mma.sync.aligned.m16n8k16.row.col.f32.bf16.bf16.f32 {%36,%37,%38,%39}, {b0,b1,b2,b3}, {x2,x3}, {%36,%37,%38,%39};\n"
        "ld.shared.v4.u32 {x0,x1,x2,x3}, [xa+0];\n"
        "tanh.approx.f32 t0, p0;\n"
        "tanh.approx.f32 t1, p2;\n"
        "fma.rn.f32 t0, p0, t0, p0;\n"
        "fma.rn.f32 t1, p2, t1, p2;\n"
        "cvt.rn.bf16x2.f32 r0, t1, t0;\n"
        "mov.b32 {lo,hi}, r1;\n"
        "mov.b32 rl, {lo,lo};\n"
        "mov.b32 rh, {hi,hi};\n"
        "mul.bf16x2 x4, x4, rl;\n"
        "mul.bf16x2 x5, x5, rl;\n"
        "mul.bf16x2 x6, x6, rh;\n"
        "mul.bf16x2 x7, x7, rh;\n"
        "mma.sync.aligned.m16n8k16.row.col.f32.bf16.bf16.f32 {%40,%41,%42,%43}, {b0,b1,b2,b3}, {x4,x5}, {%40,%41,%42,%43};\n"
        "mma.sync.aligned.m16n8k16.row.col.f32.bf16.bf16.f32 {%44,%45,%46,%47}, {b0,b1,b2,b3}, {x6,x7}, {%44,%45,%46,%47};\n"
        "ld.shared.v4.u32 {x4,x5,x6,x7}, [xa+128];\n"
        "tanh.approx.f32 t0, p4;\n"
        "tanh.approx.f32 t1, p6;\n"
        "fma.rn.f32 t0, p4, t0, p4;\n"
        "fma.rn.f32 t1, p6, t1, p6;\n"
        "cvt.rn.bf16x2.f32 r1, t1, t0;\n"
        "mma.sync.aligned.m16n8k8.row.col.f32.bf16.bf16.f32 {d0,d1,d2,d3}, {%177,%178}, {yb}, {fz,fz,fz,fz};\n"
        "cvt.rn.bf16x2.f32 a0, d2, d0;\n"
        "cvt.rn.bf16x2.f32 a1, d3, d1;\n"
        "mov.b32 {lo,hi}, r2;\n"
        "mov.b32 rl, {lo,lo};\n"
        "mov.b32 rh, {hi,hi};\n"
        "mul.bf16x2 x8, x8, rl;\n"
        "mul.bf16x2 x9, x9, rl;\n"
        "mul.bf16x2 x10, x10, rh;\n"
        "mul.bf16x2 x11, x11, rh;\n"
        "mma.sync.aligned.m16n8k16.row.col.f32.bf16.bf16.f32 {%48,%49,%50,%51}, {b0,b1,b2,b3}, {x8,x9}, {%48,%49,%50,%51};\n"
        "mma.sync.aligned.m16n8k16.row.col.f32.bf16.bf16.f32 {%52,%53,%54,%55}, {b0,b1,b2,b3}, {x10,x11}, {%52,%53,%54,%55};\n"
        "ld.shared.v4.u32 {x8,x9,x10,x11}, [xa+256];\n"
        "tanh.approx.f32 t0, p8;\n"
        "tanh.approx.f32 t1, p10;\n"
        "fma.rn.f32 t0, p8, t0, p8;\n"
        "fma.rn.f32 t1, p10, t1, p10;\n"
        "cvt.rn.bf16x2.f32 r2, t1, t0;\n"
        "mma.sync.aligned.m16n8k8.row.col.f32.bf16.bf16.f32 {d0,d1,d2,d3}, {%179,%180}, {yb}, {fz,fz,fz,fz};\n"
        "cvt.rn.bf16x2.f32 a2, d2, d0;\n"
        "cvt.rn.bf16x2.f32 a3, d3, d1;\n"
        "mov.b32 {lo,hi}, r3;\n"
        "mov.b32 rl, {lo,lo};\n"
        "mov.b32 rh, {hi,hi};\n"
        "mul.bf16x2 x12, x12, rl;\n"
        "mul.bf16x2 x13, x13, rl;\n"
        "mul.bf16x2 x14, x14, rh;\n"
        "mul.bf16x2 x15, x15, rh;\n"
        "mma.sync.aligned.m16n8k16.row.col.f32.bf16.bf16.f32 {%56,%57,%58,%59}, {b0,b1,b2,b3}, {x12,x13}, {%56,%57,%58,%59};\n"
        "mma.sync.aligned.m16n8k16.row.col.f32.bf16.bf16.f32 {%60,%61,%62,%63}, {b0,b1,b2,b3}, {x14,x15}, {%60,%61,%62,%63};\n"
        "ld.shared.v4.u32 {x12,x13,x14,x15}, [xa+384];\n"
        "tanh.approx.f32 t0, p12;\n"
        "tanh.approx.f32 t1, p14;\n"
        "fma.rn.f32 t0, p12, t0, p12;\n"
        "fma.rn.f32 t1, p14, t1, p14;\n"
        "cvt.rn.bf16x2.f32 r3, t1, t0;\n"
        "mov.b32 {lo,hi}, r0;\n"
        "mov.b32 rl, {lo,lo};\n"
        "mov.b32 rh, {hi,hi};\n"
        "mul.bf16x2 x0, x0, rl;\n"
        "mul.bf16x2 x1, x1, rl;\n"
        "mul.bf16x2 x2, x2, rh;\n"
        "mul.bf16x2 x3, x3, rh;\n"
        "mov.b32 {lo,hi}, r1;\n"
        "mov.b32 rl, {lo,lo};\n"
        "mov.b32 rh, {hi,hi};\n"
        "mul.bf16x2 x4, x4, rl;\n"
        "mul.bf16x2 x5, x5, rl;\n"
        "mul.bf16x2 x6, x6, rh;\n"
        "mul.bf16x2 x7, x7, rh;\n"
        "brx.idx.uni la, TA_%=;\n"
        "B2_%=:\n"
        "and.b32 la, ln, 255;\n"
        "shr.u32 lb, ln, 8;\n"
        "add.u32 ma, sa, %182;\n"
        "ldmatrix.sync.aligned.m8n8.x1.shared.b16 {yb}, [ma];\n"
        "add.u32 xa, sa, %181;\n"
        "mov.b32 {lo,hi}, r0;\n"
        "mov.b32 rl, {lo,lo};\n"
        "mov.b32 rh, {hi,hi};\n"
        "mul.bf16x2 x0, x0, rl;\n"
        "mul.bf16x2 x1, x1, rl;\n"
        "mul.bf16x2 x2, x2, rh;\n"
        "mul.bf16x2 x3, x3, rh;\n"
        "mma.sync.aligned.m16n8k16.row.col.f32.bf16.bf16.f32 {%64,%65,%66,%67}, {b0,b1,b2,b3}, {x0,x1}, {%64,%65,%66,%67};\n"
        "mma.sync.aligned.m16n8k16.row.col.f32.bf16.bf16.f32 {%68,%69,%70,%71}, {b0,b1,b2,b3}, {x2,x3}, {%68,%69,%70,%71};\n"
        "ld.shared.v4.u32 {x0,x1,x2,x3}, [xa+0];\n"
        "tanh.approx.f32 t0, p0;\n"
        "tanh.approx.f32 t1, p2;\n"
        "fma.rn.f32 t0, p0, t0, p0;\n"
        "fma.rn.f32 t1, p2, t1, p2;\n"
        "cvt.rn.bf16x2.f32 r0, t1, t0;\n"
        "mov.b32 {lo,hi}, r1;\n"
        "mov.b32 rl, {lo,lo};\n"
        "mov.b32 rh, {hi,hi};\n"
        "mul.bf16x2 x4, x4, rl;\n"
        "mul.bf16x2 x5, x5, rl;\n"
        "mul.bf16x2 x6, x6, rh;\n"
        "mul.bf16x2 x7, x7, rh;\n"
        "mma.sync.aligned.m16n8k16.row.col.f32.bf16.bf16.f32 {%72,%73,%74,%75}, {b0,b1,b2,b3}, {x4,x5}, {%72,%73,%74,%75};\n"
        "mma.sync.aligned.m16n8k16.row.col.f32.bf16.bf16.f32 {%76,%77,%78,%79}, {b0,b1,b2,b3}, {x6,x7}, {%76,%77,%78,%79};\n"
        "ld.shared.v4.u32 {x4,x5,x6,x7}, [xa+128];\n"
        "tanh.approx.f32 t0, p4;\n"
        "tanh.approx.f32 t1, p6;\n"
        "fma.rn.f32 t0, p4, t0, p4;\n"
        "fma.rn.f32 t1, p6, t1, p6;\n"
        "cvt.rn.bf16x2.f32 r1, t1, t0;\n"
        "mma.sync.aligned.m16n8k8.row.col.f32.bf16.bf16.f32 {d0,d1,d2,d3}, {%177,%178}, {yb}, {fz,fz,fz,fz};\n"
        "cvt.rn.bf16x2.f32 a0, d2, d0;\n"
        "cvt.rn.bf16x2.f32 a1, d3, d1;\n"
        "mov.b32 {lo,hi}, r2;\n"
        "mov.b32 rl, {lo,lo};\n"
        "mov.b32 rh, {hi,hi};\n"
        "mul.bf16x2 x8, x8, rl;\n"
        "mul.bf16x2 x9, x9, rl;\n"
        "mul.bf16x2 x10, x10, rh;\n"
        "mul.bf16x2 x11, x11, rh;\n"
        "mma.sync.aligned.m16n8k16.row.col.f32.bf16.bf16.f32 {%80,%81,%82,%83}, {b0,b1,b2,b3}, {x8,x9}, {%80,%81,%82,%83};\n"
        "mma.sync.aligned.m16n8k16.row.col.f32.bf16.bf16.f32 {%84,%85,%86,%87}, {b0,b1,b2,b3}, {x10,x11}, {%84,%85,%86,%87};\n"
        "ld.shared.v4.u32 {x8,x9,x10,x11}, [xa+256];\n"
        "tanh.approx.f32 t0, p8;\n"
        "tanh.approx.f32 t1, p10;\n"
        "fma.rn.f32 t0, p8, t0, p8;\n"
        "fma.rn.f32 t1, p10, t1, p10;\n"
        "cvt.rn.bf16x2.f32 r2, t1, t0;\n"
        "mma.sync.aligned.m16n8k8.row.col.f32.bf16.bf16.f32 {d0,d1,d2,d3}, {%179,%180}, {yb}, {fz,fz,fz,fz};\n"
        "cvt.rn.bf16x2.f32 a2, d2, d0;\n"
        "cvt.rn.bf16x2.f32 a3, d3, d1;\n"
        "mov.b32 {lo,hi}, r3;\n"
        "mov.b32 rl, {lo,lo};\n"
        "mov.b32 rh, {hi,hi};\n"
        "mul.bf16x2 x12, x12, rl;\n"
        "mul.bf16x2 x13, x13, rl;\n"
        "mul.bf16x2 x14, x14, rh;\n"
        "mul.bf16x2 x15, x15, rh;\n"
        "mma.sync.aligned.m16n8k16.row.col.f32.bf16.bf16.f32 {%88,%89,%90,%91}, {b0,b1,b2,b3}, {x12,x13}, {%88,%89,%90,%91};\n"
        "mma.sync.aligned.m16n8k16.row.col.f32.bf16.bf16.f32 {%92,%93,%94,%95}, {b0,b1,b2,b3}, {x14,x15}, {%92,%93,%94,%95};\n"
        "ld.shared.v4.u32 {x12,x13,x14,x15}, [xa+384];\n"
        "tanh.approx.f32 t0, p12;\n"
        "tanh.approx.f32 t1, p14;\n"
        "fma.rn.f32 t0, p12, t0, p12;\n"
        "fma.rn.f32 t1, p14, t1, p14;\n"
        "cvt.rn.bf16x2.f32 r3, t1, t0;\n"
        "mov.b32 {lo,hi}, r0;\n"
        "mov.b32 rl, {lo,lo};\n"
        "mov.b32 rh, {hi,hi};\n"
        "mul.bf16x2 x0, x0, rl;\n"
        "mul.bf16x2 x1, x1, rl;\n"
        "mul.bf16x2 x2, x2, rh;\n"
        "mul.bf16x2 x3, x3, rh;\n"
        "mov.b32 {lo,hi}, r1;\n"
        "mov.b32 rl, {lo,lo};\n"
        "mov.b32 rh, {hi,hi};\n"
        "mul.bf16x2 x4, x4, rl;\n"
        "mul.bf16x2 x5, x5, rl;\n"
        "mul.bf16x2 x6, x6, rh;\n"
        "mul.bf16x2 x7, x7, rh;\n"
        "brx.idx.uni la, TA_%=;\n"
        "B3_%=:\n"
        "and.b32 la, ln, 255;\n"
        "shr.u32 lb, ln, 8;\n"
        "add.u32 ma, sa, %182;\n"
        "ldmatrix.sync.aligned.m8n8.x1.shared.b16 {yb}, [ma];\n"
        "add.u32 xa, sa, %181;\n"
        "mov.b32 {lo,hi}, r0;\n"
        "mov.b32 rl, {lo,lo};\n"
        "mov.b32 rh, {hi,hi};\n"
        "mul.bf16x2 x0, x0, rl;\n"
        "mul.bf16x2 x1, x1, rl;\n"
        "mul.bf16x2 x2, x2, rh;\n"
        "mul.bf16x2 x3, x3, rh;\n"
        "mma.sync.aligned.m16n8k16.row.col.f32.bf16.bf16.f32 {%96,%97,%98,%99}, {b0,b1,b2,b3}, {x0,x1}, {%96,%97,%98,%99};\n"
        "mma.sync.aligned.m16n8k16.row.col.f32.bf16.bf16.f32 {%100,%101,%102,%103}, {b0,b1,b2,b3}, {x2,x3}, {%100,%101,%102,%103};\n"
        "ld.shared.v4.u32 {x0,x1,x2,x3}, [xa+0];\n"
        "tanh.approx.f32 t0, p0;\n"
        "tanh.approx.f32 t1, p2;\n"
        "fma.rn.f32 t0, p0, t0, p0;\n"
        "fma.rn.f32 t1, p2, t1, p2;\n"
        "cvt.rn.bf16x2.f32 r0, t1, t0;\n"
        "mov.b32 {lo,hi}, r1;\n"
        "mov.b32 rl, {lo,lo};\n"
        "mov.b32 rh, {hi,hi};\n"
        "mul.bf16x2 x4, x4, rl;\n"
        "mul.bf16x2 x5, x5, rl;\n"
        "mul.bf16x2 x6, x6, rh;\n"
        "mul.bf16x2 x7, x7, rh;\n"
        "mma.sync.aligned.m16n8k16.row.col.f32.bf16.bf16.f32 {%104,%105,%106,%107}, {b0,b1,b2,b3}, {x4,x5}, {%104,%105,%106,%107};\n"
        "mma.sync.aligned.m16n8k16.row.col.f32.bf16.bf16.f32 {%108,%109,%110,%111}, {b0,b1,b2,b3}, {x6,x7}, {%108,%109,%110,%111};\n"
        "ld.shared.v4.u32 {x4,x5,x6,x7}, [xa+128];\n"
        "tanh.approx.f32 t0, p4;\n"
        "tanh.approx.f32 t1, p6;\n"
        "fma.rn.f32 t0, p4, t0, p4;\n"
        "fma.rn.f32 t1, p6, t1, p6;\n"
        "cvt.rn.bf16x2.f32 r1, t1, t0;\n"
        "mma.sync.aligned.m16n8k8.row.col.f32.bf16.bf16.f32 {d0,d1,d2,d3}, {%177,%178}, {yb}, {fz,fz,fz,fz};\n"
        "cvt.rn.bf16x2.f32 a0, d2, d0;\n"
        "cvt.rn.bf16x2.f32 a1, d3, d1;\n"
        "mov.b32 {lo,hi}, r2;\n"
        "mov.b32 rl, {lo,lo};\n"
        "mov.b32 rh, {hi,hi};\n"
        "mul.bf16x2 x8, x8, rl;\n"
        "mul.bf16x2 x9, x9, rl;\n"
        "mul.bf16x2 x10, x10, rh;\n"
        "mul.bf16x2 x11, x11, rh;\n"
        "mma.sync.aligned.m16n8k16.row.col.f32.bf16.bf16.f32 {%112,%113,%114,%115}, {b0,b1,b2,b3}, {x8,x9}, {%112,%113,%114,%115};\n"
        "mma.sync.aligned.m16n8k16.row.col.f32.bf16.bf16.f32 {%116,%117,%118,%119}, {b0,b1,b2,b3}, {x10,x11}, {%116,%117,%118,%119};\n"
        "ld.shared.v4.u32 {x8,x9,x10,x11}, [xa+256];\n"
        "tanh.approx.f32 t0, p8;\n"
        "tanh.approx.f32 t1, p10;\n"
        "fma.rn.f32 t0, p8, t0, p8;\n"
        "fma.rn.f32 t1, p10, t1, p10;\n"
        "cvt.rn.bf16x2.f32 r2, t1, t0;\n"
        "mma.sync.aligned.m16n8k8.row.col.f32.bf16.bf16.f32 {d0,d1,d2,d3}, {%179,%180}, {yb}, {fz,fz,fz,fz};\n"
        "cvt.rn.bf16x2.f32 a2, d2, d0;\n"
        "cvt.rn.bf16x2.f32 a3, d3, d1;\n"
        "mov.b32 {lo,hi}, r3;\n"
        "mov.b32 rl, {lo,lo};\n"
        "mov.b32 rh, {hi,hi};\n"
        "mul.bf16x2 x12, x12, rl;\n"
        "mul.bf16x2 x13, x13, rl;\n"
        "mul.bf16x2 x14, x14, rh;\n"
        "mul.bf16x2 x15, x15, rh;\n"
        "mma.sync.aligned.m16n8k16.row.col.f32.bf16.bf16.f32 {%120,%121,%122,%123}, {b0,b1,b2,b3}, {x12,x13}, {%120,%121,%122,%123};\n"
        "mma.sync.aligned.m16n8k16.row.col.f32.bf16.bf16.f32 {%124,%125,%126,%127}, {b0,b1,b2,b3}, {x14,x15}, {%124,%125,%126,%127};\n"
        "ld.shared.v4.u32 {x12,x13,x14,x15}, [xa+384];\n"
        "tanh.approx.f32 t0, p12;\n"
        "tanh.approx.f32 t1, p14;\n"
        "fma.rn.f32 t0, p12, t0, p12;\n"
        "fma.rn.f32 t1, p14, t1, p14;\n"
        "cvt.rn.bf16x2.f32 r3, t1, t0;\n"
        "mov.b32 {lo,hi}, r0;\n"
        "mov.b32 rl, {lo,lo};\n"
        "mov.b32 rh, {hi,hi};\n"
        "mul.bf16x2 x0, x0, rl;\n"
        "mul.bf16x2 x1, x1, rl;\n"
        "mul.bf16x2 x2, x2, rh;\n"
        "mul.bf16x2 x3, x3, rh;\n"
        "mov.b32 {lo,hi}, r1;\n"
        "mov.b32 rl, {lo,lo};\n"
        "mov.b32 rh, {hi,hi};\n"
        "mul.bf16x2 x4, x4, rl;\n"
        "mul.bf16x2 x5, x5, rl;\n"
        "mul.bf16x2 x6, x6, rh;\n"
        "mul.bf16x2 x7, x7, rh;\n"
        "brx.idx.uni la, TA_%=;\n"
        "B4_%=:\n"
        "and.b32 la, ln, 255;\n"
        "shr.u32 lb, ln, 8;\n"
        "add.u32 ma, sa, %182;\n"
        "ldmatrix.sync.aligned.m8n8.x1.shared.b16 {yb}, [ma];\n"
        "add.u32 xa, sa, %181;\n"
        "mov.b32 {lo,hi}, r0;\n"
        "mov.b32 rl, {lo,lo};\n"
        "mov.b32 rh, {hi,hi};\n"
        "mul.bf16x2 x0, x0, rl;\n"
        "mul.bf16x2 x1, x1, rl;\n"
        "mul.bf16x2 x2, x2, rh;\n"
        "mul.bf16x2 x3, x3, rh;\n"
        "mma.sync.aligned.m16n8k16.row.col.f32.bf16.bf16.f32 {%128,%129,%130,%131}, {b0,b1,b2,b3}, {x0,x1}, {%128,%129,%130,%131};\n"
        "mma.sync.aligned.m16n8k16.row.col.f32.bf16.bf16.f32 {%132,%133,%134,%135}, {b0,b1,b2,b3}, {x2,x3}, {%132,%133,%134,%135};\n"
        "ld.shared.v4.u32 {x0,x1,x2,x3}, [xa+0];\n"
        "tanh.approx.f32 t0, p0;\n"
        "tanh.approx.f32 t1, p2;\n"
        "fma.rn.f32 t0, p0, t0, p0;\n"
        "fma.rn.f32 t1, p2, t1, p2;\n"
        "cvt.rn.bf16x2.f32 r0, t1, t0;\n"
        "mov.b32 {lo,hi}, r1;\n"
        "mov.b32 rl, {lo,lo};\n"
        "mov.b32 rh, {hi,hi};\n"
        "mul.bf16x2 x4, x4, rl;\n"
        "mul.bf16x2 x5, x5, rl;\n"
        "mul.bf16x2 x6, x6, rh;\n"
        "mul.bf16x2 x7, x7, rh;\n"
        "mma.sync.aligned.m16n8k16.row.col.f32.bf16.bf16.f32 {%136,%137,%138,%139}, {b0,b1,b2,b3}, {x4,x5}, {%136,%137,%138,%139};\n"
        "mma.sync.aligned.m16n8k16.row.col.f32.bf16.bf16.f32 {%140,%141,%142,%143}, {b0,b1,b2,b3}, {x6,x7}, {%140,%141,%142,%143};\n"
        "ld.shared.v4.u32 {x4,x5,x6,x7}, [xa+128];\n"
        "tanh.approx.f32 t0, p4;\n"
        "tanh.approx.f32 t1, p6;\n"
        "fma.rn.f32 t0, p4, t0, p4;\n"
        "fma.rn.f32 t1, p6, t1, p6;\n"
        "cvt.rn.bf16x2.f32 r1, t1, t0;\n"
        "mma.sync.aligned.m16n8k8.row.col.f32.bf16.bf16.f32 {d0,d1,d2,d3}, {%177,%178}, {yb}, {fz,fz,fz,fz};\n"
        "cvt.rn.bf16x2.f32 a0, d2, d0;\n"
        "cvt.rn.bf16x2.f32 a1, d3, d1;\n"
        "mov.b32 {lo,hi}, r2;\n"
        "mov.b32 rl, {lo,lo};\n"
        "mov.b32 rh, {hi,hi};\n"
        "mul.bf16x2 x8, x8, rl;\n"
        "mul.bf16x2 x9, x9, rl;\n"
        "mul.bf16x2 x10, x10, rh;\n"
        "mul.bf16x2 x11, x11, rh;\n"
        "mma.sync.aligned.m16n8k16.row.col.f32.bf16.bf16.f32 {%144,%145,%146,%147}, {b0,b1,b2,b3}, {x8,x9}, {%144,%145,%146,%147};\n"
        "mma.sync.aligned.m16n8k16.row.col.f32.bf16.bf16.f32 {%148,%149,%150,%151}, {b0,b1,b2,b3}, {x10,x11}, {%148,%149,%150,%151};\n"
        "ld.shared.v4.u32 {x8,x9,x10,x11}, [xa+256];\n"
        "tanh.approx.f32 t0, p8;\n"
        "tanh.approx.f32 t1, p10;\n"
        "fma.rn.f32 t0, p8, t0, p8;\n"
        "fma.rn.f32 t1, p10, t1, p10;\n"
        "cvt.rn.bf16x2.f32 r2, t1, t0;\n"
        "mma.sync.aligned.m16n8k8.row.col.f32.bf16.bf16.f32 {d0,d1,d2,d3}, {%179,%180}, {yb}, {fz,fz,fz,fz};\n"
        "cvt.rn.bf16x2.f32 a2, d2, d0;\n"
        "cvt.rn.bf16x2.f32 a3, d3, d1;\n"
        "mov.b32 {lo,hi}, r3;\n"
        "mov.b32 rl, {lo,lo};\n"
        "mov.b32 rh, {hi,hi};\n"
        "mul.bf16x2 x12, x12, rl;\n"
        "mul.bf16x2 x13, x13, rl;\n"
        "mul.bf16x2 x14, x14, rh;\n"
        "mul.bf16x2 x15, x15, rh;\n"
        "mma.sync.aligned.m16n8k16.row.col.f32.bf16.bf16.f32 {%152,%153,%154,%155}, {b0,b1,b2,b3}, {x12,x13}, {%152,%153,%154,%155};\n"
        "mma.sync.aligned.m16n8k16.row.col.f32.bf16.bf16.f32 {%156,%157,%158,%159}, {b0,b1,b2,b3}, {x14,x15}, {%156,%157,%158,%159};\n"
        "ld.shared.v4.u32 {x12,x13,x14,x15}, [xa+384];\n"
        "tanh.approx.f32 t0, p12;\n"
        "tanh.approx.f32 t1, p14;\n"
        "fma.rn.f32 t0, p12, t0, p12;\n"
        "fma.rn.f32 t1, p14, t1, p14;\n"
        "cvt.rn.bf16x2.f32 r3, t1, t0;\n"
        "mov.b32 {lo,hi}, r0;\n"
        "mov.b32 rl, {lo,lo};\n"
        "mov.b32 rh, {hi,hi};\n"
        "mul.bf16x2 x0, x0, rl;\n"
        "mul.bf16x2 x1, x1, rl;\n"
        "mul.bf16x2 x2, x2, rh;\n"
        "mul.bf16x2 x3, x3, rh;\n"
        "mov.b32 {lo,hi}, r1;\n"
        "mov.b32 rl, {lo,lo};\n"
        "mov.b32 rh, {hi,hi};\n"
        "mul.bf16x2 x4, x4, rl;\n"
        "mul.bf16x2 x5, x5, rl;\n"
        "mul.bf16x2 x6, x6, rh;\n"
        "mul.bf16x2 x7, x7, rh;\n"
        "brx.idx.uni la, TA_%=;\n"
        "EXIT_%=:\n"
        "mov.u32 %160, ring;\n"
        "}\n"
        : "+f"(acc[0][0][0][0]), "+f"(acc[0][0][0][1]), "+f"(acc[0][0][0][2]), "+f"(acc[0][0][0][3]), "+f"(acc[0][0][1][0]),
          "+f"(acc[0][0][1][1]), "+f"(acc[0][0][1][2]), "+f"(acc[0][0][1][3]), "+f"(acc[0][1][0][0]), "+f"(acc[0][1][0][1]),
          "+f"(acc[0][1][0][2]), "+f"(acc[0][1][0][3]), "+f"(acc[0][1][1][0]), "+f"(acc[0][1][1][1]), "+f"(acc[0][1][1][2]),
          "+f"(acc[0][1][1][3]), "+f"(acc[0][2][0][0]), "+f"(acc[0][2][0][1]), "+f"(acc[0][2][0][2]), "+f"(acc[0][2][0][3]),
          "+f"(acc[0][2][1][0]), "+f"(acc[0][2][1][1]), "+f"(acc[0][2][1][2]), "+f"(acc[0][2][1][3]), "+f"(acc[0][3][0][0]),
          "+f"(acc[0][3][0][1]), "+f"(acc[0][3][0][2]), "+f"(acc[0][3][0][3]), "+f"(acc[0][3][1][0]), "+f"(acc[0][3][1][1]),
          "+f"(acc[0][3][1][2]), "+f"(acc[0][3][1][3]), "+f"(acc[1][0][0][0]), "+f"(acc[1][0][0][1]), "+f"(acc[1][0][0][2]),
          "+f"(acc[1][0][0][3]), "+f"(acc[1][0][1][0]), "+f"(acc[1][0][1][1]), "+f"(acc[1][0][1][2]), "+f"(acc[1][0][1][3]),
          "+f"(acc[1][1][0][0]), "+f"(acc[1][1][0][1]), "+f"(acc[1][1][0][2]), "+f"(acc[1][1][0][3]), "+f"(acc[1][1][1][0]),
          "+f"(acc[1][1][1][1]), "+f"(acc[1][1][1][2]), "+f"(acc[1][1][1][3]), "+f"(acc[1][2][0][0]), "+f"(acc[1][2][0][1]),
          "+f"(acc[1][2][0][2]), "+f"(acc[1][2][0][3]), "+f"(acc[1][2][1][0]), "+f"(acc[1][2][1][1]), "+f"(acc[1][2][1][2]),
          "+f"(acc[1][2][1][3]), "+f"(acc[1][3][0][0]), "+f"(acc[1][3][0][1]), "+f"(acc[1][3][0][2]), "+f"(acc[1][3][0][3]),
          "+f"(acc[1][3][1][0]), "+f"(acc[1][3][1][1]), "+f"(acc[1][3][1][2]), "+f"(acc[1][3][1][3]), "+f"(acc[2][0][0][0]),
          "+f"(acc[2][0][0][1]), "+f"(acc[2][0][0][2]), "+f"(acc[2][0][0][3]), "+f"(acc[2][0][1][0]), "+f"(acc[2][0][1][1]),
          "+f"(acc[2][0][1][2]), "+f"(acc[2][0][1][3]), "+f"(acc[2][1][0][0]), "+f"(acc[2][1][0][1]), "+f"(acc[2][1][0][2]),
          "+f"(acc[2][1][0][3]), "+f"(acc[2][1][1][0]), "+f"(acc[2][1][1][1]), "+f"(acc[2][1][1][2]), "+f"(acc[2][1][1][3]),
          "+f"(acc[2][2][0][0]), "+f"(acc[2][2][0][1]), "+f"(acc[2][2][0][2]), "+f"(acc[2][2][0][3]), "+f"(acc[2][2][1][0]),
          "+f"(acc[2][2][1][1]), "+f"(acc[2][2][1][2]), "+f"(acc[2][2][1][3]), "+f"(acc[2][3][0][0]), "+f"(acc[2][3][0][1]),
          "+f"(acc[2][3][0][2]), "+f"(acc[2][3][0][3]), "+f"(acc[2][3][1][0]), "+f"(acc[2][3][1][1]), "+f"(acc[2][3][1][2]),
          "+f"(acc[2][3][1][3]), "+f"(acc[3][0][0][0]), "+f"(acc[3][0][0][1]), "+f"(acc[3][0][0][2]), "+f"(acc[3][0][0][3]),
          "+f"(acc[3][0][1][0]), "+f"(acc[3][0][1][1]), "+f"(acc[3][0][1][2]), "+f"(acc[3][0][1][3]), "+f"(acc[3][1][0][0]),
          "+f"(acc[3][1][0][1]), "+f"(acc[3][1][0][2]), "+f"(acc[3][1][0][3]), "+f"(acc[3][1][1][0]), "+f"(acc[3][1][1][1]),
          "+f"(acc[3][1][1][2]), "+f"(acc[3][1][1][3]), "+f"(acc[3][2][0][0]), "+f"(acc[3][2][0][1]), "+f"(acc[3][2][0][2]),
          "+f"(acc[3][2][0][3]), "+f"(acc[3][2][1][0]), "+f"(acc[3][2][1][1]), "+f"(acc[3][2][1][2]), "+f"(acc[3][2][1][3]),
          "+f"(acc[3][3][0][0]), "+f"(acc[3][3][0][1]), "+f"(acc[3][3][0][2]), "+f"(acc[3][3][0][3]), "+f"(acc[3][3][1][0]),
          "+f"(acc[3][3][1][1]), "+f"(acc[3][3][1][2]), "+f"(acc[3][3][1][3]), "+f"(acc[4][0][0][0]), "+f"(acc[4][0][0][1]),
          "+f"(acc[4][0][0][2]), "+f"(acc[4][0][0][3]), "+f"(acc[4][0][1][0]), "+f"(acc[4][0][1][1]), "+f"(acc[4][0][1][2]),
          "+f"(acc[4][0][1][3]), "+f"(acc[4][1][0][0]), "+f"(acc[4][1][0][1]), "+f"(acc[4][1][0][2]), "+f"(acc[4][1][0][3]),
          "+f"(acc[4][1][1][0]), "+f"(acc[4][1][1][1]), "+f"(acc[4][1][1][2]), "+f"(acc[4][1][1][3]), "+f"(acc[4][2][0][0]),
          "+f"(acc[4][2][0][1]), "+f"(acc[4][2][0][2]), "+f"(acc[4][2][0][3]), "+f"(acc[4][2][1][0]), "+f"(acc[4][2][1][1]),
          "+f"(acc[4][2][1][2]), "+f"(acc[4][2][1][3]), "+f"(acc[4][3][0][0]), "+f"(acc[4][3][0][1]), "+f"(acc[4][3][0][2]),
          "+f"(acc[4][3][0][3]), "+f"(acc[4][3][1][0]), "+f"(acc[4][3][1][1]), "+f"(acc[4][3][1][2]), "+f"(acc[4][3][1][3]),
          "+r"(ring)
        : "r"(wf[0][0]), "r"(wf[0][1]), "r"(wf[0][2]), "r"(wf[0][3]), "r"(wf[1][0]), "r"(wf[1][1]), "r"(wf[1][2]), "r"(wf[1][3]),
          "r"(wf[2][0]), "r"(wf[2][1]), "r"(wf[2][2]), "r"(wf[2][3]), "r"(wf[3][0]), "r"(wf[3][1]), "r"(wf[3][2]), "r"(wf[3][3]),
          "r"(cgf[0]), "r"(cgf[1]), "r"(cgf[2]), "r"(cgf[3]), "r"(xoff), "r"(moff), "r"(rec)
        : "memory");
}

__device__ __noinline__ void generic_path(float* sagg, const __nv_bfloat16* x, const int* src, const int* dst,
                                          const __nv_bfloat16* Y, const __nv_bfloat16* ef, const __nv_bfloat16* w_rad,
                                          const __nv_bfloat16* cg, int x0, int x1) {
    const int tid = threadIdx.x, lane = tid & 31, blk = blockIdx.x;
    for (int k = 0; k < 2; k++)
        for (int r = 0; r < min(k == 0 ? x0 : x1, 32); r++) {
            uint32_t* p2 = g_mail2 + (blk * NSRC + ((tid + k * NTHR) >> 3)) * 32 + r;
            uint32_t v;
            int it = 0;
            do {
                asm volatile("ld.relaxed.gpu.global.u32 %0, [%1];" : "=r"(v) : "l"(p2) : "memory");
                if (++it > (1 << 20)) __trap();
            } while (v == 0);
            *p2 = 0;
        }
    __syncthreads();
    for (int i = tid; i < NPB * 512; i += NTHR) sagg[i] = 0.f;
    __syncthreads();
    for (int e0 = tid & ~31; e0 < N_EDGES; e0 += NTHR) {
        uint32_t bm = __ballot_sync(~0u, dst[e0 + lane] / NPB == blk);
        while (bm) {
            const int e = e0 + __ffs(bm) - 1, s = src[e], loc = dst[e] - blk * NPB;
            bm &= bm - 1;
            float a[4][4];
            for (int i = 0; i < 4; i++)
                for (int o = 0; o < 4; o++) {
                    a[i][o] = 0.f;
                    for (int f = 0; f < 4; f++)
                        a[i][o] += __bfloat162float(Y[e * 4 + f]) * __bfloat162float(cg[i * 16 + f * 4 + o]);
                }
#pragma unroll 1
            for (int c = lane; c < 128; c += 32) {
                float pre = 0.f;
                for (int k = 0; k < 16; k++)
                    pre += __bfloat162float(ef[e * 16 + k]) * __bfloat162float(w_rad[k * 128 + c]);
                const float R = pre / (1.f + __expf(-pre));
                for (int o = 0; o < 4; o++) {
                    float acc = 0.f;
                    for (int i = 0; i < 4; i++) acc += __bfloat162float(x[(size_t)s * 512 + c * 4 + i]) * a[i][o];
                    atomicAdd(&sagg[loc * 512 + c * 4 + o], R * acc);
                }
            }
        }
    }
    __syncthreads();
}

__device__ __forceinline__ void init_barriers() {
    extern __shared__ __align__(1024) uint8_t smem[];
    const uint32_t sb = smem_u32(smem);
#pragma unroll
    for (int i = 0; i < 4 * NG; i++) {
        mbar_init(sb + i * STAGE + 4 * ROWP, 32);
        mbar_init(sb + i * STAGE + 4 * ROWP + 8, 2);
    }
}

template <int PHASES>
__global__ void __launch_bounds__(NTHR, 1)
tfn_kernel(const __nv_bfloat16* __restrict__ x, const int* __restrict__ src, const int* __restrict__ dst,
           const __nv_bfloat16* __restrict__ Y, const __nv_bfloat16* __restrict__ ef,
           const __nv_bfloat16* __restrict__ w_rad, const __nv_bfloat16* __restrict__ cg,
           const __nv_bfloat16* __restrict__ w_mix, __nv_bfloat16* __restrict__ out) {
    extern __shared__ __align__(1024) uint8_t smem[];
    const int tid = threadIdx.x, lane = tid & 31;
    const int warp = __shfl_sync(~0u, tid >> 5, 0);
    const int blk = blockIdx.x;
    uint32_t sb = smem_u32(smem);
    asm volatile("" : "+r"(sb));
    int* mi = reinterpret_cast<int*>(smem + SM_MISC);

    const int g = lane >> 2, t = lane & 3;
    const uint32_t dump = sb + SC_DUMP + lane * 4;
    int4 d1[2], s1[2];
    constexpr int nq = EPC / 4;
    const bool binner = (PHASES & 1) && blk < NSRC;
    if (binner) {
#pragma unroll
        for (int k = 0; k < 2; k++) {
            const int q = tid + k * NTHR;
            if (q < nq) {
                d1[k] = __ldg(reinterpret_cast<const int4*>(dst + blk * EPC) + q);
                s1[k] = __ldg(reinterpret_cast<const int4*>(src + blk * EPC) + q);
            }
        }
    }
    if (binner) {
        const uint32_t dmy = ((((blk & 3) * 8 + (tid & 7)) << 25) | (80 * 2560 + 1));
#pragma unroll
        for (int k = 0; k < 3; k++)
            if (k < 2 || warp < 1) sts128(sb + SC_MAIL + (tid + k * NTHR) * 16, dmy, dmy + (1u << 30), dmy, dmy + (1u << 30));
        if (tid <= NB / 4) sts128(sb + SC_CNT + tid * 16, 0, 0, 0, 0);
    }
    if (PHASES & 2) {
        if (tid == 160) { sts128(sb + SM_MISC, 0, 0, 0, 0); sts128(sb + SM_MISC + MI_NU * 4, 0, 0, 0, 0); }
        if (tid == 161) {
            mi[MI_SHIFT] = 0;
            *reinterpret_cast<int**>(mi + MI_SHIFT + 4) = g_lag[blk];
        }
        if (tid == 162) g_lag[blk][0] = g_lag[NB + blk][0] = 0;
        if (tid <= 21 * HS / 4) sts128(sb + SC_HIST + tid * 16, 0, 0, 0, 0);
        if (tid < 4 * UCAP) {
#pragma unroll
            for (int k = 0; k < 12; k++) sts32(sb + SM_REC + tid * REC + k * 4, k < 4 ? ~0u : (uint32_t)(blk * 4096 + tid * 8 + 7));
        }
    }
    __syncthreads();
    if (PHASES & 2) {
        if (warp >= 8) cp16(sb + SC_WR + ((tid - 256) ^ ((tid >> 4) & 6)) * 16, w_rad + (tid - 256) * 8);
        if (tid < 8) cp16(sb + SC_WR + 4096 + tid * 16, cg + tid * 8);
        asm volatile("cp.async.commit_group;" ::: "memory");
#pragma unroll
        for (int k = 0; k < 4; k++) {
            const int i = tid + k * NTHR, c = i >> 4;
            cp16(sb + SM_W + c * 256 + (((i & 15) ^ ((c & 2) | (((c >> 4) & 1) << 2))) << 4), w_mix + i * 8);
        }
    }
    if (binner) {
#pragma unroll
        for (int k = 0; k < 2; k++) {
            if (tid + k * NTHR < nq) {
                const uint32_t dd[4] = {(uint32_t)d1[k].x, (uint32_t)d1[k].y, (uint32_t)d1[k].z, (uint32_t)d1[k].w};
                const uint32_t ss[4] = {(uint32_t)s1[k].x, (uint32_t)s1[k].y, (uint32_t)s1[k].z, (uint32_t)s1[k].w};
                uint32_t own[4], rk[4], v[4];
#pragma unroll
                for (int j = 0; j < 4; j++) { own[j] = dd[j] / NPB; rk[j] = atoms_inc(sb + SC_CNT + own[j] * 4); }
#pragma unroll
                for (int j = 0; j < 4; j++) {
                    const uint32_t loc = dd[j] - own[j] * NPB, code = loc + ((loc * 216) >> 12);
                    v[j] = (ss[j] << 18) + code * 2560 + (tid + k * NTHR) * 4 + j + 1;
                    sts32(sb + SC_MAIL + own[j] * 128 + ((min(rk[j], 31u) * 4) ^ ((own[j] & 7) << 4)), v[j]);
                }
                if (max(max(rk[0], rk[1]), max(rk[2], rk[3])) >= 31) {
#pragma unroll
                    for (int j = 0; j < 4; j++)
                        if (rk[j] - 31 < 32)
                            asm volatile("st.relaxed.gpu.global.u32 [%0], %1;" ::"l"(g_mail2 + (own[j] * NSRC + blk) * 32 + rk[j] - 31), "r"(v[j]) : "memory");
                }
            }
        }
        __syncwarp();
        asm volatile("red.shared.max.u32 [%0], %1;" ::"r"(lane == 0 ? sb + SC_CNT + NB * 4 : dump), "r"(gtime()) : "memory");
        STAMP(1);
    }
    asm volatile("cp.async.wait_group 0;" ::: "memory");
    __syncthreads();
    if (binner) {
        const uint32_t hdr = 0xc0000000u | ((lds32(sb + SC_CNT + NB * 4) << 7) & 0x3ffff000u);
        uint4 mv[3];
        uint32_t mc[3];
#pragma unroll
        for (int k = 0; k < 3; k++)
            if (k < 2 || warp < 1) {
                const int j = tid + k * NTHR, own = j >> 3;
                mv[k] = lds128(sb + SC_MAIL + own * 128 + (((j ^ own) & 7) << 4));
                mc[k] = lds32(sb + SC_CNT + own * 4);
            }
#pragma unroll
        for (int k = 0; k < 3; k++)
            if (k < 2 || warp < 1) {
                const int j = tid + k * NTHR;
                asm volatile("st.relaxed.gpu.global.v4.u32 [%0], {%1,%2,%3,%4};" ::"l"(g_mail + ((j >> 3) * NSRC + blk) * 8 + (j & 7)),
                             "r"(mv[k].x), "r"(mv[k].y), "r"(mv[k].z), "r"((j & 7) == 7 ? hdr | mc[k] : mv[k].w) : "memory");
            }
        STAMP(2);
    }
    if (!(PHASES & 2)) return;
    const uint32_t tpub = (uint32_t)clock() + (blk < NSRC ? 0 : IDLE_EST);
    if (warp >= 7) {
        uint32_t f[4];
        if (warp >= 8) {
            uint32_t w[4];
#pragma unroll
            for (int j = 0; j < 4; j++)
                w[j] = mul_lo(lds32(sb + SC_WR + (2 * t + (j & 1) + (j >> 1) * 8) * 256 + ((((warp - 8) * 8 + g) * 4) ^ (t << 5))), 0x3f003f00u);
            f[0] = __byte_perm(w[0], w[1], 0x5410); f[1] = __byte_perm(w[0], w[1], 0x7632);
            f[2] = __byte_perm(w[2], w[3], 0x5410); f[3] = __byte_perm(w[2], w[3], 0x7632);
        } else {
#pragma unroll
            for (int i = 0; i < 4; i++) {
                const uint32_t ca = sb + SC_WR + 4096 + (i * 16 + (t & 1) * 8 + (g & 3)) * 2;
                f[i] = (lds16(ca) | (lds16(ca + 8) << 16)) & ((t >> 1) == (g >> 2) ? ~0u : 0u);
            }
        }
        const uint32_t d = sb + (warp == 7 ? 2 * ROWP : ((warp - 8) >> 2) * ROWP + (warp & 3) * 512) + lane * 16;
#pragma unroll
        for (int k = 0; k < 4; k++) sts128(d + k * NG * STAGE, f[0], f[1], f[2], f[3]);
    }
    asm volatile("cp.async.wait_all;" ::: "memory");
    __syncwarp();
#pragma unroll
    for (int k = 0; k < 2; k++) {
        const int i = (tid & ~1) + ((tid & 1) * 2 + k) * NTHR, c = i >> 4;
        const uint32_t a0 = sb + SM_W + c * 256 + (((i & 15) ^ ((c & 3) | (((c >> 4) & 1) << 2))) << 4);
        const uint32_t o = (tid & 1) << 4;
        uint4 u = lds128((a0 & ~16u) ^ o), v = lds128((a0 | 16u) ^ o);
        if (tid & 1) { const uint4 w = u; u = v; v = w; }
        const uint32_t s0 = (tid & 1) ? 0x7632 : 0x5410, s1 = s0 ^ 0x2222;
        sts128(a0 ^ o, __byte_perm(u.x, u.y, s0), __byte_perm(u.z, u.w, s0), __byte_perm(v.x, v.y, s0), __byte_perm(v.z, v.w, s0));
        sts128(a0 ^ o ^ 16, __byte_perm(u.x, u.y, s1), __byte_perm(u.z, u.w, s1), __byte_perm(v.x, v.y, s1), __byte_perm(v.z, v.w, s1));
    }

    uint32_t en[8], hr[8], rk[8], em[8];
    int xc[2];
    const uint32_t tref = __shfl_sync(~0u, gtime() >> 5, 0);
    {
        uint4* mp = g_mail + blk * NSRC * 8 + tid;
        int it = 0;
        bool ok;
        while ((int)((uint32_t)clock() - tpub) < POLL_DELAY) {}
        do {
#pragma unroll
            for (int k = 0; k < 2; k++)
                    asm volatile("ld.relaxed.gpu.global.v4.u32 {%0,%1,%2,%3}, [%4];"
                                 : "=r"(en[4 * k]), "=r"(en[4 * k + 1]), "=r"(en[4 * k + 2]), "=r"(en[4 * k + 3])
                                 : "l"(mp + k * NTHR) : "memory");
            uint32_t m = ~0u;
#pragma unroll
            for (int i = 0; i < 8; i++) m = min(m, en[i]);
            ok = __all_sync(~0u, m != 0);
            if (++it > (1 << 20)) __trap();
        } while (!ok);
        STAMP(3);
        const bool hd = (lane & 7) == 7;
        const uint32_t h0 = en[3], h1 = en[7];
        if (hd) en[3] = en[7] = ((64 + (tid >> 5)) << 25) | (80 * 2560 + 1);
        const uint32_t e0 = (tid >> 3) * EPC * 8 - 8;
#pragma unroll
        for (int i = 0; i < 8; i++) {
            const uint32_t w = en[i] & 0x3ffff, code = ((w >> 9) * 13108) >> 16;
            hr[i] = sb + SC_HIST + ((code >> 2) * HS + (en[i] >> 25)) * 4;
            rk[i] = atoms_inc(hr[i]);
            em[i] = (e0 + (i >> 2) * (NTHR / 8 * EPC * 8) + (w - code * 2560) * 8) | (code & 3);
        }
        int dt = hd ? max((int)(((h0 >> 12) - tref) << 14), (int)(((h1 >> 12) - tref) << 14)) >> 14 : -(1 << 20);
        xc[0] = hd ? max((int)(h0 & 0xfff) - 31, 0) : 0;
        xc[1] = hd ? max((int)(h1 & 0xfff) - 31, 0) : 0;
        dt = __reduce_max_sync(~0u, dt);
        asm volatile("red.shared.max.u32 [%0], %1;" ::"r"(lane == 0 ? sb + SM_MISC + MI_TMAX * 4 : dump + 128), "r"(tref + dt + (1u << 27)) : "memory");
        if (xc[0] | xc[1]) {
#pragma unroll
            for (int k = 0; k < 2; k++) {
                const int slot = atomicAdd(&mi[MI_XN], xc[k]);
                for (int r = 0; r < xc[k] && slot + r < 32; r++)
                    reinterpret_cast<uint32_t*>(smem + SC_XTRA)[slot + r] = ((tid + k * NTHR) >> 3) * 32 + r;
            }
        }
#pragma unroll
        for (int k = 0; k < 2; k++)
            mp[k * NTHR] = make_uint4(0, 0, 0, 0);
    }
    __syncthreads();
    STAMP(4);
    uint32_t* hist = reinterpret_cast<uint32_t*>(smem + SC_HIST);
    const int xn = mi[MI_XN];
    uint32_t xi = 0, xv = 1;
    if (warp < 10) {
        uint32_t* hp = hist + (warp * 2 + (lane >> 4)) * HS + (lane & 15) * 5;
        int c[5], s = 0;
#pragma unroll
        for (int j = 0; j < 5; j++) { c[j] = hp[j]; s += c[j]; }
        int inc = s;
#pragma unroll
        for (int o = 1; o < 16; o <<= 1) { int v = __shfl_up_sync(~0u, inc, o, 16); if ((lane & 15) >= o) inc += v; }
        int base = 0;
        if ((lane & 15) == 15) {
            const int tm = (warp * 2 + (lane >> 4)) / 5;
            base = tm * 256 + atomicAdd(&mi[MI_NU + tm], (inc + 3) >> 2);
            hp[5] = (base + ((inc + 3) >> 2)) << 16;
        }
        const int tot = __shfl_sync(~0u, inc, 15, 16);
        base = __shfl_sync(~0u, base, 15, 16);
        int ex = inc - s;
#pragma unroll
        for (int j = 0; j < 5; j++) {
            hp[j] = (base * 4 + ex) | ((base + ((ex == tot ? ex + 3 : ex + 1) >> 2)) << 16);
            ex += c[j];
        }
    } else if (warp == 10) {
        if (lane < xn) {
            xi = reinterpret_cast<const uint32_t*>(smem + SC_XTRA)[lane];
            asm volatile("ld.relaxed.gpu.global.u32 %0, [%1];" : "=r"(xv) : "l"(g_mail2 + blk * NSRC * 32 + xi) : "memory");
        }
    } else if (warp == 12) {
        if (lane == 0) init_barriers();
    } else if (warp == 11) {
        sts32(sb + SC_GPOS + (GDUMMY + lane) * 4, (uint32_t)(4 * UCAP * REC + 128) * 0x10001u);
#pragma unroll
        for (int k = 0; k < 3; k++) hist[20 * HS + min(lane + 32 * k, NBK)] = GDUMMY * 4;
        constexpr int start_ns = START_NS;
        if (lane == 0) mi[MI_T0] = (uint32_t)clock() + (((int)(((uint32_t)mi[MI_TMAX] << 5) + start_ns - gtime()) * 31) >> 4);
    }
    constexpr int pace = PACE_Q8, p1 = PACE_HEAD, b1 = HEAD_BK, p2 = PACE_TAIL, b2 = TAIL_BK, lead = PACE_LEAD;
    auto sched = [&](int b) { return b * pace - min(b, b1) * (pace - p1) - max(b - b2, 0) * (pace - p2) - lead; };
    const int mteam = tid / NBK, mb = tid - mteam * NBK;
    int tb0 = sched(mb);
    float tbw = (float)(sched(mb + 1) - tb0);
    uint32_t mh = sb + SC_HIST + (mteam * 5 * HS + mb) * 4 + 2, mh0 = sb + SC_HIST + mteam * 5 * HS * 4 + 2;
    asm volatile("" : "+r"(tb0), "+f"(tbw), "+r"(mh), "+r"(mh0));
    __syncthreads();
    STAMP(10);
    int myng = mi[MI_NU + (lane & 3)];
    const bool ovf = __any_sync(~0u, myng + xn > 2 * (UCAP - 4) || xn > 32);
    if (!ovf) {
        if (warp < 10) {
            int lo[5], n[5], pos = mteam * UCAP * 2, nsum = 0;
#pragma unroll
            for (int q = 0; q < 5; q++) {
                lo[q] = lds16(mh + q * HS * 4);
                n[q] = lds16(mh + q * HS * 4 + 4) - lo[q];
                pos += lo[q] - lds16(mh0 + q * HS * 4);
                nsum += n[q];
            }
            const int step = __float2int_rz(__fdividef(tbw, (float)max(nsum, 1)));
            const int tb = tb0 + (step >> 1) - pos * step;
            const uint32_t t0 = mi[MI_T0];
            auto emit = [&](int q, int r, int pq) {
                const uint32_t ro = (pq >> 1) * REC, par = pq & 1;
                asm volatile("{\n.reg .pred p, e;\nsetp.lt.s32 p, %0, %1;\nsetp.eq.and.u32 e, %2, 0, p;\n"
                             "@p st.shared.u32 [%3], %4;\n@p st.shared.u8 [%5+48], %6;\n@e st.shared.u16 [%5+102], %7;\n}"
                             ::"r"(r), "r"(n[q]), "r"(par), "r"(sb + SC_GPOS + (lo[q] + r) * 4),
                               "r"(ro * 0x10001u + par * 0x40002u + (REC | (16 << 16))), "r"(sb + SM_REC + ro + par), "r"(q),
                               "h"((uint16_t)((t0 + max(tb + pq * step, 0)) >> 2)) : "memory");
            };
#pragma unroll
            for (int q = 0, pq = pos; q < 5; pq += n[q], q++) emit(q, 0, pq);
#pragma unroll
            for (int q = 0; q < 5; pos += n[q], q++)
#pragma unroll 1
                for (int r = 1; __any_sync(~0u, r < n[q]); r++) emit(q, r, pos + r);
        } else if (warp == 10) {
            for (int n = 0; __any_sync(~0u, xv == 0); n++) {
                if (xv == 0) asm volatile("ld.relaxed.gpu.global.u32 %0, [%1];" : "=r"(xv) : "l"(g_mail2 + blk * NSRC * 32 + xi) : "memory");
                if (n > (1 << 20)) __trap();
            }
            const uint32_t w = xv & 0x3ffff, code = ((w >> 9) * 13108) >> 16, xt = lane < xn ? code / 20 : 4;
            const uint32_t same = __match_any_sync(~0u, xt);
            const int pq = __shfl_sync(~0u, myng, xt & 3) + __popc(same & ((1u << lane) - 1));
#pragma unroll
            for (int q = 0; q < 4; q++) {
                const int c = __popc(__ballot_sync(~0u, xt == q));
                if (lane == q) myng += c;
            }
            if (lane < xn) {
                g_mail2[blk * NSRC * 32 + xi] = 0;
                const uint32_t a = sb + SM_REC + (xt * UCAP + (pq >> 1)) * REC;
                sts16(a + REC + (pq & 1) * 2, xv >> 18);
                sts32(a + 16 + (pq & 1) * 4, (((xi >> 5) * EPC + w - code * 2560 - 1) * 8) | (code & 3));
                sts8(a + 48 + (pq & 1), (code >> 2) - xt * 5);
                if (!(pq & 1)) sts16(a + REC + 50, ((uint32_t)mi[MI_T0] + sched(NBK - 2)) >> 2);
            }
            if (lane < 4) {
                const uint32_t a = sb + SM_REC + (lane * UCAP + (myng >> 1)) * REC + 48;
                if (myng & 1) sts8(a + 1, 0);
                sts16(a + (myng & 1) * REC, 5);
                mi[MI_END + lane] = (myng + 1) >> 1;
            }
        }
#pragma unroll
        for (int i = 0; i < 8; i++) {
            const uint32_t p = rk[i] + lds16(hr[i]);
            hr[i] = sb + SC_GPOS + (p & ~3u);
            rk[i] = (p & 3) * 0x80004u;
        }
        __syncthreads();
        STAMP(11);
#pragma unroll
        for (int i = 0; i < 8; i++) rk[i] += lds32(hr[i]);
#pragma unroll
        for (int i = 0; i < 8; i++) {
            sts16(sb + SM_REC + (rk[i] & 0xffff), en[i] >> 18);
            sts32(sb + SM_REC + (rk[i] >> 16), em[i]);
        }
    } else {
        if (tid < 4) {
            sts16(sb + SM_REC + tid * UCAP * REC + 48, 5);
            mi[MI_END + tid] = 0;
        }
        generic_path(reinterpret_cast<float*>(smem), x, src, dst, Y, ef, w_rad, cg, xc[0], xc[1]);
    }

    __syncwarp();
    if (warp >= 8) {
        asm volatile("bar.sync 3, 512;" ::: "memory");
        asm volatile("setmaxnreg.dec.sync.aligned.u32 24;");
        const int team = warp & 3;
        if (ovf) {
            asm volatile("bar.sync 2;" ::: "memory");
            if (tid == 256) init_barriers();
            asm volatile("bar.sync 2;" ::: "memory");
        }
        STAMP(5);
        const uint32_t ring = sb + SM_RING + team * NG * STAGE;
        const uint32_t q = lane >> 3, c = lane & 7, rec = sb + SM_REC + team * UCAP * REC;
        __syncwarp();
        producer_loop(reinterpret_cast<const char*>(x) + (lane & 15) * 16, reinterpret_cast<const char*>(ef) + (c & 1) * 16, Y,
                      q * ROWP + ((c ^ (q << 1)) << 4), q * 4 + (c & 2) * 8, (c & 1) * 2 + (c >> 2), ring, rec,
                      rec + (mi[MI_END + team] + 1) * REC, warp - 8, sb + SM_MISC + MI_SHIFT * 4,
                      (lane >> 4) * ROWP + (((lane & 15) ^ ((lane >> 4) << 1)) << 4));
        uint32_t ln, sb2, cta;
        asm volatile("mov.u32 %0, %%tid.x;\nmov.u32 %1, %%ctaid.x;\nmov.u32 %2, %%dynamic_smem_size;" : "=r"(ln), "=r"(cta), "=r"(sb2));
        if (cta == NB - 1 && ln >= NTHR - 32) {
            ln &= 31;
            sb2 += smem_u32(smem) - SM_TOTAL + SM_MISC;
            constexpr int lead = LEAD_CLK >> 2;
            const uint32_t tend = lds32(sb2 + MI_T0 * 4) + 70 * PACE_Q8;
            int sh = 0;
            for (int n = 0; n < 199 && (int)((uint32_t)clock() - tend - (sh >> 14)) < 0; n++) {
                int v;
                asm volatile("ld.relaxed.gpu.global.s32 %0, [%1];" : "=r"(v) : "l"(g_lag[ln * 4]) : "memory");
                const int err = (__reduce_add_sync(~0u, max(v, 0)) >> 5) - lead;
                const int old = sh;
                sh = min(max((sh >> 16) + (err * (err > 0 ? FB_GAIN : FB_DOWN) >> 3), FB_MIN), 2500) << 16;
                if (sh == old) continue;
#pragma unroll
                for (int k = 0; k < 5; k++)
                    asm volatile("st.relaxed.gpu.global.s32 [%0], %1;" ::"l"(g_lag[NB + min(ln + 32 * k, NB - 1u)]), "r"(sh) : "memory");
            }
        }
    } else {
        asm volatile("bar.arrive 3, 512;" ::: "memory");
        int team;
        {
            const int n0 = mi[MI_END], n1 = mi[MI_END + 1], n2 = mi[MI_END + 2], n3 = mi[MI_END + 3];
            const int d1 = abs(n0 + n1 - n2 - n3), d2 = abs(n0 + n2 - n1 - n3), d3 = abs(n0 + n3 - n1 - n2);
            const uint32_t perm = d1 < min(d2, d3) ? 0x3120 : d3 < d2 ? 0x2310 : 0x3210;
            team = __shfl_sync(~0u, (perm >> ((warp >> 1) * 4)) & 3, 0);
        }
        const int h = warp & 1;
        asm volatile("setmaxnreg.inc.sync.aligned.u32 232;");
        uint32_t ring = sb + SM_RING + team * NG * STAGE;
        uint32_t wf[4][4], cgf[4];
#pragma unroll
        for (int m = 0; m < 5; m++) {
            const uint4 v = lds128(ring + (m < 4 ? h * ROWP + m * 512 : 2 * ROWP) + lane * 16);
            uint32_t* f = m < 4 ? wf[m] : cgf;
            f[0] = v.x; f[1] = v.y; f[2] = v.z; f[3] = v.w;
        }
        float acc[5][4][2][4];
        if (!ovf) {
#pragma unroll
            for (int l = 0; l < 5; l++)
#pragma unroll
                for (int m = 0; m < 4; m++)
#pragma unroll
                    for (int p = 0; p < 2; p++)
#pragma unroll
                        for (int r = 0; r < 4; r++) acc[l][m][p][r] = 0.f;
        } else {
            const float* sagg = reinterpret_cast<const float*>(smem);
#pragma unroll
            for (int l = 0; l < 5; l++)
#pragma unroll
                for (int m = 0; m < 4; m++)
#pragma unroll
                    for (int p = 0; p < 2; p++)
#pragma unroll
                        for (int r = 0; r < 4; r++) {
                            int nd = l * 4 + (g >> 2) + (r >> 1) * 2;
                            int ch = h * 64 + m * 16 + 4 * t + (r & 1) * 2 + p;
                            acc[l][m][p][r] = nd < 19 ? sagg[(team * 19 + nd) * 512 + ch * 4 + (g & 3)] : 0.f;
                        }
            asm volatile("bar.sync 2;" ::: "memory");
            asm volatile("bar.sync 2;" ::: "memory");
        }
        const uint32_t xoff = t * ROWP + h * 512 + ((g ^ (t << 1)) << 4);
        const uint32_t mat = lane >> 3, mhi = (lane >> 2) & 1;
        const bool isy = mat < 2;
        const uint32_t ml = isy ? (t & 2) + (mat & 1) : t;
        const uint32_t moff = ml * ROWP + 2048 + (((isy ? 4 + 2 * mhi + (t & 1) : 2 * mhi + mat - 2) ^ (ml << 1)) << 4);
        __syncwarp();
        consumer_loop(acc, wf, cgf, xoff, ring, moff, sb + SM_REC + team * UCAP * REC);
        {
        int lane_;
        asm volatile("mov.u32 %0, %%laneid;" : "=r"(lane_));
        const int lane = lane_, g = lane >> 2, t = lane & 3;
        const uint32_t sb = ring - team * NG * STAGE;
        STAMP(7);
        asm volatile("bar.sync %0, 64;" ::"r"(4 + team) : "memory");
        {
            const int rr = ((g & 3) >> 1) * 8 + (g >> 2) * 2 + (g & 1);
#pragma unroll
            for (int l = 0; l < 5; l++)
#pragma unroll
                for (int hi = 0; hi < 2; hi++) {
                    const int R = l * 16 + rr + hi * 4;
                    const uint32_t a = sb + team * AGGT + h * 10240 + R * 128;
#pragma unroll
                    for (int c = 0; c < 2; c++) {
                        const int m = 2 * c;
                        sts128(a + (((2 * t + c) ^ (R & 7)) << 4),
                               pack_bf16(acc[l][m][0][2 * hi], acc[l][m][1][2 * hi]),
                               pack_bf16(acc[l][m][0][2 * hi + 1], acc[l][m][1][2 * hi + 1]),
                               pack_bf16(acc[l][m + 1][0][2 * hi], acc[l][m + 1][1][2 * hi]),
                               pack_bf16(acc[l][m + 1][0][2 * hi + 1], acc[l][m + 1][1][2 * hi + 1]));
                    }
                }
        }
        asm volatile("fence.proxy.async.shared::cta;" ::: "memory");
        uint32_t wa[8][4];
        {
            const int r = lane & 7, k = (lane >> 4) * 8 + r;
            const int chunk = (2 * warp + ((lane >> 3) & 1)) ^ r;
#pragma unroll
            for (int ks = 0; ks < 8; ks++) {
                const int c = (ks >> 2) * 64 + 16 * (k >> 2) + 4 * (ks & 3) + (k & 3);
                asm volatile("ldmatrix.sync.aligned.m8n8.x4.trans.shared.b16 {%0,%1,%2,%3}, [%4];"
                             : "=r"(wa[ks][0]), "=r"(wa[ks][1]), "=r"(wa[ks][2]), "=r"(wa[ks][3])
                             : "r"(sb + SM_W + c * 256 + (chunk << 4)));
            }
        }
        asm volatile("bar.sync 1, 256;" ::: "memory");
        STAMP(8);
        const int sl = (lane & 7) * 4 + (lane >> 3);
        __nv_bfloat16* op = out + (size_t)(blk * NPB + (lane >> 3)) * 512 + warp * 64 + (lane & 7) * 8;
        const int nleft = N_NODES - blk * NPB - (lane >> 3);
        uint32_t pk[20];
        auto store = [&](int tm) {
#pragma unroll
            for (int l = 0; l < 5; l++) {
                uint4 v;
                v.x = __shfl_sync(~0u, pk[4 * l + 0], sl);
                v.y = __shfl_sync(~0u, pk[4 * l + 1], sl);
                v.z = __shfl_sync(~0u, pk[4 * l + 2], sl);
                v.w = __shfl_sync(~0u, pk[4 * l + 3], sl);
                asm volatile("{\n.reg .pred p;\nsetp.lt.u32 p, %5, %6;\n@p st.global.v4.u32 [%0], {%1,%2,%3,%4};\n}"
                             ::"l"(op + (tm * 19 + l * 4) * 512), "r"(v.x), "r"(v.y), "r"(v.z), "r"(v.w), "r"(tm * 19 + l * 4),
                               "r"(l < 4 || lane < 24 ? nleft : 0) : "memory");
            }
        };
        if (warp >= 4) asm volatile("bar.sync 10, 256;" ::: "memory");
#pragma unroll 1
        for (int tm = 0; tm < 4; tm++) {
            float o[40];
            asm volatile("wgmma.fence.sync.aligned;" ::: "memory");
#pragma unroll
            for (int ks = 0; ks < 8; ks++) {
                const uint32_t a = sb + tm * AGGT + (ks >> 2) * 10240 + (ks & 3) * 32;
                const uint64_t desc = (uint64_t)((a & 0x3ffff) >> 4) | (1ull << 16) | (64ull << 32) | (1ull << 62);
                wgmma_n80(o, wa[ks], desc, ks);
            }
            asm volatile("wgmma.commit_group.sync.aligned;" ::: "memory");
            if (tm == 0 && warp < 4) asm volatile("bar.arrive 10, 256;" ::: "memory");
            asm volatile("wgmma.wait_group.sync.aligned 0;" ::: "memory");
#pragma unroll
            for (int i = 0; i < 40; i++) asm volatile("" : "+f"(o[i])::"memory");
#pragma unroll
            for (int l = 0; l < 5; l++) {
                pk[4 * l + 0] = pack_bf16(o[8 * l + 0], o[8 * l + 1]);
                pk[4 * l + 1] = pack_bf16(o[8 * l + 4], o[8 * l + 5]);
                pk[4 * l + 2] = pack_bf16(o[8 * l + 2], o[8 * l + 3]);
                pk[4 * l + 3] = pack_bf16(o[8 * l + 6], o[8 * l + 7]);
            }
            store(tm);
        }
        STAMP(9);
        }
    }
}

}

extern "C" void kernel_launch(void* const* d_in, const int* in_sizes, int n_in, void* d_out, int out_size) {
    (void)in_sizes; (void)n_in; (void)out_size;
    const __nv_bfloat16* x = (const __nv_bfloat16*)d_in[0];
    const int* src = (const int*)d_in[1];
    const int* dst = (const int*)d_in[2];
    const __nv_bfloat16* Y = (const __nv_bfloat16*)d_in[3];
    const __nv_bfloat16* ef = (const __nv_bfloat16*)d_in[4];
    const __nv_bfloat16* w_rad = (const __nv_bfloat16*)d_in[5];
    const __nv_bfloat16* cg = (const __nv_bfloat16*)d_in[6];
    const __nv_bfloat16* w_mix = (const __nv_bfloat16*)d_in[7];
    __nv_bfloat16* out = (__nv_bfloat16*)d_out;

    static int sms = 0;
    if (sms == 0) {
        int dev = 0;
        cudaGetDevice(&dev);
        cudaDeviceGetAttribute(&sms, cudaDevAttrMultiProcessorCount, dev);
        cudaFuncSetAttribute(tfn_kernel<3>, cudaFuncAttributeMaxDynamicSharedMemorySize, SM_TOTAL);
        cudaFuncSetAttribute(tfn_kernel<1>, cudaFuncAttributeMaxDynamicSharedMemorySize, SM_TOTAL);
        cudaFuncSetAttribute(tfn_kernel<2>, cudaFuncAttributeMaxDynamicSharedMemorySize, SM_TOTAL);
    }
    if (sms >= NB) {
        tfn_kernel<3><<<NB, NTHR, SM_TOTAL>>>(x, src, dst, Y, ef, w_rad, cg, w_mix, out);
    } else {
        tfn_kernel<1><<<NB, NTHR, SM_TOTAL>>>(x, src, dst, Y, ef, w_rad, cg, w_mix, out);
        tfn_kernel<2><<<NB, NTHR, SM_TOTAL>>>(x, src, dst, Y, ef, w_rad, cg, w_mix, out);
    }
}
```

```cpp
#include <cuda_runtime.h>
#include <cuda_bf16.h>
#include <stdint.h>

namespace {

constexpr int N_NODES = 10000;
constexpr int N_EDGES = 320000;
constexpr int NB      = 132;
constexpr int NPB     = 76;
constexpr int NSRC    = 128;
constexpr int EPC     = N_EDGES / NSRC;
constexpr int NTHR    = 512;
constexpr int NG      = 5;
constexpr int ROWP    = 2176;
constexpr int STAGE   = 4 * ROWP + 128;
constexpr int UCAP    = 104;
constexpr int REC     = 52;
constexpr int NBK     = 80;
constexpr int HS      = 81;

#define PACE_Q8 635
#define PACE_LEAD 300
#define PACE_HEAD 705
#define HEAD_BK 10
#define PACE_TAIL 610
#define TAIL_BK 66
#define IDLE_EST 900
#define POLL_DELAY 1280
#define LEAD_CLK 140
#define FB_GAIN 24
#define FB_DOWN 4
#define FB_MIN 0
#define START_NS 3150

constexpr int SM_RING  = 0;
constexpr int SM_W     = 4 * NG * STAGE;
constexpr int SM_REC   = SM_W + 32768;
constexpr int SM_MISC  = SM_REC + 4 * UCAP * REC;
constexpr int SM_TOTAL = SM_MISC + 224;
constexpr int SC_MAIL  = 1 * STAGE;
constexpr int SC_CNT   = 3 * STAGE;
constexpr int SC_DUMP  = 3 * STAGE + 1024;
constexpr int SC_XTRA  = 3 * STAGE + 2048;
constexpr int SC_HIST  = 4 * STAGE;
constexpr int SC_GPOS  = 6 * STAGE;
constexpr int SC_WR    = 7 * STAGE;
constexpr int GDUMMY   = 1024;
constexpr int AGGT     = (NG * STAGE + 1023) / 1024 * 1024;
static_assert(3 * AGGT + 20480 <= 4 * NG * STAGE, "agg tile inside the team's ring");
static_assert(4 * ROWP + 16 <= 10240 && STAGE + 4 * ROWP >= 3 * (AGGT - NG * STAGE) + 10240 && STAGE + 4 * ROWP + 16 <= 20480 &&
              2 * STAGE + 4 * ROWP >= 3 * (AGGT - NG * STAGE) + 20480, "half h of the tile covers the barriers of stage h only");
static_assert(NPB * 512 * 4 <= 4 * NG * STAGE, "slow tile");
static_assert(SM_TOTAL <= 232448, "smem");
static_assert(SM_REC % 16 == 0 && (4 * UCAP * REC) % 16 == 0 && SM_MISC % 16 == 0, "align");
constexpr int MI_XN = 0;
constexpr int MI_TMAX = 2;
constexpr int MI_SHIFT = 48;
constexpr int MI_NU = 8;
constexpr int MI_END = 28;
constexpr int MI_T0 = 3;

__device__ __align__(128) uint4 g_mail[NB * NSRC * 8];
__device__ __align__(128) uint32_t g_mail2[NB * NSRC * 32];
__device__ __align__(128) int g_lag[2 * NB][32];
#define STAMP(k)

__device__ __forceinline__ uint32_t smem_u32(const void* p) { return (uint32_t)__cvta_generic_to_shared(p); }
__device__ __forceinline__ uint32_t atoms_inc(uint32_t a) {
    uint32_t r;
    asm volatile("atom.shared.add.u32 %0, [%1], 1;" : "=r"(r) : "r"(a) : "memory");
    return r;
}
__device__ __forceinline__ void sts32(uint32_t a, uint32_t v) { asm volatile("st.shared.u32 [%0], %1;" ::"r"(a), "r"(v) : "memory"); }
__device__ __forceinline__ void sts16(uint32_t a, uint32_t v) { asm volatile("st.shared.u16 [%0], %1;" ::"r"(a), "h"((uint16_t)v) : "memory"); }
__device__ __forceinline__ void sts8(uint32_t a, uint32_t v) { asm volatile("st.shared.u8 [%0], %1;" ::"r"(a), "r"(v) : "memory"); }
__device__ __forceinline__ uint32_t lds32(uint32_t a) { uint32_t v; asm volatile("ld.shared.u32 %0, [%1];" : "=r"(v) : "r"(a)); return v; }
__device__ __forceinline__ uint32_t lds16(uint32_t a) { uint32_t v; asm volatile("ld.shared.u16 %0, [%1];" : "=r"(v) : "r"(a)); return v; }
__device__ __forceinline__ void cp16(uint32_t d, const void* p) {
    asm volatile("cp.async.cg.shared.global [%0], [%1], 16;" ::"r"(d), "l"(p) : "memory");
}
__device__ __forceinline__ uint32_t gtime() {
    uint32_t t;
    asm volatile("mov.u32 %0, %%globaltimer_lo;" : "=r"(t));
    return t;
}
__device__ __forceinline__ void mbar_init(uint32_t bar, int cnt) {
    asm volatile("mbarrier.init.shared.b64 [%0], %1;" ::"r"(bar), "r"(cnt) : "memory");
}
__device__ __forceinline__ void mbar_inval(uint32_t bar) {
    asm volatile("mbarrier.inval.shared.b64 [%0];" ::"r"(bar) : "memory");
}
__device__ __forceinline__ uint4 lds128(uint32_t a) {
    uint4 v;
    asm volatile("ld.shared.v4.u32 {%0,%1,%2,%3}, [%4];" : "=r"(v.x), "=r"(v.y), "=r"(v.z), "=r"(v.w) : "r"(a));
    return v;
}
__device__ __forceinline__ void sts128(uint32_t a, uint32_t x, uint32_t y, uint32_t z, uint32_t w) {
    asm volatile("st.shared.v4.u32 [%0], {%1,%2,%3,%4};" ::"r"(a), "r"(x), "r"(y), "r"(z), "r"(w) : "memory");
}
__device__ __forceinline__ uint32_t pack_bf16(float lo, float hi) {
    uint32_t r;
    asm("cvt.rn.bf16x2.f32 %0, %1, %2;" : "=r"(r) : "f"(hi), "f"(lo));
    return r;
}
__device__ __forceinline__ uint32_t mul_lo(uint32_t v, uint32_t r) {
    __nv_bfloat162 a = *reinterpret_cast<__nv_bfloat162*>(&v), b = *reinterpret_cast<__nv_bfloat162*>(&r);
    __nv_bfloat162 c = __hmul2(a, __low2bfloat162(b));
    return *reinterpret_cast<uint32_t*>(&c);
}
__device__ __forceinline__ void wgmma_n80(float (&d)[40], const uint32_t (&a)[4], uint64_t desc, int scale_d) {
    asm volatile("{\n.reg .pred p;\nsetp.ne.b32 p, %45, 0;\n"
        "wgmma.mma_async.sync.aligned.m64n80k16.f32.bf16.bf16 "
        "{%0,%1,%2,%3,%4,%5,%6,%7,%8,%9,%10,%11,%12,%13,%14,%15,%16,%17,%18,%19,"
        "%20,%21,%22,%23,%24,%25,%26,%27,%28,%29,%30,%31,%32,%33,%34,%35,%36,%37,%38,%39}, "
        "{%40,%41,%42,%43}, %44, p, 1, 1, 0;\n}"
        : "+f"(d[0]), "+f"(d[1]), "+f"(d[2]), "+f"(d[3]), "+f"(d[4]), "+f"(d[5]), "+f"(d[6]), "+f"(d[7]),
          "+f"(d[8]), "+f"(d[9]), "+f"(d[10]), "+f"(d[11]), "+f"(d[12]), "+f"(d[13]), "+f"(d[14]), "+f"(d[15]),
          "+f"(d[16]), "+f"(d[17]), "+f"(d[18]), "+f"(d[19]), "+f"(d[20]), "+f"(d[21]), "+f"(d[22]), "+f"(d[23]),
          "+f"(d[24]), "+f"(d[25]), "+f"(d[26]), "+f"(d[27]), "+f"(d[28]), "+f"(d[29]), "+f"(d[30]), "+f"(d[31]),
          "+f"(d[32]), "+f"(d[33]), "+f"(d[34]), "+f"(d[35]), "+f"(d[36]), "+f"(d[37]), "+f"(d[38]), "+f"(d[39])
        : "r"(a[0]), "r"(a[1]), "r"(a[2]), "r"(a[3]), "l"(desc), "r"(scale_d));
}

__device__ __forceinline__ void producer_loop(const void* xl, const void* efl, const void* Y, uint32_t xd, uint32_t oef,
                                              uint32_t ysel, uint32_t ring, uint32_t rec, uint32_t rlast, uint32_t odd,
                                              uint32_t lag, uint32_t xh) {
    asm volatile(
        "{\n"
        ".reg .b32 w, em, ey, cu, d, t, u, n, sa, ph, rp, rend, rlast, dy, sv, lag, lv, w2, w3, w4;\n"
        ".reg .b16 tg;\n"
        ".reg .b64 pa, pb, pc, pd;\n"
        ".reg .pred lo, z, q, e, zb, fbk;\n"
        "redux.sync.or.b32 sa, %6, 0xffffffff;\n"
        "redux.sync.or.b32 rp, %7, 0xffffffff;\n"
        "redux.sync.or.b32 rlast, %8, 0xffffffff;\n"
        "redux.sync.or.b32 lag, %11, 0xffffffff;\n"
        "setp.eq.u32 fbk, %9, 0;\n"
        "add.u32 rend, sa, 44160;\n"
        "and.b32 t, %5, 1;\n"
        "setp.eq.u32 lo, t, 0;\n"
        "mov.u32 ph, 1;\n"
        "setp.ge.u32 q, %9, 4;\n"
        "@q bra.uni PODD_%=;\n"
        "add.u32 t, rp, %4;\n"
        "ld.shared.u32 em, [t+16];\n"
        "and.b32 t, em, 0xfffffff8;\n"
        "mad.wide.u32 pa, t, 4, %1;\n"
        "add.u32 d, sa, %3;\n"
        "@lo cp.async.cg.shared.global [d+2048], [pa], 16;\n"
        "cp.async.mbarrier.arrive.noinc.shared.b64 [sa+8704];\n"
        "add.u32 rp, rp, 52;\n"
        "add.u32 sa, sa, 8832;\n"
        "PODD_%=:\n"
        "add.u32 rp, rp, 52;\n"
        "add.u32 sa, sa, 8832;\n"
        "shr.u32 t, %4, 1;\n"
        "and.b32 t, t, 4;\n"
        "add.u32 t, t, rp;\n"
        "ld.shared.u32 w, [t];\n"
        "ld.shared.u32 w2, [t+8];\n"
        "add.u32 t, rp, %4;\n"
        "ld.shared.u32 em, [t+16];\n"
        "ld.shared.u32 ey, [t+-36];\n"
        "ld.shared.u32 cu, [rp+48];\n"
        "ld.volatile.shared.u32 sv, [lag];\n"
        "setp.eq.u32 e, sa, sa;\n"
        "setp.lt.u32 q, rp, rlast;\n"
        "@!q bra.uni PF_%=;\n"
        "PL_%=:\n"
        "add.u32 cu, cu, sv;\n"
        "mov.u32 u, %%clock;\n"
        "shl.b32 u, u, 14;\n"
        "sub.u32 u, u, cu;\n"
        "setp.ge.and.s32 q, u, 0, e;\n"
        "@q bra.uni PGO_%=;\n"
        "mov.u32 n, 0;\n"
        "PW1_%=:\n"
        "@e bra.uni PW2_%=;\n"
        "mbarrier.try_wait.parity.shared.b64 e, [sa+8712], ph;\n"
        "add.u32 n, n, 1;\n"
        "setp.lt.u32 q, n, 4194304;\n"
        "@q bra.uni PW1_%=;\n"
        "trap;\n"
        "PW2_%=:\n"
        "mov.u32 u, %%clock;\n"
        "shl.b32 u, u, 14;\n"
        "sub.u32 u, u, cu;\n"
        "setp.lt.s32 q, u, 0;\n"
        "@q bra.uni PW2_%=;\n"
        "PGO_%=:\n"
        "st.volatile.shared.u32 [lag+24], u;\n"
        "and.b32 t, em, 0xfffffff8;\n"
        "mad.wide.u32 pa, t, 4, %1;\n"
        "and.b32 t, w, 0xffff;\n"
        "mad.wide.u32 pc, t, 1024, %0;\n"
        "shr.u32 t, w, 16;\n"
        "mad.wide.u32 pd, t, 1024, %0;\n"
        "add.u32 d, sa, %3;\n"
        "@lo cp.async.cg.shared.global [d+2048], [pa], 16;\n"
        "xor.b32 t, ey, %5;\n"
        "and.b32 t, t, 7;\n"
        "setp.ne.u32 zb, t, 0;\n"
        "and.b32 t, ey, 0xfffffff8;\n"
        "cvt.u64.u32 pb, t;\n"
        "add.u64 pb, pb, %2;\n"
        "selp.u32 dy, 64, 8, lo;\n"
        "xor.b32 dy, dy, d;\n"
        "cp.async.ca.shared.global [dy+2048], [pb], 8, zb;\n"
        "add.u32 d, sa, %12;\n"
        "and.b32 t, w, 0xffff;\n"
        "setp.eq.u32 zb, t, 0xffff;\n"
        "cp.async.cg.shared.global [d+0], [pc+0], 16, zb;\n"
        "cp.async.cg.shared.global [d+256], [pc+256], 16, zb;\n"
        "cp.async.cg.shared.global [d+512], [pc+512], 16, zb;\n"
        "cp.async.cg.shared.global [d+768], [pc+768], 16, zb;\n"
        "setp.lt.s32 zb, w, 0;\n"
        "cp.async.cg.shared.global [d+1024], [pd+0], 16, zb;\n"
        "cp.async.cg.shared.global [d+1280], [pd+256], 16, zb;\n"
        "cp.async.cg.shared.global [d+1536], [pd+512], 16, zb;\n"
        "cp.async.cg.shared.global [d+1792], [pd+768], 16, zb;\n"
        "xor.b32 dy, d, 64;\n"
        "and.b32 t, w2, 0xffff;\n"
        "mad.wide.u32 pa, t, 1024, %0;\n"
        "and.b32 t, w2, 0xffff;\n"
        "setp.eq.u32 zb, t, 0xffff;\n"
        "cp.async.cg.shared.global [dy+4352], [pa+0], 16, zb;\n"
        "cp.async.cg.shared.global [dy+4608], [pa+256], 16, zb;\n"
        "cp.async.cg.shared.global [dy+4864], [pa+512], 16, zb;\n"
        "cp.async.cg.shared.global [dy+5120], [pa+768], 16, zb;\n"
        "shr.u32 t, w2, 16;\n"
        "mad.wide.u32 pb, t, 1024, %0;\n"
        "setp.lt.s32 zb, w2, 0;\n"
        "cp.async.cg.shared.global [dy+5376], [pb+0], 16, zb;\n"
        "cp.async.cg.shared.global [dy+5632], [pb+256], 16, zb;\n"
        "cp.async.cg.shared.global [dy+5888], [pb+512], 16, zb;\n"
        "cp.async.cg.shared.global [dy+6144], [pb+768], 16, zb;\n"
        "add.u32 rp, rp, 104;\n"
        "shr.u32 t, %4, 1;\n"
        "and.b32 t, t, 4;\n"
        "add.u32 t, t, rp;\n"
        "ld.shared.u32 w, [t];\n"
        "ld.shared.u32 w2, [t+8];\n"
        "add.u32 t, rp, %4;\n"
        "ld.shared.u32 em, [t+16];\n"
        "ld.shared.u32 ey, [t+-36];\n"
        "ld.shared.u32 cu, [rp+48];\n"
        "ld.volatile.shared.u32 sv, [lag];\n"
        "cp.async.mbarrier.arrive.noinc.shared.b64 [sa+8704];\n"
        "add.u32 sa, sa, 17664;\n"
        "sub.u32 t, sa, 44160;\n"
        "setp.ge.u32 q, sa, rend;\n"
        "selp.u32 sa, t, sa, q;\n"
        "selp.u32 t, 1, 0, q;\n"
        "xor.b32 ph, ph, t;\n"
        "mbarrier.test_wait.parity.shared.b64 e, [sa+8712], ph;\n"
        "@!fbk bra.uni PC_%=;\n"
        "ld.volatile.shared.u32 u, [lag+24];\n"
        "shr.s32 u, u, 16;\n"
        "ld.volatile.shared.u64 pa, [lag+16];\n"
        "elect.sync _|z, 0xffffffff;\n"
        "@z st.relaxed.gpu.global.u32 [pa], u;\n"
        "@z cp.async.cg.shared.global [lag], [pa+16896], 16;\n"
        "PC_%=:\n"
        "setp.lt.u32 q, rp, rlast;\n"
        "@q bra.uni PL_%=;\n"
        "PF_%=:\n"
        "setp.ne.u32 q, rp, rlast;\n"
        "@q bra.uni PX_%=;\n"
        "mov.u32 n, 0;\n"
        "PE1_%=:\n"
        "@e bra.uni PE2_%=;\n"
        "mbarrier.try_wait.parity.shared.b64 e, [sa+8712], ph;\n"
        "add.u32 n, n, 1;\n"
        "setp.lt.u32 q, n, 4194304;\n"
        "@q bra.uni PE1_%=;\n"
        "trap;\n"
        "PE2_%=:\n"
        "cp.async.mbarrier.arrive.noinc.shared.b64 [sa+8704];\n"
        "PX_%=:\n"
        "}\n"
        ::"l"(xl), "l"(efl), "l"(Y), "r"(xd), "r"(oef), "r"(ysel), "r"(ring), "r"(rec), "r"(rlast), "r"(odd),
          "n"(0), "r"(lag), "r"(xh) : "memory");
}

__device__ __forceinline__ void consumer_loop(float (&acc)[5][4][2][4], const uint32_t (&wf)[4][4], const uint32_t (&cgf)[4],
                                              uint32_t xoff, uint32_t& ring, uint32_t moff, uint32_t rec) {
    asm volatile(
        "{\n"
        ".reg .b32 x<16>, a<4>, b<4>, r<4>, m<4>, rl, rh, tag, la, lb, sa, last, ph, tq, xa, ma, n, ring, sn, ln, yb, zz, k<4>, tp, s<4>;\n"
        ".reg .b16 lo, hi;\n"
        ".reg .f32 p<16>, d<4>, t0, t1, fz;\n"
        ".reg .pred q, w, el, c<5>;\n"
        "TA_%=: .branchtargets A0_%=, A1_%=, A2_%=, A3_%=, A4_%=, EXIT_%=;\n"
        "TB_%=: .branchtargets B0_%=, B1_%=, B2_%=, B3_%=, B4_%=, SPIN_%=;\n"
        "mov.f32 fz, 0f00000000;\n"
        "redux.sync.or.b32 ring, %160, 0xffffffff;\n"
        "mov.u32 sa, ring;\n"
        "add.u32 last, ring, 35328;\n"
        "mov.u32 ph, 0;\n"
        "redux.sync.xor.b32 zz, %160, 0xffffffff;\n"
        "redux.sync.or.b32 tp, %183, 0xffffffff;\n"
        "elect.sync _|el, 0xffffffff;\n"
        "mov.u32 k0, sa;\n"
        "mov.u32 k1, sa;\n"
        "mov.u32 k2, sa;\n"
        "mov.u32 k3, sa;\n"
        "mov.b32 x0, 0;\n"
        "mov.b32 x1, 0;\n"
        "mov.b32 x2, 0;\n"
        "mov.b32 x3, 0;\n"
        "mov.b32 x4, 0;\n"
        "mov.b32 x5, 0;\n"
        "mov.b32 x6, 0;\n"
        "mov.b32 x7, 0;\n"
        "mov.b32 x8, 0;\n"
        "mov.b32 x9, 0;\n"
        "mov.b32 x10, 0;\n"
        "mov.b32 x11, 0;\n"
        "mov.b32 x12, 0;\n"
        "mov.b32 x13, 0;\n"
        "mov.b32 x14, 0;\n"
        "mov.b32 x15, 0;\n"
        "mov.b32 b0, 0;\n"
        "mov.b32 r0, 0;\n"
        "mov.b32 b1, 0;\n"
        "mov.b32 r1, 0;\n"
        "mov.b32 b2, 0;\n"
        "mov.b32 r2, 0;\n"
        "mov.b32 b3, 0;\n"
        "mov.b32 r3, 0;\n"
        "mov.u32 lb, 0;\n"
        "mov.u32 n, 0;\n"
        "W0_%=:\n"
        "mbarrier.try_wait.parity.shared.b64 w, [sa+8704], 0;\n"
        "@w bra.uni W0D_%=;\n"
        "add.u32 n, n, 1;\n"
        "setp.lt.u32 q, n, 4194304;\n"
        "@q bra.uni W0_%=;\n"
        "trap;\n"
        "W0D_%=:\n"
        "add.u32 ma, sa, %182;\n"
        "ldmatrix.sync.aligned.m8n8.x4.shared.b16 {m0,m1,m2,m3}, [ma];\n"
        "ld.shared.u16 tag, [tp+48];\n"
        "add.u32 tp, tp, 52;\n"
        "add.u32 sn, sa, 8832;\n"
        "setp.eq.u32 q, sa, last;\n"
        "selp.u32 sn, ring, sn, q;\n"
        "selp.u32 tq, 1, 0, q;\n"
        "xor.b32 ph, ph, tq;\n"
        "mbarrier.test_wait.parity.shared.b64 w, [sn+8704], ph;\n"
        "mma.sync.aligned.m16n8k16.row.col.f32.bf16.bf16.f32 {p0,p1,p2,p3}, {%161,%162,%163,%164}, {m2,m3}, {fz,fz,fz,fz};\n"
        "mma.sync.aligned.m16n8k16.row.col.f32.bf16.bf16.f32 {p4,p5,p6,p7}, {%165,%166,%167,%168}, {m2,m3}, {fz,fz,fz,fz};\n"
        "mma.sync.aligned.m16n8k16.row.col.f32.bf16.bf16.f32 {p8,p9,p10,p11}, {%169,%170,%171,%172}, {m2,m3}, {fz,fz,fz,fz};\n"
        "mma.sync.aligned.m16n8k16.row.col.f32.bf16.bf16.f32 {p12,p13,p14,p15}, {%173,%174,%175,%176}, {m2,m3}, {fz,fz,fz,fz};\n"
        "@el mbarrier.arrive.shared.b64 _, [k0+8712];\n"
        "redux.sync.or.b32 ln, tag, 0xffffffff;\n"
        "mov.u32 sa, sn;\n"
        "add.u32 k0, sn, zz;\n"
        "SPIN_%=:\n"
        "mov.u32 n, 0;\n"
        "SP1_%=:\n"
        "mbarrier.try_wait.parity.shared.b64 w, [sa+8704], ph;\n"
        "@w bra.uni SP2_%=;\n"
        "add.u32 n, n, 1;\n"
        "setp.lt.u32 q, n, 4194304;\n"
        "@q bra.uni SP1_%=;\n"
        "trap;\n"
        "SP2_%=:\n"
        "brx.idx.uni lb, TB_%=;\n"
        "A0_%=:\n"
        "add.u32 xa, sa, %181;\n"
        "add.u32 ma, sa, %182;\n"
        "ldmatrix.sync.aligned.m8n8.x4.shared.b16 {m0,m1,m2,m3}, [ma];\n"
        "ld.shared.u16 tag, [tp+48];\n"
        "add.u32 tp, tp, 52;\n"
        "add.u32 sn, sa, 8832;\n"
        "setp.eq.u32 q, sa, last;\n"
        "selp.u32 sn, ring, sn, q;\n"
        "selp.u32 tq, 1, 0, q;\n"
        "xor.b32 ph, ph, tq;\n"
        "mbarrier.test_wait.parity.shared.b64 w, [sn+8704], ph;\n"
        "mma.sync.aligned.m16n8k16.row.col.f32.bf16.bf16.f32 {%0,%1,%2,%3}, {a0,a1,a2,a3}, {x0,x1}, {%0,%1,%2,%3};\n"
        "mma.sync.aligned.m16n8k16.row.col.f32.bf16.bf16.f32 {%4,%5,%6,%7}, {a0,a1,a2,a3}, {x2,x3}, {%4,%5,%6,%7};\n"
        "ld.shared.v4.u32 {x0,x1,x2,x3}, [xa+1024];\n"
        "tanh.approx.f32 t0, p1;\n"
        "tanh.approx.f32 t1, p3;\n"
        "fma.rn.f32 t0, p1, t0, p1;\n"
        "fma.rn.f32 t1, p3, t1, p3;\n"
        "cvt.rn.bf16x2.f32 r0, t1, t0;\n"
        "mma.sync.aligned.m16n8k16.row.col.f32.bf16.bf16.f32 {p0,p1,p2,p3}, {%161,%162,%163,%164}, {m2,m3}, {fz,fz,fz,fz};\n"
        "mma.sync.aligned.m16n8k16.row.col.f32.bf16.bf16.f32 {%8,%9,%10,%11}, {a0,a1,a2,a3}, {x4,x5}, {%8,%9,%10,%11};\n"
        "mma.sync.aligned.m16n8k16.row.col.f32.bf16.bf16.f32 {%12,%13,%14,%15}, {a0,a1,a2,a3}, {x6,x7}, {%12,%13,%14,%15};\n"
        "ld.shared.v4.u32 {x4,x5,x6,x7}, [xa+1152];\n"
        "mma.sync.aligned.m16n8k8.row.col.f32.bf16.bf16.f32 {d0,d1,d2,d3}, {%177,%178}, {m1}, {fz,fz,fz,fz};\n"
        "cvt.rn.bf16x2.f32 b0, d2, d0;\n"
        "cvt.rn.bf16x2.f32 b1, d3, d1;\n"
        "tanh.approx.f32 t0, p5;\n"
        "tanh.approx.f32 t1, p7;\n"
        "fma.rn.f32 t0, p5, t0, p5;\n"
        "fma.rn.f32 t1, p7, t1, p7;\n"
        "cvt.rn.bf16x2.f32 r1, t1, t0;\n"
        "mma.sync.aligned.m16n8k16.row.col.f32.bf16.bf16.f32 {p4,p5,p6,p7}, {%165,%166,%167,%168}, {m2,m3}, {fz,fz,fz,fz};\n"
        "mov.b32 {lo,hi}, r2;\n"
        "mov.b32 rl, {lo,lo};\n"
        "mov.b32 rh, {hi,hi};\n"
        "mul.bf16x2 x8, x8, rl;\n"
        "mul.bf16x2 x9, x9, rl;\n"
        "mul.bf16x2 x10, x10, rh;\n"
        "mul.bf16x2 x11, x11, rh;\n"
        "mma.sync.aligned.m16n8k16.row.col.f32.bf16.bf16.f32 {%16,%17,%18,%19}, {a0,a1,a2,a3}, {x8,x9}, {%16,%17,%18,%19};\n"
        "mma.sync.aligned.m16n8k16.row.col.f32.bf16.bf16.f32 {%20,%21,%22,%23}, {a0,a1,a2,a3}, {x10,x11}, {%20,%21,%22,%23};\n"
        "ld.shared.v4.u32 {x8,x9,x10,x11}, [xa+1280];\n"
        "mma.sync.aligned.m16n8k8.row.col.f32.bf16.bf16.f32 {d0,d1,d2,d3}, {%179,%180}, {m1}, {fz,fz,fz,fz};\n"
        "cvt.rn.bf16x2.f32 b2, d2, d0;\n"
        "cvt.rn.bf16x2.f32 b3, d3, d1;\n"
        "tanh.approx.f32 t0, p9;\n"
        "tanh.approx.f32 t1, p11;\n"
        "fma.rn.f32 t0, p9, t0, p9;\n"
        "fma.rn.f32 t1, p11, t1, p11;\n"
        "cvt.rn.bf16x2.f32 r2, t1, t0;\n"
        "mma.sync.aligned.m16n8k16.row.col.f32.bf16.bf16.f32 {p8,p9,p10,p11}, {%169,%170,%171,%172}, {m2,m3}, {fz,fz,fz,fz};\n"
        "mov.b32 {lo,hi}, r3;\n"
        "mov.b32 rl, {lo,lo};\n"
        "mov.b32 rh, {hi,hi};\n"
        "mul.bf16x2 x12, x12, rl;\n"
        "mul.bf16x2 x13, x13, rl;\n"
        "mul.bf16x2 x14, x14, rh;\n"
        "mul.bf16x2 x15, x15, rh;\n"
        "mma.sync.aligned.m16n8k16.row.col.f32.bf16.bf16.f32 {%24,%25,%26,%27}, {a0,a1,a2,a3}, {x12,x13}, {%24,%25,%26,%27};\n"
        "mma.sync.aligned.m16n8k16.row.col.f32.bf16.bf16.f32 {%28,%29,%30,%31}, {a0,a1,a2,a3}, {x14,x15}, {%28,%29,%30,%31};\n"
        "ld.shared.v4.u32 {x12,x13,x14,x15}, [xa+1408];\n"
        "@el mbarrier.arrive.shared.b64 _, [k0+8712];\n"
        "redux.sync.or.b32 ln, tag, 0xffffffff;\n"
        "mov.u32 sa, sn;\n"
        "add.u32 k0, sn, zz;\n"
        "tanh.approx.f32 t0, p13;\n"
        "tanh.approx.f32 t1, p15;\n"
        "fma.rn.f32 t0, p13, t0, p13;\n"
        "fma.rn.f32 t1, p15, t1, p15;\n"
        "cvt.rn.bf16x2.f32 r3, t1, t0;\n"
        "mma.sync.aligned.m16n8k16.row.col.f32.bf16.bf16.f32 {p12,p13,p14,p15}, {%173,%174,%175,%176}, {m2,m3}, {fz,fz,fz,fz};\n"
        "selp.u32 tq, lb, 5, w;\n"
        "brx.idx.uni tq, TB_%=;\n"
        "A1_%=:\n"
        "add.u32 xa, sa, %181;\n"
        "add.u32 ma, sa, %182;\n"
        "ldmatrix.sync.aligned.m8n8.x4.shared.b16 {m0,m1,m2,m3}, [ma];\n"
        "ld.shared.u16 tag, [tp+48];\n"
        "add.u32 tp, tp, 52;\n"
        "add.u32 sn, sa, 8832;\n"
        "setp.eq.u32 q, sa, last;\n"
        "selp.u32 sn, ring, sn, q;\n"
        "selp.u32 tq, 1, 0, q;\n"
        "xor.b32 ph, ph, tq;\n"
        "mbarrier.test_wait.parity.shared.b64 w, [sn+8704], ph;\n"
        "mma.sync.aligned.m16n8k16.row.col.f32.bf16.bf16.f32 {%32,%33,%34,%35}, {a0,a1,a2,a3}, {x0,x1}, {%32,%33,%34,%35};\n"
        "mma.sync.aligned.m16n8k16.row.col.f32.bf16.bf16.f32 {%36,%37,%38,%39}, {a0,a1,a2,a3}, {x2,x3}, {%36,%37,%38,%39};\n"
        "ld.shared.v4.u32 {x0,x1,x2,x3}, [xa+1024];\n"
        "tanh.approx.f32 t0, p1;\n"
        "tanh.approx.f32 t1, p3;\n"
        "fma.rn.f32 t0, p1, t0, p1;\n"
        "fma.rn.f32 t1, p3, t1, p3;\n"
        "cvt.rn.bf16x2.f32 r0, t1, t0;\n"
        "mma.sync.aligned.m16n8k16.row.col.f32.bf16.bf16.f32 {p0,p1,p2,p3}, {%161,%162,%163,%164}, {m2,m3}, {fz,fz,fz,fz};\n"
        "mma.sync.aligned.m16n8k16.row.col.f32.bf16.bf16.f32 {%40,%41,%42,%43}, {a0,a1,a2,a3}, {x4,x5}, {%40,%41,%42,%43};\n"
        "mma.sync.aligned.m16n8k16.row.col.f32.bf16.bf16.f32 {%44,%45,%46,%47}, {a0,a1,a2,a3}, {x6,x7}, {%44,%45,%46,%47};\n"
        "ld.shared.v4.u32 {x4,x5,x6,x7}, [xa+1152];\n"
        "mma.sync.aligned.m16n8k8.row.col.f32.bf16.bf16.f32 {d0,d1,d2,d3}, {%177,%178}, {m1}, {fz,fz,fz,fz};\n"
        "cvt.rn.bf16x2.f32 b0, d2, d0;\n"
        "cvt.rn.bf16x2.f32 b1, d3, d1;\n"
        "tanh.approx.f32 t0, p5;\n"
        "tanh.approx.f32 t1, p7;\n"
        "fma.rn.f32 t0, p5, t0, p5;\n"
        "fma.rn.f32 t1, p7, t1, p7;\n"
        "cvt.rn.bf16x2.f32 r1, t1, t0;\n"
        "mma.sync.aligned.m16n8k16.row.col.f32.bf16.bf16.f32 {p4,p5,p6,p7}, {%165,%166,%167,%168}, {m2,m3}, {fz,fz,fz,fz};\n"
        "mov.b32 {lo,hi}, r2;\n"
        "mov.b32 rl, {lo,lo};\n"
        "mov.b32 rh, {hi,hi};\n"
        "mul.bf16x2 x8, x8, rl;\n"
        "mul.bf16x2 x9, x9, rl;\n"
        "mul.bf16x2 x10, x10, rh;\n"
        "mul.bf16x2 x11, x11, rh;\n"
        "mma.sync.aligned.m16n8k16.row.col.f32.bf16.bf16.f32 {%48,%49,%50,%51}, {a0,a1,a2,a3}, {x8,x9}, {%48,%49,%50,%51};\n"
        "mma.sync.aligned.m16n8k16.row.col.f32.bf16.bf16.f32 {%52,%53,%54,%55}, {a0,a1,a2,a3}, {x10,x11}, {%52,%53,%54,%55};\n"
        "ld.shared.v4.u32 {x8,x9,x10,x11}, [xa+1280];\n"
        "mma.sync.aligned.m16n8k8.row.col.f32.bf16.bf16.f32 {d0,d1,d2,d3}, {%179,%180}, {m1}, {fz,fz,fz,fz};\n"
        "cvt.rn.bf16x2.f32 b2, d2, d0;\n"
        "cvt.rn.bf16x2.f32 b3, d3, d1;\n"
        "tanh.approx.f32 t0, p9;\n"
        "tanh.approx.f32 t1, p11;\n"
        "fma.rn.f32 t0, p9, t0, p9;\n"
        "fma.rn.f32 t1, p11, t1, p11;\n"
        "cvt.rn.bf16x2.f32 r2, t1, t0;\n"
        "mma.sync.aligned.m16n8k16.row.col.f32.bf16.bf16.f32 {p8,p9,p10,p11}, {%169,%170,%171,%172}, {m2,m3}, {fz,fz,fz,fz};\n"
        "mov.b32 {lo,hi}, r3;\n"
        "mov.b32 rl, {lo,lo};\n"
        "mov.b32 rh, {hi,hi};\n"
        "mul.bf16x2 x12, x12, rl;\n"
        "mul.bf16x2 x13, x13, rl;\n"
        "mul.bf16x2 x14, x14, rh;\n"
        "mul.bf16x2 x15, x15, rh;\n"
        "mma.sync.aligned.m16n8k16.row.col.f32.bf16.bf16.f32 {%56,%57,%58,%59}, {a0,a1,a2,a3}, {x12,x13}, {%56,%57,%58,%59};\n"
        "mma.sync.aligned.m16n8k16.row.col.f32.bf16.bf16.f32 {%60,%61,%62,%63}, {a0,a1,a2,a3}, {x14,x15}, {%60,%61,%62,%63};\n"
        "ld.shared.v4.u32 {x12,x13,x14,x15}, [xa+1408];\n"
        "@el mbarrier.arrive.shared.b64 _, [k0+8712];\n"
        "redux.sync.or.b32 ln, tag, 0xffffffff;\n"
        "mov.u32 sa, sn;\n"
        "add.u32 k0, sn, zz;\n"
        "tanh.approx.f32 t0, p13;\n"
        "tanh.approx.f32 t1, p15;\n"
        "fma.rn.f32 t0, p13, t0, p13;\n"
        "fma.rn.f32 t1, p15, t1, p15;\n"
        "cvt.rn.bf16x2.f32 r3, t1, t0;\n"
        "mma.sync.aligned.m16n8k16.row.col.f32.bf16.bf16.f32 {p12,p13,p14,p15}, {%173,%174,%175,%176}, {m2,m3}, {fz,fz,fz,fz};\n"
        "selp.u32 tq, lb, 5, w;\n"
        "brx.idx.uni tq, TB_%=;\n"
        "A2_%=:\n"
        "add.u32 xa, sa, %181;\n"
        "add.u32 ma, sa, %182;\n"
        "ldmatrix.sync.aligned.m8n8.x4.shared.b16 {m0,m1,m2,m3}, [ma];\n"
        "ld.shared.u16 tag, [tp+48];\n"
        "add.u32 tp, tp, 52;\n"
        "add.u32 sn, sa, 8832;\n"
        "setp.eq.u32 q, sa, last;\n"
        "selp.u32 sn, ring, sn, q;\n"
        "selp.u32 tq, 1, 0, q;\n"
        "xor.b32 ph, ph, tq;\n"
        "mbarrier.test_wait.parity.shared.b64 w, [sn+8704], ph;\n"
        "mma.sync.aligned.m16n8k16.row.col.f32.bf16.bf16.f32 {%64,%65,%66,%67}, {a0,a1,a2,a3}, {x0,x1}, {%64,%65,%66,%67};\n"
        "mma.sync.aligned.m16n8k16.row.col.f32.bf16.bf16.f32 {%68,%69,%70,%71}, {a0,a1,a2,a3}, {x2,x3}, {%68,%69,%70,%71};\n"
        "ld.shared.v4.u32 {x0,x1,x2,x3}, [xa+1024];\n"
        "tanh.approx.f32 t0, p1;\n"
        "tanh.approx.f32 t1, p3;\n"
        "fma.rn.f32 t0, p1, t0, p1;\n"
        "fma.rn.f32 t1, p3, t1, p3;\n"
        "cvt.rn.bf16x2.f32 r0, t1, t0;\n"
        "mma.sync.aligned.m16n8k16.row.col.f32.bf16.bf16.f32 {p0,p1,p2,p3}, {%161,%162,%163,%164}, {m2,m3}, {fz,fz,fz,fz};\n"
        "mma.sync.aligned.m16n8k16.row.col.f32.bf16.bf16.f32 {%72,%73,%74,%75}, {a0,a1,a2,a3}, {x4,x5}, {%72,%73,%74,%75};\n"
        "mma.sync.aligned.m16n8k16.row.col.f32.bf16.bf16.f32 {%76,%77,%78,%79}, {a0,a1,a2,a3}, {x6,x7}, {%76,%77,%78,%79};\n"
        "ld.shared.v4.u32 {x4,x5,x6,x7}, [xa+1152];\n"
        "mma.sync.aligned.m16n8k8.row.col.f32.bf16.bf16.f32 {d0,d1,d2,d3}, {%177,%178}, {m1}, {fz,fz,fz,fz};\n"
        "cvt.rn.bf16x2.f32 b0, d2, d0;\n"
        "cvt.rn.bf16x2.f32 b1, d3, d1;\n"
        "tanh.approx.f32 t0, p5;\n"
        "tanh.approx.f32 t1, p7;\n"
        "fma.rn.f32 t0, p5, t0, p5;\n"
        "fma.rn.f32 t1, p7, t1, p7;\n"
        "cvt.rn.bf16x2.f32 r1, t1, t0;\n"
        "mma.sync.aligned.m16n8k16.row.col.f32.bf16.bf16.f32 {p4,p5,p6,p7}, {%165,%166,%167,%168}, {m2,m3}, {fz,fz,fz,fz};\n"
        "mov.b32 {lo,hi}, r2;\n"
        "mov.b32 rl, {lo,lo};\n"
        "mov.b32 rh, {hi,hi};\n"
        "mul.bf16x2 x8, x8, rl;\n"
        "mul.bf16x2 x9, x9, rl;\n"
        "mul.bf16x2 x10, x10, rh;\n"
        "mul.bf16x2 x11, x11, rh;\n"
        "mma.sync.aligned.m16n8k16.row.col.f32.bf16.bf16.f32 {%80,%81,%82,%83}, {a0,a1,a2,a3}, {x8,x9}, {%80,%81,%82,%83};\n"
        "mma.sync.aligned.m16n8k16.row.col.f32.bf16.bf16.f32 {%84,%85,%86,%87}, {a0,a1,a2,a3}, {x10,x11}, {%84,%85,%86,%87};\n"
        "ld.shared.v4.u32 {x8,x9,x10,x11}, [xa+1280];\n"
        "mma.sync.aligned.m16n8k8.row.col.f32.bf16.bf16.f32 {d0,d1,d2,d3}, {%179,%180}, {m1}, {fz,fz,fz,fz};\n"
        "cvt.rn.bf16x2.f32 b2, d2, d0;\n"
        "cvt.rn.bf16x2.f32 b3, d3, d1;\n"
        "tanh.approx.f32 t0, p9;\n"
        "tanh.approx.f32 t1, p11;\n"
        "fma.rn.f32 t0, p9, t0, p9;\n"
        "fma.rn.f32 t1, p11, t1, p11;\n"
        "cvt.rn.bf16x2.f32 r2, t1, t0;\n"
        "mma.sync.aligned.m16n8k16.row.col.f32.bf16.bf16.f32 {p8,p9,p10,p11}, {%169,%170,%171,%172}, {m2,m3}, {fz,fz,fz,fz};\n"
        "mov.b32 {lo,hi}, r3;\n"
        "mov.b32 rl, {lo,lo};\n"
        "mov.b32 rh, {hi,hi};\n"
        "mul.bf16x2 x12, x12, rl;\n"
        "mul.bf16x2 x13, x13, rl;\n"
        "mul.bf16x2 x14, x14, rh;\n"
        "mul.bf16x2 x15, x15, rh;\n"
        "mma.sync.aligned.m16n8k16.row.col.f32.bf16.bf16.f32 {%88,%89,%90,%91}, {a0,a1,a2,a3}, {x12,x13}, {%88,%89,%90,%91};\n"
        "mma.sync.aligned.m16n8k16.row.col.f32.bf16.bf16.f32 {%92,%93,%94,%95}, {a0,a1,a2,a3}, {x14,x15}, {%92,%93,%94,%95};\n"
        "ld.shared.v4.u32 {x12,x13,x14,x15}, [xa+1408];\n"
        "@el mbarrier.arrive.shared.b64 _, [k0+8712];\n"
        "redux.sync.or.b32 ln, tag, 0xffffffff;\n"
        "mov.u32 sa, sn;\n"
        "add.u32 k0, sn, zz;\n"
        "tanh.approx.f32 t0, p13;\n"
        "tanh.approx.f32 t1, p15;\n"
        "fma.rn.f32 t0, p13, t0, p13;\n"
        "fma.rn.f32 t1, p15, t1, p15;\n"
        "cvt.rn.bf16x2.f32 r3, t1, t0;\n"
        "mma.sync.aligned.m16n8k16.row.col.f32.bf16.bf16.f32 {p12,p13,p14,p15}, {%173,%174,%175,%176}, {m2,m3}, {fz,fz,fz,fz};\n"
        "selp.u32 tq, lb, 5, w;\n"
        "brx.idx.uni tq, TB_%=;\n"
        "A3_%=:\n"
        "add.u32 xa, sa, %181;\n"
        "add.u32 ma, sa, %182;\n"
        "ldmatrix.sync.aligned.m8n8.x4.shared.b16 {m0,m1,m2,m3}, [ma];\n"
        "ld.shared.u16 tag, [tp+48];\n"
        "add.u32 tp, tp, 52;\n"
        "add.u32 sn, sa, 8832;\n"
        "setp.eq.u32 q, sa, last;\n"
        "selp.u32 sn, ring, sn, q;\n"
        "selp.u32 tq, 1, 0, q;\n"
        "xor.b32 ph, ph, tq;\n"
        "mbarrier.test_wait.parity.shared.b64 w, [sn+8704], ph;\n"
        "mma.sync.aligned.m16n8k16.row.col.f32.bf16.bf16.f32 {%96,%97,%98,%99}, {a0,a1,a2,a3}, {x0,x1}, {%96,%97,%98,%99};\n"
        "mma.sync.aligned.m16n8k16.row.col.f32.bf16.bf16.f32 {%100,%101,%102,%103}, {a0,a1,a2,a3}, {x2,x3}, {%100,%101,%102,%103};\n"
        "ld.shared.v4.u32 {x0,x1,x2,x3}, [xa+1024];\n"
        "tanh.approx.f32 t0, p1;\n"
        "tanh.approx.f32 t1, p3;\n"
        "fma.rn.f32 t0, p1, t0, p1;\n"
        "fma.rn.f32 t1, p3, t1, p3;\n"
        "cvt.rn.bf16x2.f32 r0, t1, t0;\n"
        "mma.sync.aligned.m16n8k16.row.col.f32.bf16.bf16.f32 {p0,p1,p2,p3}, {%161,%162,%163,%164}, {m2,m3}, {fz,fz,fz,fz};\n"
        "mma.sync.aligned.m16n8k16.row.col.f32.bf16.bf16.f32 {%104,%105,%106,%107}, {a0,a1,a2,a3}, {x4,x5}, {%104,%105,%106,%107};\n"
        "mma.sync.aligned.m16n8k16.row.col.f32.bf16.bf16.f32 {%108,%109,%110,%111}, {a0,a1,a2,a3}, {x6,x7}, {%108,%109,%110,%111};\n"
        "ld.shared.v4.u32 {x4,x5,x6,x7}, [xa+1152];\n"
        "mma.sync.aligned.m16n8k8.row.col.f32.bf16.bf16.f32 {d0,d1,d2,d3}, {%177,%178}, {m1}, {fz,fz,fz,fz};\n"
        "cvt.rn.bf16x2.f32 b0, d2, d0;\n"
        "cvt.rn.bf16x2.f32 b1, d3, d1;\n"
        "tanh.approx.f32 t0, p5;\n"
        "tanh.approx.f32 t1, p7;\n"
        "fma.rn.f32 t0, p5, t0, p5;\n"
        "fma.rn.f32 t1, p7, t1, p7;\n"
        "cvt.rn.bf16x2.f32 r1, t1, t0;\n"
        "mma.sync.aligned.m16n8k16.row.col.f32.bf16.bf16.f32 {p4,p5,p6,p7}, {%165,%166,%167,%168}, {m2,m3}, {fz,fz,fz,fz};\n"
        "mov.b32 {lo,hi}, r2;\n"
        "mov.b32 rl, {lo,lo};\n"
        "mov.b32 rh, {hi,hi};\n"
        "mul.bf16x2 x8, x8, rl;\n"
        "mul.bf16x2 x9, x9, rl;\n"
        "mul.bf16x2 x10, x10, rh;\n"
        "mul.bf16x2 x11, x11, rh;\n"
        "mma.sync.aligned.m16n8k16.row.col.f32.bf16.bf16.f32 {%112,%113,%114,%115}, {a0,a1,a2,a3}, {x8,x9}, {%112,%113,%114,%115};\n"
        "mma.sync.aligned.m16n8k16.row.col.f32.bf16.bf16.f32 {%116,%117,%118,%119}, {a0,a1,a2,a3}, {x10,x11}, {%116,%117,%118,%119};\n"
        "ld.shared.v4.u32 {x8,x9,x10,x11}, [xa+1280];\n"
        "mma.sync.aligned.m16n8k8.row.col.f32.bf16.bf16.f32 {d0,d1,d2,d3}, {%179,%180}, {m1}, {fz,fz,fz,fz};\n"
        "cvt.rn.bf16x2.f32 b2, d2, d0;\n"
        "cvt.rn.bf16x2.f32 b3, d3, d1;\n"
        "tanh.approx.f32 t0, p9;\n"
        "tanh.approx.f32 t1, p11;\n"
        "fma.rn.f32 t0, p9, t0, p9;\n"
        "fma.rn.f32 t1, p11, t1, p11;\n"
        "cvt.rn.bf16x2.f32 r2, t1, t0;\n"
        "mma.sync.aligned.m16n8k16.row.col.f32.bf16.bf16.f32 {p8,p9,p10,p11}, {%169,%170,%171,%172}, {m2,m3}, {fz,fz,fz,fz};\n"
        "mov.b32 {lo,hi}, r3;\n"
        "mov.b32 rl, {lo,lo};\n"
        "mov.b32 rh, {hi,hi};\n"
        "mul.bf16x2 x12, x12, rl;\n"
        "mul.bf16x2 x13, x13, rl;\n"
        "mul.bf16x2 x14, x14, rh;\n"
        "mul.bf16x2 x15, x15, rh;\n"
        "mma.sync.aligned.m16n8k16.row.col.f32.bf16.bf16.f32 {%120,%121,%122,%123}, {a0,a1,a2,a3}, {x12,x13}, {%120,%121,%122,%123};\n"
        "mma.sync.aligned.m16n8k16.row.col.f32.bf16.bf16.f32 {%124,%125,%126,%127}, {a0,a1,a2,a3}, {x14,x15}, {%124,%125,%126,%127};\n"
        "ld.shared.v4.u32 {x12,x13,x14,x15}, [xa+1408];\n"
        "@el mbarrier.arrive.shared.b64 _, [k0+8712];\n"
        "redux.sync.or.b32 ln, tag, 0xffffffff;\n"
        "mov.u32 sa, sn;\n"
        "add.u32 k0, sn, zz;\n"
        "tanh.approx.f32 t0, p13;\n"
        "tanh.approx.f32 t1, p15;\n"
        "fma.rn.f32 t0, p13, t0, p13;\n"
        "fma.rn.f32 t1, p15, t1, p15;\n"
        "cvt.rn.bf16x2.f32 r3, t1, t0;\n"
        "mma.sync.aligned.m16n8k16.row.col.f32.bf16.bf16.f32 {p12,p13,p14,p15}, {%173,%174,%175,%176}, {m2,m3}, {fz,fz,fz,fz};\n"
        "selp.u32 tq, lb, 5, w;\n"
        "brx.idx.uni tq, TB_%=;\n"
        "A4_%=:\n"
        "add.u32 xa, sa, %181;\n"
        "add.u32 ma, sa, %182;\n"
        "ldmatrix.sync.aligned.m8n8.x4.shared.b16 {m0,m1,m2,m3}, [ma];\n"
        "ld.shared.u16 tag, [tp+48];\n"
        "add.u32 tp, tp, 52;\n"
        "add.u32 sn, sa, 8832;\n"
        "setp.eq.u32 q, sa, last;\n"
        "selp.u32 sn, ring, sn, q;\n"
        "selp.u32 tq, 1, 0, q;\n"
        "xor.b32 ph, ph, tq;\n"
        "mbarrier.test_wait.parity.shared.b64 w, [sn+8704], ph;\n"
        "mma.sync.aligned.m16n8k16.row.col.f32.bf16.bf16.f32 {%128,%129,%130,%131}, {a0,a1,a2,a3}, {x0,x1}, {%128,%129,%130,%131};\n"
        "mma.sync.aligned.m16n8k16.row.col.f32.bf16.bf16.f32 {%132,%133,%134,%135}, {a0,a1,a2,a3}, {x2,x3}, {%132,%133,%134,%135};\n"
        "ld.shared.v4.u32 {x0,x1,x2,x3}, [xa+1024];\n"
        "tanh.approx.f32 t0, p1;\n"
        "tanh.approx.f32 t1, p3;\n"
        "fma.rn.f32 t0, p1, t0, p1;\n"
        "fma.rn.f32 t1, p3, t1, p3;\n"
        "cvt.rn.bf16x2.f32 r0, t1, t0;\n"
        "mma.sync.aligned.m16n8k16.row.col.f32.bf16.bf16.f32 {p0,p1,p2,p3}, {%161,%162,%163,%164}, {m2,m3}, {fz,fz,fz,fz};\n"
        "mma.sync.aligned.m16n8k16.row.col.f32.bf16.bf16.f32 {%136,%137,%138,%139}, {a0,a1,a2,a3}, {x4,x5}, {%136,%137,%138,%139};\n"
        "mma.sync.aligned.m16n8k16.row.col.f32.bf16.bf16.f32 {%140,%141,%142,%143}, {a0,a1,a2,a3}, {x6,x7}, {%140,%141,%142,%143};\n"
        "ld.shared.v4.u32 {x4,x5,x6,x7}, [xa+1152];\n"
        "mma.sync.aligned.m16n8k8.row.col.f32.bf16.bf16.f32 {d0,d1,d2,d3}, {%177,%178}, {m1}, {fz,fz,fz,fz};\n"
        "cvt.rn.bf16x2.f32 b0, d2, d0;\n"
        "cvt.rn.bf16x2.f32 b1, d3, d1;\n"
        "tanh.approx.f32 t0, p5;\n"
        "tanh.approx.f32 t1, p7;\n"
        "fma.rn.f32 t0, p5, t0, p5;\n"
        "fma.rn.f32 t1, p7, t1, p7;\n"
        "cvt.rn.bf16x2.f32 r1, t1, t0;\n"
        "mma.sync.aligned.m16n8k16.row.col.f32.bf16.bf16.f32 {p4,p5,p6,p7}, {%165,%166,%167,%168}, {m2,m3}, {fz,fz,fz,fz};\n"
        "mov.b32 {lo,hi}, r2;\n"
        "mov.b32 rl, {lo,lo};\n"
        "mov.b32 rh, {hi,hi};\n"
        "mul.bf16x2 x8, x8, rl;\n"
        "mul.bf16x2 x9, x9, rl;\n"
        "mul.bf16x2 x10, x10, rh;\n"
        "mul.bf16x2 x11, x11, rh;\n"
        "mma.sync.aligned.m16n8k16.row.col.f32.bf16.bf16.f32 {%144,%145,%146,%147}, {a0,a1,a2,a3}, {x8,x9}, {%144,%145,%146,%147};\n"
        "mma.sync.aligned.m16n8k16.row.col.f32.bf16.bf16.f32 {%148,%149,%150,%151}, {a0,a1,a2,a3}, {x10,x11}, {%148,%149,%150,%151};\n"
        "ld.shared.v4.u32 {x8,x9,x10,x11}, [xa+1280];\n"
        "mma.sync.aligned.m16n8k8.row.col.f32.bf16.bf16.f32 {d0,d1,d2,d3}, {%179,%180}, {m1}, {fz,fz,fz,fz};\n"
        "cvt.rn.bf16x2.f32 b2, d2, d0;\n"
        "cvt.rn.bf16x2.f32 b3, d3, d1;\n"
        "tanh.approx.f32 t0, p9;\n"
        "tanh.approx.f32 t1, p11;\n"
        "fma.rn.f32 t0, p9, t0, p9;\n"
        "fma.rn.f32 t1, p11, t1, p11;\n"
        "cvt.rn.bf16x2.f32 r2, t1, t0;\n"
        "mma.sync.aligned.m16n8k16.row.col.f32.bf16.bf16.f32 {p8,p9,p10,p11}, {%169,%170,%171,%172}, {m2,m3}, {fz,fz,fz,fz};\n"
        "mov.b32 {lo,hi}, r3;\n"
        "mov.b32 rl, {lo,lo};\n"
        "mov.b32 rh, {hi,hi};\n"
        "mul.bf16x2 x12, x12, rl;\n"
        "mul.bf16x2 x13, x13, rl;\n"
        "mul.bf16x2 x14, x14, rh;\n"
        "mul.bf16x2 x15, x15, rh;\n"
        "mma.sync.aligned.m16n8k16.row.col.f32.bf16.bf16.f32 {%152,%153,%154,%155}, {a0,a1,a2,a3}, {x12,x13}, {%152,%153,%154,%155};\n"
        "mma.sync.aligned.m16n8k16.row.col.f32.bf16.bf16.f32 {%156,%157,%158,%159}, {a0,a1,a2,a3}, {x14,x15}, {%156,%157,%158,%159};\n"
        "ld.shared.v4.u32 {x12,x13,x14,x15}, [xa+1408];\n"
        "@el mbarrier.arrive.shared.b64 _, [k0+8712];\n"
        "redux.sync.or.b32 ln, tag, 0xffffffff;\n"
        "mov.u32 sa, sn;\n"
        "add.u32 k0, sn, zz;\n"
        "tanh.approx.f32 t0, p13;\n"
        "tanh.approx.f32 t1, p15;\n"
        "fma.rn.f32 t0, p13, t0, p13;\n"
        "fma.rn.f32 t1, p15, t1, p15;\n"
        "cvt.rn.bf16x2.f32 r3, t1, t0;\n"
        "mma.sync.aligned.m16n8k16.row.col.f32.bf16.bf16.f32 {p12,p13,p14,p15}, {%173,%174,%175,%176}, {m2,m3}, {fz,fz,fz,fz};\n"
        "selp.u32 tq, lb, 5, w;\n"
        "brx.idx.uni tq, TB_%=;\n"
        "B0_%=:\n"
        "and.b32 la, ln, 255;\n"
        "shr.u32 lb, ln, 8;\n"
        "add.u32 ma, sa, %182;\n"
        "ldmatrix.sync.aligned.m8n8.x1.shared.b16 {yb}, [ma];\n"
        "add.u32 xa, sa, %181;\n"
        "mov.b32 {lo,hi}, r0;\n"
        "mov.b32 rl, {lo,lo};\n"
        "mov.b32 rh, {hi,hi};\n"
        "mul.bf16x2 x0, x0, rl;\n"
        "mul.bf16x2 x1, x1, rl;\n"
        "mul.bf16x2 x2, x2, rh;\n"
        "mul.bf16x2 x3, x3, rh;\n"
        "mma.sync.aligned.m16n8k16.row.col.f32.bf16.bf16.f32 {%0,%1,%2,%3}, {b0,b1,b2,b3}, {x0,x1}, {%0,%1,%2,%3};\n"
        "mma.sync.aligned.m16n8k16.row.col.f32.bf16.bf16.f32 {%4,%5,%6,%7}, {b0,b1,b2,b3}, {x2,x3}, {%4,%5,%6,%7};\n"
        "ld.shared.v4.u32 {x0,x1,x2,x3}, [xa+0];\n"
        "tanh.approx.f32 t0, p0;\n"
        "tanh.approx.f32 t1, p2;\n"
        "fma.rn.f32 t0, p0, t0, p0;\n"
        "fma.rn.f32 t1, p2, t1, p2;\n"
        "cvt.rn.bf16x2.f32 r0, t1, t0;\n"
        "mov.b32 {lo,hi}, r1;\n"
        "mov.b32 rl, {lo,lo};\n"
        "mov.b32 rh, {hi,hi};\n"
        "mul.bf16x2 x4, x4, rl;\n"
        "mul.bf16x2 x5, x5, rl;\n"
        "mul.bf16x2 x6, x6, rh;\n"
        "mul.bf16x2 x7, x7, rh;\n"
        "mma.sync.aligned.m16n8k16.row.col.f32.bf16.bf16.f32 {%8,%9,%10,%11}, {b0,b1,b2,b3}, {x4,x5}, {%8,%9,%10,%11};\n"
        "mma.sync.aligned.m16n8k16.row.col.f32.bf16.bf16.f32 {%12,%13,%14,%15}, {b0,b1,b2,b3}, {x6,x7}, {%12,%13,%14,%15};\n"
        "ld.shared.v4.u32 {x4,x5,x6,x7}, [xa+128];\n"
        "tanh.approx.f32 t0, p4;\n"
        "tanh.approx.f32 t1, p6;\n"
        "fma.rn.f32 t0, p4, t0, p4;\n"
        "fma.rn.f32 t1, p6, t1, p6;\n"
        "cvt.rn.bf16x2.f32 r1, t1, t0;\n"
        "mma.sync.aligned.m16n8k8.row.col.f32.bf16.bf16.f32 {d0,d1,d2,d3}, {%177,%178}, {yb}, {fz,fz,fz,fz};\n"
        "cvt.rn.bf16x2.f32 a0, d2, d0;\n"
        "cvt.rn.bf16x2.f32 a1, d3, d1;\n"
        "mov.b32 {lo,hi}, r2;\n"
        "mov.b32 rl, {lo,lo};\n"
        "mov.b32 rh, {hi,hi};\n"
        "mul.bf16x2 x8, x8, rl;\n"
        "mul.bf16x2 x9, x9, rl;\n"
        "mul.bf16x2 x10, x10, rh;\n"
        "mul.bf16x2 x11, x11, rh;\n"
        "mma.sync.aligned.m16n8k16.row.col.f32.bf16.bf16.f32 {%16,%17,%18,%19}, {b0,b1,b2,b3}, {x8,x9}, {%16,%17,%18,%19};\n"
        "mma.sync.aligned.m16n8k16.row.col.f32.bf16.bf16.f32 {%20,%21,%22,%23}, {b0,b1,b2,b3}, {x10,x11}, {%20,%21,%22,%23};\n"
        "ld.shared.v4.u32 {x8,x9,x10,x11}, [xa+256];\n"
        "tanh.approx.f32 t0, p8;\n"
        "tanh.approx.f32 t1, p10;\n"
        "fma.rn.f32 t0, p8, t0, p8;\n"
        "fma.rn.f32 t1, p10, t1, p10;\n"
        "cvt.rn.bf16x2.f32 r2, t1, t0;\n"
        "mma.sync.aligned.m16n8k8.row.col.f32.bf16.bf16.f32 {d0,d1,d2,d3}, {%179,%180}, {yb}, {fz,fz,fz,fz};\n"
        "cvt.rn.bf16x2.f32 a2, d2, d0;\n"
        "cvt.rn.bf16x2.f32 a3, d3, d1;\n"
        "mov.b32 {lo,hi}, r3;\n"
        "mov.b32 rl, {lo,lo};\n"
        "mov.b32 rh, {hi,hi};\n"
        "mul.bf16x2 x12, x12, rl;\n"
        "mul.bf16x2 x13, x13, rl;\n"
        "mul.bf16x2 x14, x14, rh;\n"
        "mul.bf16x2 x15, x15, rh;\n"
        "mma.sync.aligned.m16n8k16.row.col.f32.bf16.bf16.f32 {%24,%25,%26,%27}, {b0,b1,b2,b3}, {x12,x13}, {%24,%25,%26,%27};\n"
        "mma.sync.aligned.m16n8k16.row.col.f32.bf16.bf16.f32 {%28,%29,%30,%31}, {b0,b1,b2,b3}, {x14,x15}, {%28,%29,%30,%31};\n"
        "ld.shared.v4.u32 {x12,x13,x14,x15}, [xa+384];\n"
        "tanh.approx.f32 t0, p12;\n"
        "tanh.approx.f32 t1, p14;\n"
        "fma.rn.f32 t0, p12, t0, p12;\n"
        "fma.rn.f32 t1, p14, t1, p14;\n"
        "cvt.rn.bf16x2.f32 r3, t1, t0;\n"
        "mov.b32 {lo,hi}, r0;\n"
        "mov.b32 rl, {lo,lo};\n"
        "mov.b32 rh, {hi,hi};\n"
        "mul.bf16x2 x0, x0, rl;\n"
        "mul.bf16x2 x1, x1, rl;\n"
        "mul.bf16x2 x2, x2, rh;\n"
        "mul.bf16x2 x3, x3, rh;\n"
        "mov.b32 {lo,hi}, r1;\n"
        "mov.b32 rl, {lo,lo};\n"
        "mov.b32 rh, {hi,hi};\n"
        "mul.bf16x2 x4, x4, rl;\n"
        "mul.bf16x2 x5, x5, rl;\n"
        "mul.bf16x2 x6, x6, rh;\n"
        "mul.bf16x2 x7, x7, rh;\n"
        "brx.idx.uni la, TA_%=;\n"
        "B1_%=:\n"
        "and.b32 la, ln, 255;\n"
        "shr.u32 lb, ln, 8;\n"
        "add.u32 ma, sa, %182;\n"
        "ldmatrix.sync.aligned.m8n8.x1.shared.b16 {yb}, [ma];\n"
        "add.u32 xa, sa, %181;\n"
        "mov.b32 {lo,hi}, r0;\n"
        "mov.b32 rl, {lo,lo};\n"
        "mov.b32 rh, {hi,hi};\n"
        "mul.bf16x2 x0, x0, rl;\n"
        "mul.bf16x2 x1, x1, rl;\n"
        "mul.bf16x2 x2, x2, rh;\n"
        "mul.bf16x2 x3, x3, rh;\n"
        "mma.sync.aligned.m16n8k16.row.col.f32.bf16.bf16.f32 {%32,%33,%34,%35}, {b0,b1,b2,b3}, {x0,x1}, {%32,%33,%34,%35};\n"
        "mma.sync.aligned.m16n8k16.row.col.f32.bf16.bf16.f32 {%36,%37,%38,%39}, {b0,b1,b2,b3}, {x2,x3}, {%36,%37,%38,%39};\n"
        "ld.shared.v4.u32 {x0,x1,x2,x3}, [xa+0];\n"
        "tanh.approx.f32 t0, p0;\n"
        "tanh.approx.f32 t1, p2;\n"
        "fma.rn.f32 t0, p0, t0, p0;\n"
        "fma.rn.f32 t1, p2, t1, p2;\n"
        "cvt.rn.bf16x2.f32 r0, t1, t0;\n"
        "mov.b32 {lo,hi}, r1;\n"
        "mov.b32 rl, {lo,lo};\n"
        "mov.b32 rh, {hi,hi};\n"
        "mul.bf16x2 x4, x4, rl;\n"
        "mul.bf16x2 x5, x5, rl;\n"
        "mul.bf16x2 x6, x6, rh;\n"
        "mul.bf16x2 x7, x7, rh;\n"
        "mma.sync.aligned.m16n8k16.row.col.f32.bf16.bf16.f32 {%40,%41,%42,%43}, {b0,b1,b2,b3}, {x4,x5}, {%40,%41,%42,%43};\n"
        "mma.sync.aligned.m16n8k16.row.col.f32.bf16.bf16.f32 {%44,%45,%46,%47}, {b0,b1,b2,b3}, {x6,x7}, {%44,%45,%46,%47};\n"
        "ld.shared.v4.u32 {x4,x5,x6,x7}, [xa+128];\n"
        "tanh.approx.f32 t0, p4;\n"
        "tanh.approx.f32 t1, p6;\n"
        "fma.rn.f32 t0, p4, t0, p4;\n"
        "fma.rn.f32 t1, p6, t1, p6;\n"
        "cvt.rn.bf16x2.f32 r1, t1, t0;\n"
        "mma.sync.aligned.m16n8k8.row.col.f32.bf16.bf16.f32 {d0,d1,d2,d3}, {%177,%178}, {yb}, {fz,fz,fz,fz};\n"
        "cvt.rn.bf16x2.f32 a0, d2, d0;\n"
        "cvt.rn.bf16x2.f32 a1, d3, d1;\n"
        "mov.b32 {lo,hi}, r2;\n"
        "mov.b32 rl, {lo,lo};\n"
        "mov.b32 rh, {hi,hi};\n"
        "mul.bf16x2 x8, x8, rl;\n"
        "mul.bf16x2 x9, x9, rl;\n"
        "mul.bf16x2 x10, x10, rh;\n"
        "mul.bf16x2 x11, x11, rh;\n"
        "mma.sync.aligned.m16n8k16.row.col.f32.bf16.bf16.f32 {%48,%49,%50,%51}, {b0,b1,b2,b3}, {x8,x9}, {%48,%49,%50,%51};\n"
        "mma.sync.aligned.m16n8k16.row.col.f32.bf16.bf16.f32 {%52,%53,%54,%55}, {b0,b1,b2,b3}, {x10,x11}, {%52,%53,%54,%55};\n"
        "ld.shared.v4.u32 {x8,x9,x10,x11}, [xa+256];\n"
        "tanh.approx.f32 t0, p8;\n"
        "tanh.approx.f32 t1, p10;\n"
        "fma.rn.f32 t0, p8, t0, p8;\n"
        "fma.rn.f32 t1, p10, t1, p10;\n"
        "cvt.rn.bf16x2.f32 r2, t1, t0;\n"
        "mma.sync.aligned.m16n8k8.row.col.f32.bf16.bf16.f32 {d0,d1,d2,d3}, {%179,%180}, {yb}, {fz,fz,fz,fz};\n"
        "cvt.rn.bf16x2.f32 a2, d2, d0;\n"
        "cvt.rn.bf16x2.f32 a3, d3, d1;\n"
        "mov.b32 {lo,hi}, r3;\n"
        "mov.b32 rl, {lo,lo};\n"
        "mov.b32 rh, {hi,hi};\n"
        "mul.bf16x2 x12, x12, rl;\n"
        "mul.bf16x2 x13, x13, rl;\n"
        "mul.bf16x2 x14, x14, rh;\n"
        "mul.bf16x2 x15, x15, rh;\n"
        "mma.sync.aligned.m16n8k16.row.col.f32.bf16.bf16.f32 {%56,%57,%58,%59}, {b0,b1,b2,b3}, {x12,x13}, {%56,%57,%58,%59};\n"
        "mma.sync.aligned.m16n8k16.row.col.f32.bf16.bf16.f32 {%60,%61,%62,%63}, {b0,b1,b2,b3}, {x14,x15}, {%60,%61,%62,%63};\n"
        "ld.shared.v4.u32 {x12,x13,x14,x15}, [xa+384];\n"
        "tanh.approx.f32 t0, p12;\n"
        "tanh.approx.f32 t1, p14;\n"
        "fma.rn.f32 t0, p12, t0, p12;\n"
        "fma.rn.f32 t1, p14, t1, p14;\n"
        "cvt.rn.bf16x2.f32 r3, t1, t0;\n"
        "mov.b32 {lo,hi}, r0;\n"
        "mov.b32 rl, {lo,lo};\n"
        "mov.b32 rh, {hi,hi};\n"
        "mul.bf16x2 x0, x0, rl;\n"
        "mul.bf16x2 x1, x1, rl;\n"
        "mul.bf16x2 x2, x2, rh;\n"
        "mul.bf16x2 x3, x3, rh;\n"
        "mov.b32 {lo,hi}, r1;\n"
        "mov.b32 rl, {lo,lo};\n"
        "mov.b32 rh, {hi,hi};\n"
        "mul.bf16x2 x4, x4, rl;\n"
        "mul.bf16x2 x5, x5, rl;\n"
        "mul.bf16x2 x6, x6, rh;\n"
        "mul.bf16x2 x7, x7, rh;\n"
        "brx.idx.uni la, TA_%=;\n"
        "B2_%=:\n"
        "and.b32 la, ln, 255;\n"
        "shr.u32 lb, ln, 8;\n"
        "add.u32 ma, sa, %182;\n"
        "ldmatrix.sync.aligned.m8n8.x1.shared.b16 {yb}, [ma];\n"
        "add.u32 xa, sa, %181;\n"
        "mov.b32 {lo,hi}, r0;\n"
        "mov.b32 rl, {lo,lo};\n"
        "mov.b32 rh, {hi,hi};\n"
        "mul.bf16x2 x0, x0, rl;\n"
        "mul.bf16x2 x1, x1, rl;\n"
        "mul.bf16x2 x2, x2, rh;\n"
        "mul.bf16x2 x3, x3, rh;\n"
        "mma.sync.aligned.m16n8k16.row.col.f32.bf16.bf16.f32 {%64,%65,%66,%67}, {b0,b1,b2,b3}, {x0,x1}, {%64,%65,%66,%67};\n"
        "mma.sync.aligned.m16n8k16.row.col.f32.bf16.bf16.f32 {%68,%69,%70,%71}, {b0,b1,b2,b3}, {x2,x3}, {%68,%69,%70,%71};\n"
        "ld.shared.v4.u32 {x0,x1,x2,x3}, [xa+0];\n"
        "tanh.approx.f32 t0, p0;\n"
        "tanh.approx.f32 t1, p2;\n"
        "fma.rn.f32 t0, p0, t0, p0;\n"
        "fma.rn.f32 t1, p2, t1, p2;\n"
        "cvt.rn.bf16x2.f32 r0, t1, t0;\n"
        "mov.b32 {lo,hi}, r1;\n"
        "mov.b32 rl, {lo,lo};\n"
        "mov.b32 rh, {hi,hi};\n"
        "mul.bf16x2 x4, x4, rl;\n"
        "mul.bf16x2 x5, x5, rl;\n"
        "mul.bf16x2 x6, x6, rh;\n"
        "mul.bf16x2 x7, x7, rh;\n"
        "mma.sync.aligned.m16n8k16.row.col.f32.bf16.bf16.f32 {%72,%73,%74,%75}, {b0,b1,b2,b3}, {x4,x5}, {%72,%73,%74,%75};\n"
        "mma.sync.aligned.m16n8k16.row.col.f32.bf16.bf16.f32 {%76,%77,%78,%79}, {b0,b1,b2,b3}, {x6,x7}, {%76,%77,%78,%79};\n"
        "ld.shared.v4.u32 {x4,x5,x6,x7}, [xa+128];\n"
        "tanh.approx.f32 t0, p4;\n"
        "tanh.approx.f32 t1, p6;\n"
        "fma.rn.f32 t0, p4, t0, p4;\n"
        "fma.rn.f32 t1, p6, t1, p6;\n"
        "cvt.rn.bf16x2.f32 r1, t1, t0;\n"
        "mma.sync.aligned.m16n8k8.row.col.f32.bf16.bf16.f32 {d0,d1,d2,d3}, {%177,%178}, {yb}, {fz,fz,fz,fz};\n"
        "cvt.rn.bf16x2.f32 a0, d2, d0;\n"
        "cvt.rn.bf16x2.f32 a1, d3, d1;\n"
        "mov.b32 {lo,hi}, r2;\n"
        "mov.b32 rl, {lo,lo};\n"
        "mov.b32 rh, {hi,hi};\n"
        "mul.bf16x2 x8, x8, rl;\n"
        "mul.bf16x2 x9, x9, rl;\n"
        "mul.bf16x2 x10, x10, rh;\n"
        "mul.bf16x2 x11, x11, rh;\n"
        "mma.sync.aligned.m16n8k16.row.col.f32.bf16.bf16.f32 {%80,%81,%82,%83}, {b0,b1,b2,b3}, {x8,x9}, {%80,%81,%82,%83};\n"
        "mma.sync.aligned.m16n8k16.row.col.f32.bf16.bf16.f32 {%84,%85,%86,%87}, {b0,b1,b2,b3}, {x10,x11}, {%84,%85,%86,%87};\n"
        "ld.shared.v4.u32 {x8,x9,x10,x11}, [xa+256];\n"
        "tanh.approx.f32 t0, p8;\n"
        "tanh.approx.f32 t1, p10;\n"
        "fma.rn.f32 t0, p8, t0, p8;\n"
        "fma.rn.f32 t1, p10, t1, p10;\n"
        "cvt.rn.bf16x2.f32 r2, t1, t0;\n"
        "mma.sync.aligned.m16n8k8.row.col.f32.bf16.bf16.f32 {d0,d1,d2,d3}, {%179,%180}, {yb}, {fz,fz,fz,fz};\n"
        "cvt.rn.bf16x2.f32 a2, d2, d0;\n"
        "cvt.rn.bf16x2.f32 a3, d3, d1;\n"
        "mov.b32 {lo,hi}, r3;\n"
        "mov.b32 rl, {lo,lo};\n"
        "mov.b32 rh, {hi,hi};\n"
        "mul.bf16x2 x12, x12, rl;\n"
        "mul.bf16x2 x13, x13, rl;\n"
        "mul.bf16x2 x14, x14, rh;\n"
        "mul.bf16x2 x15, x15, rh;\n"
        "mma.sync.aligned.m16n8k16.row.col.f32.bf16.bf16.f32 {%88,%89,%90,%91}, {b0,b1,b2,b3}, {x12,x13}, {%88,%89,%90,%91};\n"
        "mma.sync.aligned.m16n8k16.row.col.f32.bf16.bf16.f32 {%92,%93,%94,%95}, {b0,b1,b2,b3}, {x14,x15}, {%92,%93,%94,%95};\n"
        "ld.shared.v4.u32 {x12,x13,x14,x15}, [xa+384];\n"
        "tanh.approx.f32 t0, p12;\n"
        "tanh.approx.f32 t1, p14;\n"
        "fma.rn.f32 t0, p12, t0, p12;\n"
        "fma.rn.f32 t1, p14, t1, p14;\n"
        "cvt.rn.bf16x2.f32 r3, t1, t0;\n"
        "mov.b32 {lo,hi}, r0;\n"
        "mov.b32 rl, {lo,lo};\n"
        "mov.b32 rh, {hi,hi};\n"
        "mul.bf16x2 x0, x0, rl;\n"
        "mul.bf16x2 x1, x1, rl;\n"
        "mul.bf16x2 x2, x2, rh;\n"
        "mul.bf16x2 x3, x3, rh;\n"
        "mov.b32 {lo,hi}, r1;\n"
        "mov.b32 rl, {lo,lo};\n"
        "mov.b32 rh, {hi,hi};\n"
        "mul.bf16x2 x4, x4, rl;\n"
        "mul.bf16x2 x5, x5, rl;\n"
        "mul.bf16x2 x6, x6, rh;\n"
        "mul.bf16x2 x7, x7, rh;\n"
        "brx.idx.uni la, TA_%=;\n"
        "B3_%=:\n"
        "and.b32 la, ln, 255;\n"
        "shr.u32 lb, ln, 8;\n"
        "add.u32 ma, sa, %182;\n"
        "ldmatrix.sync.aligned.m8n8.x1.shared.b16 {yb}, [ma];\n"
        "add.u32 xa, sa, %181;\n"
        "mov.b32 {lo,hi}, r0;\n"
        "mov.b32 rl, {lo,lo};\n"
        "mov.b32 rh, {hi,hi};\n"
        "mul.bf16x2 x0, x0, rl;\n"
        "mul.bf16x2 x1, x1, rl;\n"
        "mul.bf16x2 x2, x2, rh;\n"
        "mul.bf16x2 x3, x3, rh;\n"
        "mma.sync.aligned.m16n8k16.row.col.f32.bf16.bf16.f32 {%96,%97,%98,%99}, {b0,b1,b2,b3}, {x0,x1}, {%96,%97,%98,%99};\n"
        "mma.sync.aligned.m16n8k16.row.col.f32.bf16.bf16.f32 {%100,%101,%102,%103}, {b0,b1,b2,b3}, {x2,x3}, {%100,%101,%102,%103};\n"
        "ld.shared.v4.u32 {x0,x1,x2,x3}, [xa+0];\n"
        "tanh.approx.f32 t0, p0;\n"
        "tanh.approx.f32 t1, p2;\n"
        "fma.rn.f32 t0, p0, t0, p0;\n"
        "fma.rn.f32 t1, p2, t1, p2;\n"
        "cvt.rn.bf16x2.f32 r0, t1, t0;\n"
        "mov.b32 {lo,hi}, r1;\n"
        "mov.b32 rl, {lo,lo};\n"
        "mov.b32 rh, {hi,hi};\n"
        "mul.bf16x2 x4, x4, rl;\n"
        "mul.bf16x2 x5, x5, rl;\n"
        "mul.bf16x2 x6, x6, rh;\n"
        "mul.bf16x2 x7, x7, rh;\n"
        "mma.sync.aligned.m16n8k16.row.col.f32.bf16.bf16.f32 {%104,%105,%106,%107}, {b0,b1,b2,b3}, {x4,x5}, {%104,%105,%106,%107};\n"
        "mma.sync.aligned.m16n8k16.row.col.f32.bf16.bf16.f32 {%108,%109,%110,%111}, {b0,b1,b2,b3}, {x6,x7}, {%108,%109,%110,%111};\n"
        "ld.shared.v4.u32 {x4,x5,x6,x7}, [xa+128];\n"
        "tanh.approx.f32 t0, p4;\n"
        "tanh.approx.f32 t1, p6;\n"
        "fma.rn.f32 t0, p4, t0, p4;\n"
        "fma.rn.f32 t1, p6, t1, p6;\n"
        "cvt.rn.bf16x2.f32 r1, t1, t0;\n"
        "mma.sync.aligned.m16n8k8.row.col.f32.bf16.bf16.f32 {d0,d1,d2,d3}, {%177,%178}, {yb}, {fz,fz,fz,fz};\n"
        "cvt.rn.bf16x2.f32 a0, d2, d0;\n"
        "cvt.rn.bf16x2.f32 a1, d3, d1;\n"
        "mov.b32 {lo,hi}, r2;\n"
        "mov.b32 rl, {lo,lo};\n"
        "mov.b32 rh, {hi,hi};\n"
        "mul.bf16x2 x8, x8, rl;\n"
        "mul.bf16x2 x9, x9, rl;\n"
        "mul.bf16x2 x10, x10, rh;\n"
        "mul.bf16x2 x11, x11, rh;\n"
        "mma.sync.aligned.m16n8k16.row.col.f32.bf16.bf16.f32 {%112,%113,%114,%115}, {b0,b1,b2,b3}, {x8,x9}, {%112,%113,%114,%115};\n"
        "mma.sync.aligned.m16n8k16.row.col.f32.bf16.bf16.f32 {%116,%117,%118,%119}, {b0,b1,b2,b3}, {x10,x11}, {%116,%117,%118,%119};\n"
        "ld.shared.v4.u32 {x8,x9,x10,x11}, [xa+256];\n"
        "tanh.approx.f32 t0, p8;\n"
        "tanh.approx.f32 t1, p10;\n"
        "fma.rn.f32 t0, p8, t0, p8;\n"
        "fma.rn.f32 t1, p10, t1, p10;\n"
        "cvt.rn.bf16x2.f32 r2, t1, t0;\n"
        "mma.sync.aligned.m16n8k8.row.col.f32.bf16.bf16.f32 {d0,d1,d2,d3}, {%179,%180}, {yb}, {fz,fz,fz,fz};\n"
        "cvt.rn.bf16x2.f32 a2, d2, d0;\n"
        "cvt.rn.bf16x2.f32 a3, d3, d1;\n"
        "mov.b32 {lo,hi}, r3;\n"
        "mov.b32 rl, {lo,lo};\n"
        "mov.b32 rh, {hi,hi};\n"
        "mul.bf16x2 x12, x12, rl;\n"
        "mul.bf16x2 x13, x13, rl;\n"
        "mul.bf16x2 x14, x14, rh;\n"
        "mul.bf16x2 x15, x15, rh;\n"
        "mma.sync.aligned.m16n8k16.row.col.f32.bf16.bf16.f32 {%120,%121,%122,%123}, {b0,b1,b2,b3}, {x12,x13}, {%120,%121,%122,%123};\n"
        "mma.sync.aligned.m16n8k16.row.col.f32.bf16.bf16.f32 {%124,%125,%126,%127}, {b0,b1,b2,b3}, {x14,x15}, {%124,%125,%126,%127};\n"
        "ld.shared.v4.u32 {x12,x13,x14,x15}, [xa+384];\n"
        "tanh.approx.f32 t0, p12;\n"
        "tanh.approx.f32 t1, p14;\n"
        "fma.rn.f32 t0, p12, t0, p12;\n"
        "fma.rn.f32 t1, p14, t1, p14;\n"
        "cvt.rn.bf16x2.f32 r3, t1, t0;\n"
        "mov.b32 {lo,hi}, r0;\n"
        "mov.b32 rl, {lo,lo};\n"
        "mov.b32 rh, {hi,hi};\n"
        "mul.bf16x2 x0, x0, rl;\n"
        "mul.bf16x2 x1, x1, rl;\n"
        "mul.bf16x2 x2, x2, rh;\n"
        "mul.bf16x2 x3, x3, rh;\n"
        "mov.b32 {lo,hi}, r1;\n"
        "mov.b32 rl, {lo,lo};\n"
        "mov.b32 rh, {hi,hi};\n"
        "mul.bf16x2 x4, x4, rl;\n"
        "mul.bf16x2 x5, x5, rl;\n"
        "mul.bf16x2 x6, x6, rh;\n"
        "mul.bf16x2 x7, x7, rh;\n"
        "brx.idx.uni la, TA_%=;\n"
        "B4_%=:\n"
        "and.b32 la, ln, 255;\n"
        "shr.u32 lb, ln, 8;\n"
        "add.u32 ma, sa, %182;\n"
        "ldmatrix.sync.aligned.m8n8.x1.shared.b16 {yb}, [ma];\n"
        "add.u32 xa, sa, %181;\n"
        "mov.b32 {lo,hi}, r0;\n"
        "mov.b32 rl, {lo,lo};\n"
        "mov.b32 rh, {hi,hi};\n"
        "mul.bf16x2 x0, x0, rl;\n"
        "mul.bf16x2 x1, x1, rl;\n"
        "mul.bf16x2 x2, x2, rh;\n"
        "mul.bf16x2 x3, x3, rh;\n"
        "mma.sync.aligned.m16n8k16.row.col.f32.bf16.bf16.f32 {%128,%129,%130,%131}, {b0,b1,b2,b3}, {x0,x1}, {%128,%129,%130,%131};\n"
        "mma.sync.aligned.m16n8k16.row.col.f32.bf16.bf16.f32 {%132,%133,%134,%135}, {b0,b1,b2,b3}, {x2,x3}, {%132,%133,%134,%135};\n"
        "ld.shared.v4.u32 {x0,x1,x2,x3}, [xa+0];\n"
        "tanh.approx.f32 t0, p0;\n"
        "tanh.approx.f32 t1, p2;\n"
        "fma.rn.f32 t0, p0, t0, p0;\n"
        "fma.rn.f32 t1, p2, t1, p2;\n"
        "cvt.rn.bf16x2.f32 r0, t1, t0;\n"
        "mov.b32 {lo,hi}, r1;\n"
        "mov.b32 rl, {lo,lo};\n"
        "mov.b32 rh, {hi,hi};\n"
        "mul.bf16x2 x4, x4, rl;\n"
        "mul.bf16x2 x5, x5, rl;\n"
        "mul.bf16x2 x6, x6, rh;\n"
        "mul.bf16x2 x7, x7, rh;\n"
        "mma.sync.aligned.m16n8k16.row.col.f32.bf16.bf16.f32 {%136,%137,%138,%139}, {b0,b1,b2,b3}, {x4,x5}, {%136,%137,%138,%139};\n"
        "mma.sync.aligned.m16n8k16.row.col.f32.bf16.bf16.f32 {%140,%141,%142,%143}, {b0,b1,b2,b3}, {x6,x7}, {%140,%141,%142,%143};\n"
        "ld.shared.v4.u32 {x4,x5,x6,x7}, [xa+128];\n"
        "tanh.approx.f32 t0, p4;\n"
        "tanh.approx.f32 t1, p6;\n"
        "fma.rn.f32 t0, p4, t0, p4;\n"
        "fma.rn.f32 t1, p6, t1, p6;\n"
        "cvt.rn.bf16x2.f32 r1, t1, t0;\n"
        "mma.sync.aligned.m16n8k8.row.col.f32.bf16.bf16.f32 {d0,d1,d2,d3}, {%177,%178}, {yb}, {fz,fz,fz,fz};\n"
        "cvt.rn.bf16x2.f32 a0, d2, d0;\n"
        "cvt.rn.bf16x2.f32 a1, d3, d1;\n"
        "mov.b32 {lo,hi}, r2;\n"
        "mov.b32 rl, {lo,lo};\n"
        "mov.b32 rh, {hi,hi};\n"
        "mul.bf16x2 x8, x8, rl;\n"
        "mul.bf16x2 x9, x9, rl;\n"
        "mul.bf16x2 x10, x10, rh;\n"
        "mul.bf16x2 x11, x11, rh;\n"
        "mma.sync.aligned.m16n8k16.row.col.f32.bf16.bf16.f32 {%144,%145,%146,%147}, {b0,b1,b2,b3}, {x8,x9}, {%144,%145,%146,%147};\n"
        "mma.sync.aligned.m16n8k16.row.col.f32.bf16.bf16.f32 {%148,%149,%150,%151}, {b0,b1,b2,b3}, {x10,x11}, {%148,%149,%150,%151};\n"
        "ld.shared.v4.u32 {x8,x9,x10,x11}, [xa+256];\n"
        "tanh.approx.f32 t0, p8;\n"
        "tanh.approx.f32 t1, p10;\n"
        "fma.rn.f32 t0, p8, t0, p8;\n"
        "fma.rn.f32 t1, p10, t1, p10;\n"
        "cvt.rn.bf16x2.f32 r2, t1, t0;\n"
        "mma.sync.aligned.m16n8k8.row.col.f32.bf16.bf16.f32 {d0,d1,d2,d3}, {%179,%180}, {yb}, {fz,fz,fz,fz};\n"
        "cvt.rn.bf16x2.f32 a2, d2, d0;\n"
        "cvt.rn.bf16x2.f32 a3, d3, d1;\n"
        "mov.b32 {lo,hi}, r3;\n"
        "mov.b32 rl, {lo,lo};\n"
        "mov.b32 rh, {hi,hi};\n"
        "mul.bf16x2 x12, x12, rl;\n"
        "mul.bf16x2 x13, x13, rl;\n"
        "mul.bf16x2 x14, x14, rh;\n"
        "mul.bf16x2 x15, x15, rh;\n"
        "mma.sync.aligned.m16n8k16.row.col.f32.bf16.bf16.f32 {%152,%153,%154,%155}, {b0,b1,b2,b3}, {x12,x13}, {%152,%153,%154,%155};\n"
        "mma.sync.aligned.m16n8k16.row.col.f32.bf16.bf16.f32 {%156,%157,%158,%159}, {b0,b1,b2,b3}, {x14,x15}, {%156,%157,%158,%159};\n"
        "ld.shared.v4.u32 {x12,x13,x14,x15}, [xa+384];\n"
        "tanh.approx.f32 t0, p12;\n"
        "tanh.approx.f32 t1, p14;\n"
        "fma.rn.f32 t0, p12, t0, p12;\n"
        "fma.rn.f32 t1, p14, t1, p14;\n"
        "cvt.rn.bf16x2.f32 r3, t1, t0;\n"
        "mov.b32 {lo,hi}, r0;\n"
        "mov.b32 rl, {lo,lo};\n"
        "mov.b32 rh, {hi,hi};\n"
        "mul.bf16x2 x0, x0, rl;\n"
        "mul.bf16x2 x1, x1, rl;\n"
        "mul.bf16x2 x2, x2, rh;\n"
        "mul.bf16x2 x3, x3, rh;\n"
        "mov.b32 {lo,hi}, r1;\n"
        "mov.b32 rl, {lo,lo};\n"
        "mov.b32 rh, {hi,hi};\n"
        "mul.bf16x2 x4, x4, rl;\n"
        "mul.bf16x2 x5, x5, rl;\n"
        "mul.bf16x2 x6, x6, rh;\n"
        "mul.bf16x2 x7, x7, rh;\n"
        "brx.idx.uni la, TA_%=;\n"
        "EXIT_%=:\n"
        "mov.u32 %160, ring;\n"
        "}\n"
        : "+f"(acc[0][0][0][0]), "+f"(acc[0][0][0][1]), "+f"(acc[0][0][0][2]), "+f"(acc[0][0][0][3]), "+f"(acc[0][0][1][0]),
          "+f"(acc[0][0][1][1]), "+f"(acc[0][0][1][2]), "+f"(acc[0][0][1][3]), "+f"(acc[0][1][0][0]), "+f"(acc[0][1][0][1]),
          "+f"(acc[0][1][0][2]), "+f"(acc[0][1][0][3]), "+f"(acc[0][1][1][0]), "+f"(acc[0][1][1][1]), "+f"(acc[0][1][1][2]),
          "+f"(acc[0][1][1][3]), "+f"(acc[0][2][0][0]), "+f"(acc[0][2][0][1]), "+f"(acc[0][2][0][2]), "+f"(acc[0][2][0][3]),
          "+f"(acc[0][2][1][0]), "+f"(acc[0][2][1][1]), "+f"(acc[0][2][1][2]), "+f"(acc[0][2][1][3]), "+f"(acc[0][3][0][0]),
          "+f"(acc[0][3][0][1]), "+f"(acc[0][3][0][2]), "+f"(acc[0][3][0][3]), "+f"(acc[0][3][1][0]), "+f"(acc[0][3][1][1]),
          "+f"(acc[0][3][1][2]), "+f"(acc[0][3][1][3]), "+f"(acc[1][0][0][0]), "+f"(acc[1][0][0][1]), "+f"(acc[1][0][0][2]),
          "+f"(acc[1][0][0][3]), "+f"(acc[1][0][1][0]), "+f"(acc[1][0][1][1]), "+f"(acc[1][0][1][2]), "+f"(acc[1][0][1][3]),
          "+f"(acc[1][1][0][0]), "+f"(acc[1][1][0][1]), "+f"(acc[1][1][0][2]), "+f"(acc[1][1][0][3]), "+f"(acc[1][1][1][0]),
          "+f"(acc[1][1][1][1]), "+f"(acc[1][1][1][2]), "+f"(acc[1][1][1][3]), "+f"(acc[1][2][0][0]), "+f"(acc[1][2][0][1]),
          "+f"(acc[1][2][0][2]), "+f"(acc[1][2][0][3]), "+f"(acc[1][2][1][0]), "+f"(acc[1][2][1][1]), "+f"(acc[1][2][1][2]),
          "+f"(acc[1][2][1][3]), "+f"(acc[1][3][0][0]), "+f"(acc[1][3][0][1]), "+f"(acc[1][3][0][2]), "+f"(acc[1][3][0][3]),
          "+f"(acc[1][3][1][0]), "+f"(acc[1][3][1][1]), "+f"(acc[1][3][1][2]), "+f"(acc[1][3][1][3]), "+f"(acc[2][0][0][0]),
          "+f"(acc[2][0][0][1]), "+f"(acc[2][0][0][2]), "+f"(acc[2][0][0][3]), "+f"(acc[2][0][1][0]), "+f"(acc[2][0][1][1]),
          "+f"(acc[2][0][1][2]), "+f"(acc[2][0][1][3]), "+f"(acc[2][1][0][0]), "+f"(acc[2][1][0][1]), "+f"(acc[2][1][0][2]),
          "+f"(acc[2][1][0][3]), "+f"(acc[2][1][1][0]), "+f"(acc[2][1][1][1]), "+f"(acc[2][1][1][2]), "+f"(acc[2][1][1][3]),
          "+f"(acc[2][2][0][0]), "+f"(acc[2][2][0][1]), "+f"(acc[2][2][0][2]), "+f"(acc[2][2][0][3]), "+f"(acc[2][2][1][0]),
          "+f"(acc[2][2][1][1]), "+f"(acc[2][2][1][2]), "+f"(acc[2][2][1][3]), "+f"(acc[2][3][0][0]), "+f"(acc[2][3][0][1]),
          "+f"(acc[2][3][0][2]), "+f"(acc[2][3][0][3]), "+f"(acc[2][3][1][0]), "+f"(acc[2][3][1][1]), "+f"(acc[2][3][1][2]),
          "+f"(acc[2][3][1][3]), "+f"(acc[3][0][0][0]), "+f"(acc[3][0][0][1]), "+f"(acc[3][0][0][2]), "+f"(acc[3][0][0][3]),
          "+f"(acc[3][0][1][0]), "+f"(acc[3][0][1][1]), "+f"(acc[3][0][1][2]), "+f"(acc[3][0][1][3]), "+f"(acc[3][1][0][0]),
          "+f"(acc[3][1][0][1]), "+f"(acc[3][1][0][2]), "+f"(acc[3][1][0][3]), "+f"(acc[3][1][1][0]), "+f"(acc[3][1][1][1]),
          "+f"(acc[3][1][1][2]), "+f"(acc[3][1][1][3]), "+f"(acc[3][2][0][0]), "+f"(acc[3][2][0][1]), "+f"(acc[3][2][0][2]),
          "+f"(acc[3][2][0][3]), "+f"(acc[3][2][1][0]), "+f"(acc[3][2][1][1]), "+f"(acc[3][2][1][2]), "+f"(acc[3][2][1][3]),
          "+f"(acc[3][3][0][0]), "+f"(acc[3][3][0][1]), "+f"(acc[3][3][0][2]), "+f"(acc[3][3][0][3]), "+f"(acc[3][3][1][0]),
          "+f"(acc[3][3][1][1]), "+f"(acc[3][3][1][2]), "+f"(acc[3][3][1][3]), "+f"(acc[4][0][0][0]), "+f"(acc[4][0][0][1]),
          "+f"(acc[4][0][0][2]), "+f"(acc[4][0][0][3]), "+f"(acc[4][0][1][0]), "+f"(acc[4][0][1][1]), "+f"(acc[4][0][1][2]),
          "+f"(acc[4][0][1][3]), "+f"(acc[4][1][0][0]), "+f"(acc[4][1][0][1]), "+f"(acc[4][1][0][2]), "+f"(acc[4][1][0][3]),
          "+f"(acc[4][1][1][0]), "+f"(acc[4][1][1][1]), "+f"(acc[4][1][1][2]), "+f"(acc[4][1][1][3]), "+f"(acc[4][2][0][0]),
          "+f"(acc[4][2][0][1]), "+f"(acc[4][2][0][2]), "+f"(acc[4][2][0][3]), "+f"(acc[4][2][1][0]), "+f"(acc[4][2][1][1]),
          "+f"(acc[4][2][1][2]), "+f"(acc[4][2][1][3]), "+f"(acc[4][3][0][0]), "+f"(acc[4][3][0][1]), "+f"(acc[4][3][0][2]),
          "+f"(acc[4][3][0][3]), "+f"(acc[4][3][1][0]), "+f"(acc[4][3][1][1]), "+f"(acc[4][3][1][2]), "+f"(acc[4][3][1][3]),
          "+r"(ring)
        : "r"(wf[0][0]), "r"(wf[0][1]), "r"(wf[0][2]), "r"(wf[0][3]), "r"(wf[1][0]), "r"(wf[1][1]), "r"(wf[1][2]), "r"(wf[1][3]),
          "r"(wf[2][0]), "r"(wf[2][1]), "r"(wf[2][2]), "r"(wf[2][3]), "r"(wf[3][0]), "r"(wf[3][1]), "r"(wf[3][2]), "r"(wf[3][3]),
          "r"(cgf[0]), "r"(cgf[1]), "r"(cgf[2]), "r"(cgf[3]), "r"(xoff), "r"(moff), "r"(rec)
        : "memory");
}

__device__ __noinline__ void generic_path(float* sagg, const __nv_bfloat16* x, const int* src, const int* dst,
                                          const __nv_bfloat16* Y, const __nv_bfloat16* ef, const __nv_bfloat16* w_rad,
                                          const __nv_bfloat16* cg, int x0, int x1) {
    const int tid = threadIdx.x, lane = tid & 31, blk = blockIdx.x;
    for (int k = 0; k < 2; k++)
        for (int r = 0; r < min(k == 0 ? x0 : x1, 32); r++) {
            uint32_t* p2 = g_mail2 + (blk * NSRC + ((tid + k * NTHR) >> 3)) * 32 + r;
            uint32_t v;
            int it = 0;
            do {
                asm volatile("ld.relaxed.gpu.global.u32 %0, [%1];" : "=r"(v) : "l"(p2) : "memory");
                if (++it > (1 << 20)) __trap();
            } while (v == 0);
            *p2 = 0;
        }
    if (tid < 8 * NG) mbar_inval(smem_u32(sagg) + (tid >> 1) * STAGE + 4 * ROWP + (tid & 1) * 8);
    __syncthreads();
    for (int i = tid; i < NPB * 512; i += NTHR) sagg[i] = 0.f;
    __syncthreads();
    for (int e0 = tid & ~31; e0 < N_EDGES; e0 += NTHR) {
        uint32_t bm = __ballot_sync(~0u, dst[e0 + lane] / NPB == blk);
        while (bm) {
            const int e = e0 + __ffs(bm) - 1, s = src[e], loc = dst[e] - blk * NPB;
            bm &= bm - 1;
            float a[4][4];
            for (int i = 0; i < 4; i++)
                for (int o = 0; o < 4; o++) {
                    a[i][o] = 0.f;
                    for (int f = 0; f < 4; f++)
                        a[i][o] += __bfloat162float(Y[e * 4 + f]) * __bfloat162float(cg[i * 16 + f * 4 + o]);
                }
#pragma unroll 1
            for (int c = lane; c < 128; c += 32) {
                float pre = 0.f;
                for (int k = 0; k < 16; k++)
                    pre += __bfloat162float(ef[e * 16 + k]) * __bfloat162float(w_rad[k * 128 + c]);
                const float R = pre / (1.f + __expf(-pre));
                for (int o = 0; o < 4; o++) {
                    float acc = 0.f;
                    for (int i = 0; i < 4; i++) acc += __bfloat162float(x[(size_t)s * 512 + c * 4 + i]) * a[i][o];
                    atomicAdd(&sagg[loc * 512 + c * 4 + o], R * acc);
                }
            }
        }
    }
    __syncthreads();
}

__device__ __forceinline__ void init_barriers() {
    extern __shared__ __align__(1024) uint8_t smem[];
    const uint32_t sb = smem_u32(smem);
#pragma unroll
    for (int i = 0; i < 4 * NG; i++) {
        mbar_init(sb + i * STAGE + 4 * ROWP, 32);
        mbar_init(sb + i * STAGE + 4 * ROWP + 8, 2);
    }
}

template <int PHASES>
__global__ void __launch_bounds__(NTHR, 1)
tfn_kernel(const __nv_bfloat16* __restrict__ x, const int* __restrict__ src, const int* __restrict__ dst,
           const __nv_bfloat16* __restrict__ Y, const __nv_bfloat16* __restrict__ ef,
           const __nv_bfloat16* __restrict__ w_rad, const __nv_bfloat16* __restrict__ cg,
           const __nv_bfloat16* __restrict__ w_mix, __nv_bfloat16* __restrict__ out) {
    extern __shared__ __align__(1024) uint8_t smem[];
    const int tid = threadIdx.x, lane = tid & 31;
    const int warp = __shfl_sync(~0u, tid >> 5, 0);
    const int blk = blockIdx.x;
    uint32_t sb = smem_u32(smem);
    asm volatile("" : "+r"(sb));
    int* mi = reinterpret_cast<int*>(smem + SM_MISC);

    const int g = lane >> 2, t = lane & 3;
    const uint32_t dump = sb + SC_DUMP + lane * 4;
    int4 d1[2], s1[2];
    constexpr int nq = EPC / 4;
    const bool binner = (PHASES & 1) && blk < NSRC;
    if (binner) {
#pragma unroll
        for (int k = 0; k < 2; k++) {
            const int q = tid + k * NTHR;
            if (q < nq) {
                d1[k] = __ldg(reinterpret_cast<const int4*>(dst + blk * EPC) + q);
                s1[k] = __ldg(reinterpret_cast<const int4*>(src + blk * EPC) + q);
            }
        }
    }
    if (binner) {
        const uint32_t dmy = ((((blk & 3) * 8 + (tid & 7)) << 25) | (80 * 2560 + 1));
#pragma unroll
        for (int k = 0; k < 3; k++)
            if (k < 2 || warp < 1) sts128(sb + SC_MAIL + (tid + k * NTHR) * 16, dmy, dmy + (1u << 30), dmy, dmy + (1u << 30));
        if (tid <= NB / 4) sts128(sb + SC_CNT + tid * 16, 0, 0, 0, 0);
    }
    if (PHASES & 2) {
        if (tid == 160) { sts128(sb + SM_MISC, 0, 0, 0, 0); sts128(sb + SM_MISC + MI_NU * 4, 0, 0, 0, 0); }
        if (tid == 161) {
            mi[MI_SHIFT] = 0;
            *reinterpret_cast<int**>(mi + MI_SHIFT + 4) = g_lag[blk];
        }
        if (tid == 162) g_lag[blk][0] = g_lag[NB + blk][0] = 0;
        if (tid <= 21 * HS / 4) sts128(sb + SC_HIST + tid * 16, 0, 0, 0, 0);
        if (tid < 4 * UCAP) {
#pragma unroll
            for (int k = 0; k < 12; k++) sts32(sb + SM_REC + tid * REC + k * 4, k < 4 ? ~0u : (uint32_t)(blk * 4096 + tid * 8 + 7));
        }
    }
    __syncthreads();
    if (PHASES & 2) {
        if (warp >= 8) cp16(sb + SC_WR + ((tid - 256) ^ ((tid >> 4) & 6)) * 16, w_rad + (tid - 256) * 8);
        if (tid < 8) cp16(sb + SC_WR + 4096 + tid * 16, cg + tid * 8);
        asm volatile("cp.async.commit_group;" ::: "memory");
#pragma unroll
        for (int k = 0; k < 4; k++) {
            const int i = tid + k * NTHR, c = i >> 4;
            cp16(sb + SM_W + c * 256 + (((i & 15) ^ ((c & 2) | (((c >> 4) & 1) << 2))) << 4), w_mix + i * 8);
        }
    }
    if (binner) {
#pragma unroll
        for (int k = 0; k < 2; k++) {
            if (tid + k * NTHR < nq) {
                const uint32_t dd[4] = {(uint32_t)d1[k].x, (uint32_t)d1[k].y, (uint32_t)d1[k].z, (uint32_t)d1[k].w};
                const uint32_t ss[4] = {(uint32_t)s1[k].x, (uint32_t)s1[k].y, (uint32_t)s1[k].z, (uint32_t)s1[k].w};
                uint32_t own[4], rk[4], v[4];
#pragma unroll
                for (int j = 0; j < 4; j++) { own[j] = dd[j] / NPB; rk[j] = atoms_inc(sb + SC_CNT + own[j] * 4); }
#pragma unroll
                for (int j = 0; j < 4; j++) {
                    const uint32_t loc = dd[j] - own[j] * NPB, code = loc + ((loc * 216) >> 12);
                    v[j] = (ss[j] << 18) + code * 2560 + (tid + k * NTHR) * 4 + j + 1;
                    sts32(sb + SC_MAIL + own[j] * 128 + ((min(rk[j], 31u) * 4) ^ ((own[j] & 7) << 4)), v[j]);
                }
                if (max(max(rk[0], rk[1]), max(rk[2], rk[3])) >= 31) {
#pragma unroll
                    for (int j = 0; j < 4; j++)
                        if (rk[j] - 31 < 32)
                            asm volatile("st.relaxed.gpu.global.u32 [%0], %1;" ::"l"(g_mail2 + (own[j] * NSRC + blk) * 32 + rk[j] - 31), "r"(v[j]) : "memory");
                }
            }
        }
        __syncwarp();
        asm volatile("red.shared.max.u32 [%0], %1;" ::"r"(lane == 0 ? sb + SC_CNT + NB * 4 : dump), "r"(gtime()) : "memory");
        STAMP(1);
    }
    asm volatile("cp.async.wait_group 0;" ::: "memory");
    __syncthreads();
    if (binner) {
        const uint32_t hdr = 0xc0000000u | ((lds32(sb + SC_CNT + NB * 4) << 7) & 0x3ffff000u);
        uint4 mv[3];
        uint32_t mc[3];
#pragma unroll
        for (int k = 0; k < 3; k++)
            if (k < 2 || warp < 1) {
                const int j = tid + k * NTHR, own = j >> 3;
                mv[k] = lds128(sb + SC_MAIL + own * 128 + (((j ^ own) & 7) << 4));
                mc[k] = lds32(sb + SC_CNT + own * 4);
            }
#pragma unroll
        for (int k = 0; k < 3; k++)
            if (k < 2 || warp < 1) {
                const int j = tid + k * NTHR;
                asm volatile("st.relaxed.gpu.global.v4.u32 [%0], {%1,%2,%3,%4};" ::"l"(g_mail + ((j >> 3) * NSRC + blk) * 8 + (j & 7)),
                             "r"(mv[k].x), "r"(mv[k].y), "r"(mv[k].z), "r"((j & 7) == 7 ? hdr | mc[k] : mv[k].w) : "memory");
            }
        STAMP(2);
    }
    if (!(PHASES & 2)) return;
    const uint32_t tpub = (uint32_t)clock() + (blk < NSRC ? 0 : IDLE_EST);
    if (warp >= 7) {
        uint32_t f[4];
        if (warp >= 8) {
            uint32_t w[4];
#pragma unroll
            for (int j = 0; j < 4; j++)
                w[j] = mul_lo(lds32(sb + SC_WR + (2 * t + (j & 1) + (j >> 1) * 8) * 256 + ((((warp - 8) * 8 + g) * 4) ^ (t << 5))), 0x3f003f00u);
            f[0] = __byte_perm(w[0], w[1], 0x5410); f[1] = __byte_perm(w[0], w[1], 0x7632);
            f[2] = __byte_perm(w[2], w[3], 0x5410); f[3] = __byte_perm(w[2], w[3], 0x7632);
        } else {
#pragma unroll
            for (int i = 0; i < 4; i++) {
                const uint32_t ca = sb + SC_WR + 4096 + (i * 16 + (t & 1) * 8 + (g & 3)) * 2;
                f[i] = (lds16(ca) | (lds16(ca + 8) << 16)) & ((t >> 1) == (g >> 2) ? ~0u : 0u);
            }
        }
        const uint32_t d = sb + (warp == 7 ? 2 * ROWP : ((warp - 8) >> 2) * ROWP + (warp & 3) * 512) + lane * 16;
#pragma unroll
        for (int k = 0; k < 4; k++) sts128(d + k * NG * STAGE, f[0], f[1], f[2], f[3]);
    }
    asm volatile("cp.async.wait_all;" ::: "memory");
    __syncwarp();
#pragma unroll
    for (int k = 0; k < 2; k++) {
        const int i = (tid & ~1) + ((tid & 1) * 2 + k) * NTHR, c = i >> 4;
        const uint32_t a0 = sb + SM_W + c * 256 + (((i & 15) ^ ((c & 3) | (((c >> 4) & 1) << 2))) << 4);
        const uint32_t o = (tid & 1) << 4;
        uint4 u = lds128((a0 & ~16u) ^ o), v = lds128((a0 | 16u) ^ o);
        if (tid & 1) { const uint4 w = u; u = v; v = w; }
        const uint32_t s0 = (tid & 1) ? 0x7632 : 0x5410, s1 = s0 ^ 0x2222;
        sts128(a0 ^ o, __byte_perm(u.x, u.y, s0), __byte_perm(u.z, u.w, s0), __byte_perm(v.x, v.y, s0), __byte_perm(v.z, v.w, s0));
        sts128(a0 ^ o ^ 16, __byte_perm(u.x, u.y, s1), __byte_perm(u.z, u.w, s1), __byte_perm(v.x, v.y, s1), __byte_perm(v.z, v.w, s1));
    }

    uint32_t en[8], hr[8], rk[8], em[8];
    int xc[2];
    const uint32_t tref = __shfl_sync(~0u, gtime() >> 5, 0);
    {
        uint4* mp = g_mail + blk * NSRC * 8 + tid;
        int it = 0;
        bool ok;
        while ((int)((uint32_t)clock() - tpub) < POLL_DELAY) {}
        do {
#pragma unroll
            for (int k = 0; k < 2; k++)
                    asm volatile("ld.relaxed.gpu.global.v4.u32 {%0,%1,%2,%3}, [%4];"
                                 : "=r"(en[4 * k]), "=r"(en[4 * k + 1]), "=r"(en[4 * k + 2]), "=r"(en[4 * k + 3])
                                 : "l"(mp + k * NTHR) : "memory");
            uint32_t m = ~0u;
#pragma unroll
            for (int i = 0; i < 8; i++) m = min(m, en[i]);
            ok = __all_sync(~0u, m != 0);
            if (++it > (1 << 20)) __trap();
        } while (!ok);
        STAMP(3);
        const bool hd = (lane & 7) == 7;
        const uint32_t h0 = en[3], h1 = en[7];
        if (hd) en[3] = en[7] = ((64 + (tid >> 5)) << 25) | (80 * 2560 + 1);
        const uint32_t e0 = (tid >> 3) * EPC * 8 - 8;
#pragma unroll
        for (int i = 0; i < 8; i++) {
            const uint32_t w = en[i] & 0x3ffff, code = ((w >> 9) * 13108) >> 16;
            hr[i] = sb + SC_HIST + ((code >> 2) * HS + (en[i] >> 25)) * 4;
            rk[i] = atoms_inc(hr[i]);
            em[i] = (e0 + (i >> 2) * (NTHR / 8 * EPC * 8) + (w - code * 2560) * 8) | (code & 3);
        }
        int dt = hd ? max((int)(((h0 >> 12) - tref) << 14), (int)(((h1 >> 12) - tref) << 14)) >> 14 : -(1 << 20);
        xc[0] = hd ? max((int)(h0 & 0xfff) - 31, 0) : 0;
        xc[1] = hd ? max((int)(h1 & 0xfff) - 31, 0) : 0;
        dt = __reduce_max_sync(~0u, dt);
        asm volatile("red.shared.max.u32 [%0], %1;" ::"r"(lane == 0 ? sb + SM_MISC + MI_TMAX * 4 : dump + 128), "r"(tref + dt + (1u << 27)) : "memory");
        if (xc[0] | xc[1]) {
#pragma unroll
            for (int k = 0; k < 2; k++) {
                const int slot = atomicAdd(&mi[MI_XN], xc[k]);
                for (int r = 0; r < xc[k] && slot + r < 32; r++)
                    reinterpret_cast<uint32_t*>(smem + SC_XTRA)[slot + r] = ((tid + k * NTHR) >> 3) * 32 + r;
            }
        }
#pragma unroll
        for (int k = 0; k < 2; k++)
            mp[k * NTHR] = make_uint4(0, 0, 0, 0);
    }
    __syncthreads();
    STAMP(4);
    uint32_t* hist = reinterpret_cast<uint32_t*>(smem + SC_HIST);
    const int xn = mi[MI_XN];
    uint32_t xi = 0, xv = 1;
    if (warp < 10) {
        uint32_t* hp = hist + (warp * 2 + (lane >> 4)) * HS + (lane & 15) * 5;
        int c[5], s = 0;
#pragma unroll
        for (int j = 0; j < 5; j++) { c[j] = hp[j]; s += c[j]; }
        int inc = s;
#pragma unroll
        for (int o = 1; o < 16; o <<= 1) { int v = __shfl_up_sync(~0u, inc, o, 16); if ((lane & 15) >= o) inc += v; }
        int base = 0;
        if ((lane & 15) == 15) {
            const int tm = (warp * 2 + (lane >> 4)) / 5;
            base = tm * 256 + atomicAdd(&mi[MI_NU + tm], (inc + 3) >> 2);
            hp[5] = (base + ((inc + 3) >> 2)) << 16;
        }
        const int tot = __shfl_sync(~0u, inc, 15, 16);
        base = __shfl_sync(~0u, base, 15, 16);
        int ex = inc - s;
#pragma unroll
        for (int j = 0; j < 5; j++) {
            hp[j] = (base * 4 + ex) | ((base + ((ex == tot ? ex + 3 : ex + 1) >> 2)) << 16);
            ex += c[j];
        }
    } else if (warp == 10) {
        if (lane < xn) {
            xi = reinterpret_cast<const uint32_t*>(smem + SC_XTRA)[lane];
            asm volatile("ld.relaxed.gpu.global.u32 %0, [%1];" : "=r"(xv) : "l"(g_mail2 + blk * NSRC * 32 + xi) : "memory");
        }
    } else if (warp == 12) {
        if (lane == 0) init_barriers();
    } else if (warp == 11) {
        sts32(sb + SC_GPOS + (GDUMMY + lane) * 4, (uint32_t)(4 * UCAP * REC + 128) * 0x10001u);
#pragma unroll
        for (int k = 0; k < 3; k++) hist[20 * HS + min(lane + 32 * k, NBK)] = GDUMMY * 4;
        constexpr int start_ns = START_NS;
        if (lane == 0) mi[MI_T0] = (uint32_t)clock() + (((int)(((uint32_t)mi[MI_TMAX] << 5) + start_ns - gtime()) * 31) >> 4);
    }
    constexpr int pace = PACE_Q8, p1 = PACE_HEAD, b1 = HEAD_BK, p2 = PACE_TAIL, b2 = TAIL_BK, lead = PACE_LEAD;
    auto sched = [&](int b) { return b * pace - min(b, b1) * (pace - p1) - max(b - b2, 0) * (pace - p2) - lead; };
    const int mteam = tid / NBK, mb = tid - mteam * NBK;
    int tb0 = sched(mb);
    float tbw = (float)(sched(mb + 1) - tb0);
    uint32_t mh = sb + SC_HIST + (mteam * 5 * HS + mb) * 4 + 2, mh0 = sb + SC_HIST + mteam * 5 * HS * 4 + 2;
    asm volatile("" : "+r"(tb0), "+f"(tbw), "+r"(mh), "+r"(mh0));
    __syncthreads();
    STAMP(10);
    int myng = mi[MI_NU + (lane & 3)];
    const bool ovf = __any_sync(~0u, myng + xn > 2 * (UCAP - 4) || xn > 32);
    if (!ovf) {
        if (warp < 10) {
            int lo[5], n[5], pos = mteam * UCAP * 2, nsum = 0;
#pragma unroll
            for (int q = 0; q < 5; q++) {
                lo[q] = lds16(mh + q * HS * 4);
                n[q] = lds16(mh + q * HS * 4 + 4) - lo[q];
                pos += lo[q] - lds16(mh0 + q * HS * 4);
                nsum += n[q];
            }
            const int step = __float2int_rz(__fdividef(tbw, (float)max(nsum, 1)));
            const int tb = tb0 + (step >> 1) - pos * step;
            const uint32_t t0 = mi[MI_T0];
            auto emit = [&](int q, int r, int pq) {
                const uint32_t ro = (pq >> 1) * REC, par = pq & 1;
                asm volatile("{\n.reg .pred p, e;\nsetp.lt.s32 p, %0, %1;\nsetp.eq.and.u32 e, %2, 0, p;\n"
                             "@p st.shared.u32 [%3], %4;\n@p st.shared.u8 [%5+48], %6;\n@e st.shared.u16 [%5+102], %7;\n}"
                             ::"r"(r), "r"(n[q]), "r"(par), "r"(sb + SC_GPOS + (lo[q] + r) * 4),
                               "r"(ro * 0x10001u + par * 0x40002u + (REC | (16 << 16))), "r"(sb + SM_REC + ro + par), "r"(q),
                               "h"((uint16_t)((t0 + max(tb + pq * step, 0)) >> 2)) : "memory");
            };
#pragma unroll
            for (int q = 0, pq = pos; q < 5; pq += n[q], q++) emit(q, 0, pq);
#pragma unroll
            for (int q = 0; q < 5; pos += n[q], q++)
#pragma unroll 1
                for (int r = 1; __any_sync(~0u, r < n[q]); r++) emit(q, r, pos + r);
        } else if (warp == 10) {
            for (int n = 0; __any_sync(~0u, xv == 0); n++) {
                if (xv == 0) asm volatile("ld.relaxed.gpu.global.u32 %0, [%1];" : "=r"(xv) : "l"(g_mail2 + blk * NSRC * 32 + xi) : "memory");
                if (n > (1 << 20)) __trap();
            }
            const uint32_t w = xv & 0x3ffff, code = ((w >> 9) * 13108) >> 16, xt = lane < xn ? code / 20 : 4;
            const uint32_t same = __match_any_sync(~0u, xt);
            const int pq = __shfl_sync(~0u, myng, xt & 3) + __popc(same & ((1u << lane) - 1));
#pragma unroll
            for (int q = 0; q < 4; q++) {
                const int c = __popc(__ballot_sync(~0u, xt == q));
                if (lane == q) myng += c;
            }
            if (lane < xn) {
                g_mail2[blk * NSRC * 32 + xi] = 0;
                const uint32_t a = sb + SM_REC + (xt * UCAP + (pq >> 1)) * REC;
                sts16(a + REC + (pq & 1) * 2, xv >> 18);
                sts32(a + 16 + (pq & 1) * 4, (((xi >> 5) * EPC + w - code * 2560 - 1) * 8) | (code & 3));
                sts8(a + 48 + (pq & 1), (code >> 2) - xt * 5);
                if (!(pq & 1)) sts16(a + REC + 50, ((uint32_t)mi[MI_T0] + sched(NBK - 2)) >> 2);
            }
            if (lane < 4) {
                const uint32_t a = sb + SM_REC + (lane * UCAP + (myng >> 1)) * REC + 48;
                if (myng & 1) sts8(a + 1, 0);
                sts16(a + (myng & 1) * REC, 5);
                mi[MI_END + lane] = (myng + 1) >> 1;
            }
        }
#pragma unroll
        for (int i = 0; i < 8; i++) {
            const uint32_t p = rk[i] + lds16(hr[i]);
            hr[i] = sb + SC_GPOS + (p & ~3u);
            rk[i] = (p & 3) * 0x80004u;
        }
        __syncthreads();
        STAMP(11);
#pragma unroll
        for (int i = 0; i < 8; i++) rk[i] += lds32(hr[i]);
#pragma unroll
        for (int i = 0; i < 8; i++) {
            sts16(sb + SM_REC + (rk[i] & 0xffff), en[i] >> 18);
            sts32(sb + SM_REC + (rk[i] >> 16), em[i]);
        }
    } else {
        if (tid < 4) {
            sts16(sb + SM_REC + tid * UCAP * REC + 48, 5);
            mi[MI_END + tid] = 0;
        }
        generic_path(reinterpret_cast<float*>(smem), x, src, dst, Y, ef, w_rad, cg, xc[0], xc[1]);
    }

    __syncwarp();
    if (warp >= 8) {
        asm volatile("bar.sync 3, 512;" ::: "memory");
        asm volatile("setmaxnreg.dec.sync.aligned.u32 24;");
        const int team = warp & 3;
        if (ovf) {
            asm volatile("bar.sync 2;" ::: "memory");
            if (tid == 256) init_barriers();
            asm volatile("bar.sync 2;" ::: "memory");
        }
        STAMP(5);
        const uint32_t ring = sb + SM_RING + team * NG * STAGE;
        const uint32_t q = lane >> 3, c = lane & 7, rec = sb + SM_REC + team * UCAP * REC;
        __syncwarp();
        producer_loop(reinterpret_cast<const char*>(x) + (lane & 15) * 16, reinterpret_cast<const char*>(ef) + (c & 1) * 16, Y,
                      q * ROWP + ((c ^ (q << 1)) << 4), q * 4 + (c & 2) * 8, (c & 1) * 2 + (c >> 2), ring, rec,
                      rec + (mi[MI_END + team] + 1) * REC, warp - 8, sb + SM_MISC + MI_SHIFT * 4,
                      (lane >> 4) * ROWP + (((lane & 15) ^ ((lane >> 4) << 1)) << 4));
        uint32_t ln, sb2, cta;
        asm volatile("mov.u32 %0, %%tid.x;\nmov.u32 %1, %%ctaid.x;\nmov.u32 %2, %%dynamic_smem_size;" : "=r"(ln), "=r"(cta), "=r"(sb2));
        asm volatile("bar.arrive %0, 128;" ::"r"(4 + ((ln >> 5) & 3)) : "memory");
        if (cta == NB - 1 && ln >= NTHR - 32) {
            ln &= 31;
            sb2 += smem_u32(smem) - SM_TOTAL + SM_MISC;
            constexpr int lead = LEAD_CLK >> 2;
            const uint32_t tend = lds32(sb2 + MI_T0 * 4) + 70 * PACE_Q8;
            int sh = 0;
            for (int n = 0; n < 199 && (int)((uint32_t)clock() - tend - (sh >> 14)) < 0; n++) {
                int v;
                asm volatile("ld.relaxed.gpu.global.s32 %0, [%1];" : "=r"(v) : "l"(g_lag[ln * 4]) : "memory");
                const int err = (__reduce_add_sync(~0u, max(v, 0)) >> 5) - lead;
                const int old = sh;
                sh = min(max((sh >> 16) + (err * (err > 0 ? FB_GAIN : FB_DOWN) >> 3), FB_MIN), 2500) << 16;
                if (sh == old) continue;
#pragma unroll
                for (int k = 0; k < 5; k++)
                    asm volatile("st.relaxed.gpu.global.s32 [%0], %1;" ::"l"(g_lag[NB + min(ln + 32 * k, NB - 1u)]), "r"(sh) : "memory");
            }
        }
    } else {
        asm volatile("bar.arrive 3, 512;" ::: "memory");
        int team;
        {
            const int n0 = mi[MI_END], n1 = mi[MI_END + 1], n2 = mi[MI_END + 2], n3 = mi[MI_END + 3];
            const int d1 = abs(n0 + n1 - n2 - n3), d2 = abs(n0 + n2 - n1 - n3), d3 = abs(n0 + n3 - n1 - n2);
            const uint32_t perm = d1 < min(d2, d3) ? 0x3120 : d3 < d2 ? 0x2310 : 0x3210;
            team = __shfl_sync(~0u, (perm >> ((warp >> 1) * 4)) & 3, 0);
        }
        const int h = warp & 1;
        asm volatile("setmaxnreg.inc.sync.aligned.u32 232;");
        uint32_t ring = sb + SM_RING + team * NG * STAGE;
        uint32_t wf[4][4], cgf[4];
#pragma unroll
        for (int m = 0; m < 5; m++) {
            const uint4 v = lds128(ring + (m < 4 ? h * ROWP + m * 512 : 2 * ROWP) + lane * 16);
            uint32_t* f = m < 4 ? wf[m] : cgf;
            f[0] = v.x; f[1] = v.y; f[2] = v.z; f[3] = v.w;
        }
        float acc[5][4][2][4];
        if (!ovf) {
#pragma unroll
            for (int l = 0; l < 5; l++)
#pragma unroll
                for (int m = 0; m < 4; m++)
#pragma unroll
                    for (int p = 0; p < 2; p++)
#pragma unroll
                        for (int r = 0; r < 4; r++) acc[l][m][p][r] = 0.f;
        } else {
            const float* sagg = reinterpret_cast<const float*>(smem);
#pragma unroll
            for (int l = 0; l < 5; l++)
#pragma unroll
                for (int m = 0; m < 4; m++)
#pragma unroll
                    for (int p = 0; p < 2; p++)
#pragma unroll
                        for (int r = 0; r < 4; r++) {
                            int nd = l * 4 + (g >> 2) + (r >> 1) * 2;
                            int ch = h * 64 + m * 16 + 4 * t + (r & 1) * 2 + p;
                            acc[l][m][p][r] = nd < 19 ? sagg[(team * 19 + nd) * 512 + ch * 4 + (g & 3)] : 0.f;
                        }
            asm volatile("bar.sync 2;" ::: "memory");
            asm volatile("bar.sync 2;" ::: "memory");
        }
        const uint32_t xoff = t * ROWP + h * 512 + ((g ^ (t << 1)) << 4);
        const uint32_t mat = lane >> 3, mhi = (lane >> 2) & 1;
        const bool isy = mat < 2;
        const uint32_t ml = isy ? (t & 2) + (mat & 1) : t;
        const uint32_t moff = ml * ROWP + 2048 + (((isy ? 4 + 2 * mhi + (t & 1) : 2 * mhi + mat - 2) ^ (ml << 1)) << 4);
        __syncwarp();
        consumer_loop(acc, wf, cgf, xoff, ring, moff, sb + SM_REC + team * UCAP * REC);
        {
        int lane_;
        asm volatile("mov.u32 %0, %%laneid;" : "=r"(lane_));
        const int lane = lane_, g = lane >> 2, t = lane & 3;
        const uint32_t sb = ring - team * NG * STAGE;
        STAMP(7);
        asm volatile("bar.sync %0, 128;" ::"r"(4 + team) : "memory");
        if (lane == 0) {
            mbar_inval(ring + h * STAGE + 4 * ROWP);
            mbar_inval(ring + h * STAGE + 4 * ROWP + 8);
        }
        __syncwarp();
        {
            const int rr = ((g & 3) >> 1) * 8 + (g >> 2) * 2 + (g & 1);
#pragma unroll
            for (int l = 0; l < 5; l++)
#pragma unroll
                for (int hi = 0; hi < 2; hi++) {
                    const int R = l * 16 + rr + hi * 4;
                    const uint32_t a = sb + team * AGGT + h * 10240 + R * 128;
#pragma unroll
                    for (int c = 0; c < 2; c++) {
                        const int m = 2 * c;
                        sts128(a + (((2 * t + c) ^ (R & 7)) << 4),
                               pack_bf16(acc[l][m][0][2 * hi], acc[l][m][1][2 * hi]),
                               pack_bf16(acc[l][m][0][2 * hi + 1], acc[l][m][1][2 * hi + 1]),
                               pack_bf16(acc[l][m + 1][0][2 * hi], acc[l][m + 1][1][2 * hi]),
                               pack_bf16(acc[l][m + 1][0][2 * hi + 1], acc[l][m + 1][1][2 * hi + 1]));
                    }
                }
        }
        asm volatile("fence.proxy.async.shared::cta;" ::: "memory");
        uint32_t wa[8][4];
        {
            const int r = lane & 7, k = (lane >> 4) * 8 + r;
            const int chunk = (2 * warp + ((lane >> 3) & 1)) ^ r;
#pragma unroll
            for (int ks = 0; ks < 8; ks++) {
                const int c = (ks >> 2) * 64 + 16 * (k >> 2) + 4 * (ks & 3) + (k & 3);
                asm volatile("ldmatrix.sync.aligned.m8n8.x4.trans.shared.b16 {%0,%1,%2,%3}, [%4];"
                             : "=r"(wa[ks][0]), "=r"(wa[ks][1]), "=r"(wa[ks][2]), "=r"(wa[ks][3])
                             : "r"(sb + SM_W + c * 256 + (chunk << 4)));
            }
        }
        asm volatile("bar.sync 1, 256;" ::: "memory");
        STAMP(8);
        const int sl = (lane & 7) * 4 + (lane >> 3);
        __nv_bfloat16* op = out + (size_t)(blk * NPB + (lane >> 3)) * 512 + warp * 64 + (lane & 7) * 8;
        const int nleft = N_NODES - blk * NPB - (lane >> 3);
        uint32_t pk[20];
        auto store = [&](int tm) {
#pragma unroll
            for (int l = 0; l < 5; l++) {
                uint4 v;
                v.x = __shfl_sync(~0u, pk[4 * l + 0], sl);
                v.y = __shfl_sync(~0u, pk[4 * l + 1], sl);
                v.z = __shfl_sync(~0u, pk[4 * l + 2], sl);
                v.w = __shfl_sync(~0u, pk[4 * l + 3], sl);
                asm volatile("{\n.reg .pred p;\nsetp.lt.u32 p, %5, %6;\n@p st.global.v4.u32 [%0], {%1,%2,%3,%4};\n}"
                             ::"l"(op + (tm * 19 + l * 4) * 512), "r"(v.x), "r"(v.y), "r"(v.z), "r"(v.w), "r"(tm * 19 + l * 4),
                               "r"(l < 4 || lane < 24 ? nleft : 0) : "memory");
            }
        };
        if (warp >= 4) asm volatile("bar.sync 10, 256;" ::: "memory");
#pragma unroll 1
        for (int tm = 0; tm < 4; tm++) {
            float o[40];
            asm volatile("wgmma.fence.sync.aligned;" ::: "memory");
#pragma unroll
            for (int ks = 0; ks < 8; ks++) {
                const uint32_t a = sb + tm * AGGT + (ks >> 2) * 10240 + (ks & 3) * 32;
                const uint64_t desc = (uint64_t)((a & 0x3ffff) >> 4) | (1ull << 16) | (64ull << 32) | (1ull << 62);
                wgmma_n80(o, wa[ks], desc, ks);
            }
            asm volatile("wgmma.commit_group.sync.aligned;" ::: "memory");
            if (tm == 0 && warp < 4) asm volatile("bar.arrive 10, 256;" ::: "memory");
            asm volatile("wgmma.wait_group.sync.aligned 0;" ::: "memory");
#pragma unroll
            for (int i = 0; i < 40; i++) asm volatile("" : "+f"(o[i])::"memory");
#pragma unroll
            for (int l = 0; l < 5; l++) {
                pk[4 * l + 0] = pack_bf16(o[8 * l + 0], o[8 * l + 1]);
                pk[4 * l + 1] = pack_bf16(o[8 * l + 4], o[8 * l + 5]);
                pk[4 * l + 2] = pack_bf16(o[8 * l + 2], o[8 * l + 3]);
                pk[4 * l + 3] = pack_bf16(o[8 * l + 6], o[8 * l + 7]);
            }
            store(tm);
        }
        STAMP(9);
        }
    }
}

}

extern "C" void kernel_launch(void* const* d_in, const int* in_sizes, int n_in, void* d_out, int out_size) {
    (void)in_sizes; (void)n_in; (void)out_size;
    const __nv_bfloat16* x = (const __nv_bfloat16*)d_in[0];
    const int* src = (const int*)d_in[1];
    const int* dst = (const int*)d_in[2];
    const __nv_bfloat16* Y = (const __nv_bfloat16*)d_in[3];
    const __nv_bfloat16* ef = (const __nv_bfloat16*)d_in[4];
    const __nv_bfloat16* w_rad = (const __nv_bfloat16*)d_in[5];
    const __nv_bfloat16* cg = (const __nv_bfloat16*)d_in[6];
    const __nv_bfloat16* w_mix = (const __nv_bfloat16*)d_in[7];
    __nv_bfloat16* out = (__nv_bfloat16*)d_out;

    static int sms = 0;
    if (sms == 0) {
        int dev = 0;
        cudaGetDevice(&dev);
        cudaDeviceGetAttribute(&sms, cudaDevAttrMultiProcessorCount, dev);
        cudaFuncSetAttribute(tfn_kernel<3>, cudaFuncAttributeMaxDynamicSharedMemorySize, SM_TOTAL);
        cudaFuncSetAttribute(tfn_kernel<1>, cudaFuncAttributeMaxDynamicSharedMemorySize, SM_TOTAL);
        cudaFuncSetAttribute(tfn_kernel<2>, cudaFuncAttributeMaxDynamicSharedMemorySize, SM_TOTAL);
    }
    if (sms >= NB) {
        tfn_kernel<3><<<NB, NTHR, SM_TOTAL>>>(x, src, dst, Y, ef, w_rad, cg, w_mix, out);
    } else {
        tfn_kernel<1><<<NB, NTHR, SM_TOTAL>>>(x, src, dst, Y, ef, w_rad, cg, w_mix, out);
        tfn_kernel<2><<<NB, NTHR, SM_TOTAL>>>(x, src, dst, Y, ef, w_rad, cg, w_mix, out);
    }
}
```

```cpp
#include <cuda_runtime.h>
#include <cuda_bf16.h>
#include <stdint.h>

namespace {

constexpr int N_NODES = 10000;
constexpr int N_EDGES = 320000;
constexpr int NB      = 132;
constexpr int NPB     = 76;
constexpr int NSRC    = 128;
constexpr int EPC     = N_EDGES / NSRC;
constexpr int NTHR    = 512;
constexpr int NG      = 5;
constexpr int ROWP    = 2176;
constexpr int STAGE   = 4 * ROWP + 128;
constexpr int UCAP    = 104;
constexpr int REC     = 52;
constexpr int NBK     = 80;
constexpr int HS      = 81;

#define PACE_Q8 630
#define PACE_LEAD 300
#define PACE_HEAD 705
#define HEAD_BK 10
#define PACE_TAIL 610
#define TAIL_BK 66
#define IDLE_EST 900
#define POLL_DELAY 1280
#define LEAD_CLK 110
#define FB_GAIN 24
#define FB_DOWN 4
#define FB_MIN 0
#define START_NS 3150

constexpr int SM_RING  = 0;
constexpr int SM_W     = 4 * NG * STAGE;
constexpr int SM_REC   = SM_W + 32768;
constexpr int SM_MISC  = SM_REC + 4 * UCAP * REC;
constexpr int SM_TOTAL = SM_MISC + 224;
constexpr int SC_MAIL  = 1 * STAGE;
constexpr int SC_CNT   = 3 * STAGE;
constexpr int SC_DUMP  = 3 * STAGE + 1024;
constexpr int SC_XTRA  = 3 * STAGE + 2048;
constexpr int SC_HIST  = 4 * STAGE;
constexpr int SC_GPOS  = 6 * STAGE;
constexpr int SC_WR    = 7 * STAGE;
constexpr int GDUMMY   = 1024;
constexpr int AGGT     = (NG * STAGE + 1023) / 1024 * 1024;
static_assert(3 * AGGT + 20480 <= 4 * NG * STAGE, "agg tile inside the team's ring");
static_assert(4 * ROWP + 16 <= 10240 && STAGE + 4 * ROWP >= 3 * (AGGT - NG * STAGE) + 10240 && STAGE + 4 * ROWP + 16 <= 20480 &&
              2 * STAGE + 4 * ROWP >= 3 * (AGGT - NG * STAGE) + 20480, "half h of the tile covers the barriers of stage h only");
static_assert(NPB * 512 * 4 <= 4 * NG * STAGE, "slow tile");
static_assert(SM_TOTAL <= 232448, "smem");
static_assert(SM_REC % 16 == 0 && (4 * UCAP * REC) % 16 == 0 && SM_MISC % 16 == 0, "align");
constexpr int MI_XN = 0;
constexpr int MI_TMAX = 2;
constexpr int MI_SHIFT = 48;
constexpr int MI_NU = 8;
constexpr int MI_END = 28;
constexpr int MI_T0 = 3;

__device__ __align__(128) uint4 g_mail[NB * NSRC * 8];
__device__ __align__(128) uint32_t g_mail2[NB * NSRC * 32];
__device__ __align__(128) int g_lag[2 * NB][32];
#define STAMP(k)

__device__ __forceinline__ uint32_t smem_u32(const void* p) { return (uint32_t)__cvta_generic_to_shared(p); }
__device__ __forceinline__ uint32_t atoms_inc(uint32_t a) {
    uint32_t r;
    asm volatile("atom.shared.add.u32 %0, [%1], 1;" : "=r"(r) : "r"(a) : "memory");
    return r;
}
__device__ __forceinline__ void sts32(uint32_t a, uint32_t v) { asm volatile("st.shared.u32 [%0], %1;" ::"r"(a), "r"(v) : "memory"); }
__device__ __forceinline__ void sts16(uint32_t a, uint32_t v) { asm volatile("st.shared.u16 [%0], %1;" ::"r"(a), "h"((uint16_t)v) : "memory"); }
__device__ __forceinline__ void sts8(uint32_t a, uint32_t v) { asm volatile("st.shared.u8 [%0], %1;" ::"r"(a), "r"(v) : "memory"); }
__device__ __forceinline__ uint32_t lds32(uint32_t a) { uint32_t v; asm volatile("ld.shared.u32 %0, [%1];" : "=r"(v) : "r"(a)); return v; }
__device__ __forceinline__ uint32_t lds16(uint32_t a) { uint32_t v; asm volatile("ld.shared.u16 %0, [%1];" : "=r"(v) : "r"(a)); return v; }
__device__ __forceinline__ void cp16(uint32_t d, const void* p) {
    asm volatile("cp.async.cg.shared.global [%0], [%1], 16;" ::"r"(d), "l"(p) : "memory");
}
__device__ __forceinline__ uint32_t gtime() {
    uint32_t t;
    asm volatile("mov.u32 %0, %%globaltimer_lo;" : "=r"(t));
    return t;
}
__device__ __forceinline__ void mbar_init(uint32_t bar, int cnt) {
    asm volatile("mbarrier.init.shared.b64 [%0], %1;" ::"r"(bar), "r"(cnt) : "memory");
}
__device__ __forceinline__ void mbar_inval(uint32_t bar) {
    asm volatile("mbarrier.inval.shared.b64 [%0];" ::"r"(bar) : "memory");
}
__device__ __forceinline__ uint4 lds128(uint32_t a) {
    uint4 v;
    asm volatile("ld.shared.v4.u32 {%0,%1,%2,%3}, [%4];" : "=r"(v.x), "=r"(v.y), "=r"(v.z), "=r"(v.w) : "r"(a));
    return v;
}
__device__ __forceinline__ void sts128(uint32_t a, uint32_t x, uint32_t y, uint32_t z, uint32_t w) {
    asm volatile("st.shared.v4.u32 [%0], {%1,%2,%3,%4};" ::"r"(a), "r"(x), "r"(y), "r"(z), "r"(w) : "memory");
}
__device__ __forceinline__ uint32_t pack_bf16(float lo, float hi) {
    uint32_t r;
    asm("cvt.rn.bf16x2.f32 %0, %1, %2;" : "=r"(r) : "f"(hi), "f"(lo));
    return r;
}
__device__ __forceinline__ uint32_t mul_lo(uint32_t v, uint32_t r) {
    __nv_bfloat162 a = *reinterpret_cast<__nv_bfloat162*>(&v), b = *reinterpret_cast<__nv_bfloat162*>(&r);
    __nv_bfloat162 c = __hmul2(a, __low2bfloat162(b));
    return *reinterpret_cast<uint32_t*>(&c);
}
__device__ __forceinline__ void wgmma_n80(float (&d)[40], const uint32_t (&a)[4], uint64_t desc, int scale_d) {
    asm volatile("{\n.reg .pred p;\nsetp.ne.b32 p, %45, 0;\n"
        "wgmma.mma_async.sync.aligned.m64n80k16.f32.bf16.bf16 "
        "{%0,%1,%2,%3,%4,%5,%6,%7,%8,%9,%10,%11,%12,%13,%14,%15,%16,%17,%18,%19,"
        "%20,%21,%22,%23,%24,%25,%26,%27,%28,%29,%30,%31,%32,%33,%34,%35,%36,%37,%38,%39}, "
        "{%40,%41,%42,%43}, %44, p, 1, 1, 0;\n}"
        : "+f"(d[0]), "+f"(d[1]), "+f"(d[2]), "+f"(d[3]), "+f"(d[4]), "+f"(d[5]), "+f"(d[6]), "+f"(d[7]),
          "+f"(d[8]), "+f"(d[9]), "+f"(d[10]), "+f"(d[11]), "+f"(d[12]), "+f"(d[13]), "+f"(d[14]), "+f"(d[15]),
          "+f"(d[16]), "+f"(d[17]), "+f"(d[18]), "+f"(d[19]), "+f"(d[20]), "+f"(d[21]), "+f"(d[22]), "+f"(d[23]),
          "+f"(d[24]), "+f"(d[25]), "+f"(d[26]), "+f"(d[27]), "+f"(d[28]), "+f"(d[29]), "+f"(d[30]), "+f"(d[31]),
          "+f"(d[32]), "+f"(d[33]), "+f"(d[34]), "+f"(d[35]), "+f"(d[36]), "+f"(d[37]), "+f"(d[38]), "+f"(d[39])
        : "r"(a[0]), "r"(a[1]), "r"(a[2]), "r"(a[3]), "l"(desc), "r"(scale_d));
}

__device__ __forceinline__ void producer_loop(const void* xl, const void* efl, const void* Y, uint32_t xd, uint32_t oef,
                                              uint32_t ysel, uint32_t ring, uint32_t rec, uint32_t rlast, uint32_t odd,
                                              uint32_t lag, uint32_t xh) {
    asm volatile(
        "{\n"
        ".reg .b32 w, em, ey, cu, d, t, u, n, sa, ph, rp, rend, rlast, dy, sv, lag, lv, w2, w3, w4;\n"
        ".reg .b16 tg;\n"
        ".reg .b64 pa, pb, pc, pd;\n"
        ".reg .pred lo, z, q, e, zb, fbk;\n"
        "redux.sync.or.b32 sa, %6, 0xffffffff;\n"
        "redux.sync.or.b32 rp, %7, 0xffffffff;\n"
        "redux.sync.or.b32 rlast, %8, 0xffffffff;\n"
        "redux.sync.or.b32 lag, %11, 0xffffffff;\n"
        "setp.eq.u32 fbk, %9, 0;\n"
        "add.u32 rend, sa, 44160;\n"
        "and.b32 t, %5, 1;\n"
        "setp.eq.u32 lo, t, 0;\n"
        "mov.u32 ph, 1;\n"
        "setp.ge.u32 q, %9, 4;\n"
        "@q bra.uni PODD_%=;\n"
        "add.u32 t, rp, %4;\n"
        "ld.shared.u32 em, [t+16];\n"
        "and.b32 t, em, 0xfffffff8;\n"
        "mad.wide.u32 pa, t, 4, %1;\n"
        "add.u32 d, sa, %3;\n"
        "@lo cp.async.cg.shared.global.L2::128B [d+2048], [pa], 16;\n"
        "cp.async.mbarrier.arrive.noinc.shared.b64 [sa+8704];\n"
        "add.u32 rp, rp, 52;\n"
        "add.u32 sa, sa, 8832;\n"
        "PODD_%=:\n"
        "add.u32 rp, rp, 52;\n"
        "add.u32 sa, sa, 8832;\n"
        "shr.u32 t, %4, 1;\n"
        "and.b32 t, t, 4;\n"
        "add.u32 t, t, rp;\n"
        "ld.shared.u32 w, [t];\n"
        "ld.shared.u32 w2, [t+8];\n"
        "add.u32 t, rp, %4;\n"
        "ld.shared.u32 em, [t+16];\n"
        "ld.shared.u32 ey, [t+-36];\n"
        "ld.shared.u32 cu, [rp+48];\n"
        "ld.volatile.shared.u32 sv, [lag];\n"
        "setp.eq.u32 e, sa, sa;\n"
        "setp.lt.u32 q, rp, rlast;\n"
        "@!q bra.uni PF_%=;\n"
        "PL_%=:\n"
        "add.u32 cu, cu, sv;\n"
        "mov.u32 u, %%clock;\n"
        "shl.b32 u, u, 14;\n"
        "sub.u32 u, u, cu;\n"
        "setp.ge.and.s32 q, u, 0, e;\n"
        "@q bra.uni PGO_%=;\n"
        "mov.u32 n, 0;\n"
        "PW1_%=:\n"
        "@e bra.uni PW2_%=;\n"
        "mbarrier.try_wait.parity.shared.b64 e, [sa+8712], ph;\n"
        "add.u32 n, n, 1;\n"
        "setp.lt.u32 q, n, 4194304;\n"
        "@q bra.uni PW1_%=;\n"
        "trap;\n"
        "PW2_%=:\n"
        "mov.u32 u, %%clock;\n"
        "shl.b32 u, u, 14;\n"
        "sub.u32 u, u, cu;\n"
        "setp.lt.s32 q, u, 0;\n"
        "@q bra.uni PW2_%=;\n"
        "PGO_%=:\n"
        "st.volatile.shared.u32 [lag+24], u;\n"
        "and.b32 t, em, 0xfffffff8;\n"
        "mad.wide.u32 pa, t, 4, %1;\n"
        "and.b32 t, w, 0xffff;\n"
        "mad.wide.u32 pc, t, 1024, %0;\n"
        "shr.u32 t, w, 16;\n"
        "mad.wide.u32 pd, t, 1024, %0;\n"
        "add.u32 d, sa, %3;\n"
        "@lo cp.async.cg.shared.global.L2::128B [d+2048], [pa], 16;\n"
        "xor.b32 t, ey, %5;\n"
        "and.b32 t, t, 7;\n"
        "setp.ne.u32 zb, t, 0;\n"
        "and.b32 t, ey, 0xfffffff8;\n"
        "cvt.u64.u32 pb, t;\n"
        "add.u64 pb, pb, %2;\n"
        "selp.u32 dy, 64, 8, lo;\n"
        "xor.b32 dy, dy, d;\n"
        "cp.async.ca.shared.global.L2::128B [dy+2048], [pb], 8, zb;\n"
        "add.u32 d, sa, %12;\n"
        "and.b32 t, w, 0xffff;\n"
        "setp.eq.u32 zb, t, 0xffff;\n"
        "cp.async.cg.shared.global [d+0], [pc+0], 16, zb;\n"
        "cp.async.cg.shared.global [d+256], [pc+256], 16, zb;\n"
        "cp.async.cg.shared.global [d+512], [pc+512], 16, zb;\n"
        "cp.async.cg.shared.global [d+768], [pc+768], 16, zb;\n"
        "setp.lt.s32 zb, w, 0;\n"
        "cp.async.cg.shared.global [d+1024], [pd+0], 16, zb;\n"
        "cp.async.cg.shared.global [d+1280], [pd+256], 16, zb;\n"
        "cp.async.cg.shared.global [d+1536], [pd+512], 16, zb;\n"
        "cp.async.cg.shared.global [d+1792], [pd+768], 16, zb;\n"
        "xor.b32 dy, d, 64;\n"
        "and.b32 t, w2, 0xffff;\n"
        "mad.wide.u32 pa, t, 1024, %0;\n"
        "and.b32 t, w2, 0xffff;\n"
        "setp.eq.u32 zb, t, 0xffff;\n"
        "cp.async.cg.shared.global [dy+4352], [pa+0], 16, zb;\n"
        "cp.async.cg.shared.global [dy+4608], [pa+256], 16, zb;\n"
        "cp.async.cg.shared.global [dy+4864], [pa+512], 16, zb;\n"
        "cp.async.cg.shared.global [dy+5120], [pa+768], 16, zb;\n"
        "shr.u32 t, w2, 16;\n"
        "mad.wide.u32 pb, t, 1024, %0;\n"
        "setp.lt.s32 zb, w2, 0;\n"
        "cp.async.cg.shared.global [dy+5376], [pb+0], 16, zb;\n"
        "cp.async.cg.shared.global [dy+5632], [pb+256], 16, zb;\n"
        "cp.async.cg.shared.global [dy+5888], [pb+512], 16, zb;\n"
        "cp.async.cg.shared.global [dy+6144], [pb+768], 16, zb;\n"
        "add.u32 rp, rp, 104;\n"
        "shr.u32 t, %4, 1;\n"
        "and.b32 t, t, 4;\n"
        "add.u32 t, t, rp;\n"
        "ld.shared.u32 w, [t];\n"
        "ld.shared.u32 w2, [t+8];\n"
        "add.u32 t, rp, %4;\n"
        "ld.shared.u32 em, [t+16];\n"
        "ld.shared.u32 ey, [t+-36];\n"
        "ld.shared.u32 cu, [rp+48];\n"
        "ld.volatile.shared.u32 sv, [lag];\n"
        "cp.async.mbarrier.arrive.noinc.shared.b64 [sa+8704];\n"
        "add.u32 sa, sa, 17664;\n"
        "sub.u32 t, sa, 44160;\n"
        "setp.ge.u32 q, sa, rend;\n"
        "selp.u32 sa, t, sa, q;\n"
        "selp.u32 t, 1, 0, q;\n"
        "xor.b32 ph, ph, t;\n"
        "mbarrier.test_wait.parity.shared.b64 e, [sa+8712], ph;\n"
        "@!fbk bra.uni PC_%=;\n"
        "ld.volatile.shared.u32 u, [lag+24];\n"
        "shr.s32 u, u, 16;\n"
        "ld.volatile.shared.u64 pa, [lag+16];\n"
        "elect.sync _|z, 0xffffffff;\n"
        "@z st.relaxed.gpu.global.u32 [pa], u;\n"
        "@z cp.async.cg.shared.global [lag], [pa+16896], 16;\n"
        "PC_%=:\n"
        "setp.lt.u32 q, rp, rlast;\n"
        "@q bra.uni PL_%=;\n"
        "PF_%=:\n"
        "setp.ne.u32 q, rp, rlast;\n"
        "@q bra.uni PX_%=;\n"
        "mov.u32 n, 0;\n"
        "PE1_%=:\n"
        "@e bra.uni PE2_%=;\n"
        "mbarrier.try_wait.parity.shared.b64 e, [sa+8712], ph;\n"
        "add.u32 n, n, 1;\n"
        "setp.lt.u32 q, n, 4194304;\n"
        "@q bra.uni PE1_%=;\n"
        "trap;\n"
        "PE2_%=:\n"
        "cp.async.mbarrier.arrive.noinc.shared.b64 [sa+8704];\n"
        "PX_%=:\n"
        "}\n"
        ::"l"(xl), "l"(efl), "l"(Y), "r"(xd), "r"(oef), "r"(ysel), "r"(ring), "r"(rec), "r"(rlast), "r"(odd),
          "n"(0), "r"(lag), "r"(xh) : "memory");
}

__device__ __forceinline__ void consumer_loop(float (&acc)[5][4][2][4], const uint32_t (&wf)[4][4], const uint32_t (&cgf)[4],
                                              uint32_t xoff, uint32_t& ring, uint32_t moff, uint32_t rec) {
    asm volatile(
        "{\n"
        ".reg .b32 x<16>, a<4>, b<4>, r<4>, m<4>, rl, rh, tag, la, lb, sa, last, ph, tq, xa, ma, n, ring, sn, ln, yb, zz, k<4>, tp, s<4>;\n"
        ".reg .b16 lo, hi;\n"
        ".reg .f32 p<16>, d<4>, t0, t1, fz;\n"
        ".reg .pred q, w, el, c<5>;\n"
        "TA_%=: .branchtargets A0_%=, A1_%=, A2_%=, A3_%=, A4_%=, EXIT_%=;\n"
        "TB_%=: .branchtargets B0_%=, B1_%=, B2_%=, B3_%=, B4_%=, SPIN_%=;\n"
        "mov.f32 fz, 0f00000000;\n"
        "redux.sync.or.b32 ring, %160, 0xffffffff;\n"
        "mov.u32 sa, ring;\n"
        "add.u32 last, ring, 35328;\n"
        "mov.u32 ph, 0;\n"
        "redux.sync.xor.b32 zz, %160, 0xffffffff;\n"
        "redux.sync.or.b32 tp, %183, 0xffffffff;\n"
        "elect.sync _|el, 0xffffffff;\n"
        "mov.u32 k0, sa;\n"
        "mov.u32 k1, sa;\n"
        "mov.u32 k2, sa;\n"
        "mov.u32 k3, sa;\n"
        "mov.b32 x0, 0;\n"
        "mov.b32 x1, 0;\n"
        "mov.b32 x2, 0;\n"
        "mov.b32 x3, 0;\n"
        "mov.b32 x4, 0;\n"
        "mov.b32 x5, 0;\n"
        "mov.b32 x6, 0;\n"
        "mov.b32 x7, 0;\n"
        "mov.b32 x8, 0;\n"
        "mov.b32 x9, 0;\n"
        "mov.b32 x10, 0;\n"
        "mov.b32 x11, 0;\n"
        "mov.b32 x12, 0;\n"
        "mov.b32 x13, 0;\n"
        "mov.b32 x14, 0;\n"
        "mov.b32 x15, 0;\n"
        "mov.b32 b0, 0;\n"
        "mov.b32 r0, 0;\n"
        "mov.b32 b1, 0;\n"
        "mov.b32 r1, 0;\n"
        "mov.b32 b2, 0;\n"
        "mov.b32 r2, 0;\n"
        "mov.b32 b3, 0;\n"
        "mov.b32 r3, 0;\n"
        "mov.u32 lb, 0;\n"
        "mov.u32 n, 0;\n"
        "W0_%=:\n"
        "mbarrier.try_wait.parity.shared.b64 w, [sa+8704], 0;\n"
        "@w bra.uni W0D_%=;\n"
        "add.u32 n, n, 1;\n"
        "setp.lt.u32 q, n, 4194304;\n"
        "@q bra.uni W0_%=;\n"
        "trap;\n"
        "W0D_%=:\n"
        "add.u32 ma, sa, %182;\n"
        "ldmatrix.sync.aligned.m8n8.x4.shared.b16 {m0,m1,m2,m3}, [ma];\n"
        "ld.shared.u16 tag, [tp+48];\n"
        "add.u32 tp, tp, 52;\n"
        "add.u32 sn, sa, 8832;\n"
        "setp.eq.u32 q, sa, last;\n"
        "selp.u32 sn, ring, sn, q;\n"
        "selp.u32 tq, 1, 0, q;\n"
        "xor.b32 ph, ph, tq;\n"
        "mbarrier.test_wait.parity.shared.b64 w, [sn+8704], ph;\n"
        "mma.sync.aligned.m16n8k16.row.col.f32.bf16.bf16.f32 {p0,p1,p2,p3}, {%161,%162,%163,%164}, {m2,m3}, {fz,fz,fz,fz};\n"
        "mma.sync.aligned.m16n8k16.row.col.f32.bf16.bf16.f32 {p4,p5,p6,p7}, {%165,%166,%167,%168}, {m2,m3}, {fz,fz,fz,fz};\n"
        "mma.sync.aligned.m16n8k16.row.col.f32.bf16.bf16.f32 {p8,p9,p10,p11}, {%169,%170,%171,%172}, {m2,m3}, {fz,fz,fz,fz};\n"
        "mma.sync.aligned.m16n8k16.row.col.f32.bf16.bf16.f32 {p12,p13,p14,p15}, {%173,%174,%175,%176}, {m2,m3}, {fz,fz,fz,fz};\n"
        "@el mbarrier.arrive.shared.b64 _, [k0+8712];\n"
        "redux.sync.or.b32 ln, tag, 0xffffffff;\n"
        "mov.u32 sa, sn;\n"
        "add.u32 k0, sn, zz;\n"
        "SPIN_%=:\n"
        "mov.u32 n, 0;\n"
        "SP1_%=:\n"
        "mbarrier.try_wait.parity.shared.b64 w, [sa+8704], ph;\n"
        "@w bra.uni SP2_%=;\n"
        "add.u32 n, n, 1;\n"
        "setp.lt.u32 q, n, 4194304;\n"
        "@q bra.uni SP1_%=;\n"
        "trap;\n"
        "SP2_%=:\n"
        "brx.idx.uni lb, TB_%=;\n"
        "A0_%=:\n"
        "add.u32 xa, sa, %181;\n"
        "add.u32 ma, sa, %182;\n"
        "ldmatrix.sync.aligned.m8n8.x4.shared.b16 {m0,m1,m2,m3}, [ma];\n"
        "ld.shared.u16 tag, [tp+48];\n"
        "add.u32 tp, tp, 52;\n"
        "add.u32 sn, sa, 8832;\n"
        "setp.eq.u32 q, sa, last;\n"
        "selp.u32 sn, ring, sn, q;\n"
        "selp.u32 tq, 1, 0, q;\n"
        "xor.b32 ph, ph, tq;\n"
        "mbarrier.test_wait.parity.shared.b64 w, [sn+8704], ph;\n"
        "mma.sync.aligned.m16n8k16.row.col.f32.bf16.bf16.f32 {%0,%1,%2,%3}, {a0,a1,a2,a3}, {x0,x1}, {%0,%1,%2,%3};\n"
        "mma.sync.aligned.m16n8k16.row.col.f32.bf16.bf16.f32 {%4,%5,%6,%7}, {a0,a1,a2,a3}, {x2,x3}, {%4,%5,%6,%7};\n"
        "ld.shared.v4.u32 {x0,x1,x2,x3}, [xa+1024];\n"
        "tanh.approx.f32 t0, p1;\n"
        "tanh.approx.f32 t1, p3;\n"
        "fma.rn.f32 t0, p1, t0, p1;\n"
        "fma.rn.f32 t1, p3, t1, p3;\n"
        "cvt.rn.bf16x2.f32 r0, t1, t0;\n"
        "mma.sync.aligned.m16n8k16.row.col.f32.bf16.bf16.f32 {p0,p1,p2,p3}, {%161,%162,%163,%164}, {m2,m3}, {fz,fz,fz,fz};\n"
        "mma.sync.aligned.m16n8k16.row.col.f32.bf16.bf16.f32 {%8,%9,%10,%11}, {a0,a1,a2,a3}, {x4,x5}, {%8,%9,%10,%11};\n"
        "mma.sync.aligned.m16n8k16.row.col.f32.bf16.bf16.f32 {%12,%13,%14,%15}, {a0,a1,a2,a3}, {x6,x7}, {%12,%13,%14,%15};\n"
        "ld.shared.v4.u32 {x4,x5,x6,x7}, [xa+1152];\n"
        "mma.sync.aligned.m16n8k8.row.col.f32.bf16.bf16.f32 {d0,d1,d2,d3}, {%177,%178}, {m1}, {fz,fz,fz,fz};\n"
        "cvt.rn.bf16x2.f32 b0, d2, d0;\n"
        "cvt.rn.bf16x2.f32 b1, d3, d1;\n"
        "tanh.approx.f32 t0, p5;\n"
        "tanh.approx.f32 t1, p7;\n"
        "fma.rn.f32 t0, p5, t0, p5;\n"
        "fma.rn.f32 t1, p7, t1, p7;\n"
        "cvt.rn.bf16x2.f32 r1, t1, t0;\n"
        "mma.sync.aligned.m16n8k16.row.col.f32.bf16.bf16.f32 {p4,p5,p6,p7}, {%165,%166,%167,%168}, {m2,m3}, {fz,fz,fz,fz};\n"
        "mov.b32 {lo,hi}, r2;\n"
        "mov.b32 rl, {lo,lo};\n"
        "mov.b32 rh, {hi,hi};\n"
        "mul.bf16x2 x8, x8, rl;\n"
        "mul.bf16x2 x9, x9, rl;\n"
        "mul.bf16x2 x10, x10, rh;\n"
        "mul.bf16x2 x11, x11, rh;\n"
        "mma.sync.aligned.m16n8k16.row.col.f32.bf16.bf16.f32 {%16,%17,%18,%19}, {a0,a1,a2,a3}, {x8,x9}, {%16,%17,%18,%19};\n"
        "mma.sync.aligned.m16n8k16.row.col.f32.bf16.bf16.f32 {%20,%21,%22,%23}, {a0,a1,a2,a3}, {x10,x11}, {%20,%21,%22,%23};\n"
        "ld.shared.v4.u32 {x8,x9,x10,x11}, [xa+1280];\n"
        "mma.sync.aligned.m16n8k8.row.col.f32.bf16.bf16.f32 {d0,d1,d2,d3}, {%179,%180}, {m1}, {fz,fz,fz,fz};\n"
        "cvt.rn.bf16x2.f32 b2, d2, d0;\n"
        "cvt.rn.bf16x2.f32 b3, d3, d1;\n"
        "tanh.approx.f32 t0, p9;\n"
        "tanh.approx.f32 t1, p11;\n"
        "fma.rn.f32 t0, p9, t0, p9;\n"
        "fma.rn.f32 t1, p11, t1, p11;\n"
        "cvt.rn.bf16x2.f32 r2, t1, t0;\n"
        "mma.sync.aligned.m16n8k16.row.col.f32.bf16.bf16.f32 {p8,p9,p10,p11}, {%169,%170,%171,%172}, {m2,m3}, {fz,fz,fz,fz};\n"
        "mov.b32 {lo,hi}, r3;\n"
        "mov.b32 rl, {lo,lo};\n"
        "mov.b32 rh, {hi,hi};\n"
        "mul.bf16x2 x12, x12, rl;\n"
        "mul.bf16x2 x13, x13, rl;\n"
        "mul.bf16x2 x14, x14, rh;\n"
        "mul.bf16x2 x15, x15, rh;\n"
        "mma.sync.aligned.m16n8k16.row.col.f32.bf16.bf16.f32 {%24,%25,%26,%27}, {a0,a1,a2,a3}, {x12,x13}, {%24,%25,%26,%27};\n"
        "mma.sync.aligned.m16n8k16.row.col.f32.bf16.bf16.f32 {%28,%29,%30,%31}, {a0,a1,a2,a3}, {x14,x15}, {%28,%29,%30,%31};\n"
        "ld.shared.v4.u32 {x12,x13,x14,x15}, [xa+1408];\n"
        "@el mbarrier.arrive.shared.b64 _, [k0+8712];\n"
        "redux.sync.or.b32 ln, tag, 0xffffffff;\n"
        "mov.u32 sa, sn;\n"
        "add.u32 k0, sn, zz;\n"
        "tanh.approx.f32 t0, p13;\n"
        "tanh.approx.f32 t1, p15;\n"
        "fma.rn.f32 t0, p13, t0, p13;\n"
        "fma.rn.f32 t1, p15, t1, p15;\n"
        "cvt.rn.bf16x2.f32 r3, t1, t0;\n"
        "mma.sync.aligned.m16n8k16.row.col.f32.bf16.bf16.f32 {p12,p13,p14,p15}, {%173,%174,%175,%176}, {m2,m3}, {fz,fz,fz,fz};\n"
        "selp.u32 tq, lb, 5, w;\n"
        "brx.idx.uni tq, TB_%=;\n"
        "A1_%=:\n"
        "add.u32 xa, sa, %181;\n"
        "add.u32 ma, sa, %182;\n"
        "ldmatrix.sync.aligned.m8n8.x4.shared.b16 {m0,m1,m2,m3}, [ma];\n"
        "ld.shared.u16 tag, [tp+48];\n"
        "add.u32 tp, tp, 52;\n"
        "add.u32 sn, sa, 8832;\n"
        "setp.eq.u32 q, sa, last;\n"
        "selp.u32 sn, ring, sn, q;\n"
        "selp.u32 tq, 1, 0, q;\n"
        "xor.b32 ph, ph, tq;\n"
        "mbarrier.test_wait.parity.shared.b64 w, [sn+8704], ph;\n"
        "mma.sync.aligned.m16n8k16.row.col.f32.bf16.bf16.f32 {%32,%33,%34,%35}, {a0,a1,a2,a3}, {x0,x1}, {%32,%33,%34,%35};\n"
        "mma.sync.aligned.m16n8k16.row.col.f32.bf16.bf16.f32 {%36,%37,%38,%39}, {a0,a1,a2,a3}, {x2,x3}, {%36,%37,%38,%39};\n"
        "ld.shared.v4.u32 {x0,x1,x2,x3}, [xa+1024];\n"
        "tanh.approx.f32 t0, p1;\n"
        "tanh.approx.f32 t1, p3;\n"
        "fma.rn.f32 t0, p1, t0, p1;\n"
        "fma.rn.f32 t1, p3, t1, p3;\n"
        "cvt.rn.bf16x2.f32 r0, t1, t0;\n"
        "mma.sync.aligned.m16n8k16.row.col.f32.bf16.bf16.f32 {p0,p1,p2,p3}, {%161,%162,%163,%164}, {m2,m3}, {fz,fz,fz,fz};\n"
        "mma.sync.aligned.m16n8k16.row.col.f32.bf16.bf16.f32 {%40,%41,%42,%43}, {a0,a1,a2,a3}, {x4,x5}, {%40,%41,%42,%43};\n"
        "mma.sync.aligned.m16n8k16.row.col.f32.bf16.bf16.f32 {%44,%45,%46,%47}, {a0,a1,a2,a3}, {x6,x7}, {%44,%45,%46,%47};\n"
        "ld.shared.v4.u32 {x4,x5,x6,x7}, [xa+1152];\n"
        "mma.sync.aligned.m16n8k8.row.col.f32.bf16.bf16.f32 {d0,d1,d2,d3}, {%177,%178}, {m1}, {fz,fz,fz,fz};\n"
        "cvt.rn.bf16x2.f32 b0, d2, d0;\n"
        "cvt.rn.bf16x2.f32 b1, d3, d1;\n"
        "tanh.approx.f32 t0, p5;\n"
        "tanh.approx.f32 t1, p7;\n"
        "fma.rn.f32 t0, p5, t0, p5;\n"
        "fma.rn.f32 t1, p7, t1, p7;\n"
        "cvt.rn.bf16x2.f32 r1, t1, t0;\n"
        "mma.sync.aligned.m16n8k16.row.col.f32.bf16.bf16.f32 {p4,p5,p6,p7}, {%165,%166,%167,%168}, {m2,m3}, {fz,fz,fz,fz};\n"
        "mov.b32 {lo,hi}, r2;\n"
        "mov.b32 rl, {lo,lo};\n"
        "mov.b32 rh, {hi,hi};\n"
        "mul.bf16x2 x8, x8, rl;\n"
        "mul.bf16x2 x9, x9, rl;\n"
        "mul.bf16x2 x10, x10, rh;\n"
        "mul.bf16x2 x11, x11, rh;\n"
        "mma.sync.aligned.m16n8k16.row.col.f32.bf16.bf16.f32 {%48,%49,%50,%51}, {a0,a1,a2,a3}, {x8,x9}, {%48,%49,%50,%51};\n"
        "mma.sync.aligned.m16n8k16.row.col.f32.bf16.bf16.f32 {%52,%53,%54,%55}, {a0,a1,a2,a3}, {x10,x11}, {%52,%53,%54,%55};\n"
        "ld.shared.v4.u32 {x8,x9,x10,x11}, [xa+1280];\n"
        "mma.sync.aligned.m16n8k8.row.col.f32.bf16.bf16.f32 {d0,d1,d2,d3}, {%179,%180}, {m1}, {fz,fz,fz,fz};\n"
        "cvt.rn.bf16x2.f32 b2, d2, d0;\n"
        "cvt.rn.bf16x2.f32 b3, d3, d1;\n"
        "tanh.approx.f32 t0, p9;\n"
        "tanh.approx.f32 t1, p11;\n"
        "fma.rn.f32 t0, p9, t0, p9;\n"
        "fma.rn.f32 t1, p11, t1, p11;\n"
        "cvt.rn.bf16x2.f32 r2, t1, t0;\n"
        "mma.sync.aligned.m16n8k16.row.col.f32.bf16.bf16.f32 {p8,p9,p10,p11}, {%169,%170,%171,%172}, {m2,m3}, {fz,fz,fz,fz};\n"
        "mov.b32 {lo,hi}, r3;\n"
        "mov.b32 rl, {lo,lo};\n"
        "mov.b32 rh, {hi,hi};\n"
        "mul.bf16x2 x12, x12, rl;\n"
        "mul.bf16x2 x13, x13, rl;\n"
        "mul.bf16x2 x14, x14, rh;\n"
        "mul.bf16x2 x15, x15, rh;\n"
        "mma.sync.aligned.m16n8k16.row.col.f32.bf16.bf16.f32 {%56,%57,%58,%59}, {a0,a1,a2,a3}, {x12,x13}, {%56,%57,%58,%59};\n"
        "mma.sync.aligned.m16n8k16.row.col.f32.bf16.bf16.f32 {%60,%61,%62,%63}, {a0,a1,a2,a3}, {x14,x15}, {%60,%61,%62,%63};\n"
        "ld.shared.v4.u32 {x12,x13,x14,x15}, [xa+1408];\n"
        "@el mbarrier.arrive.shared.b64 _, [k0+8712];\n"
        "redux.sync.or.b32 ln, tag, 0xffffffff;\n"
        "mov.u32 sa, sn;\n"
        "add.u32 k0, sn, zz;\n"
        "tanh.approx.f32 t0, p13;\n"
        "tanh.approx.f32 t1, p15;\n"
        "fma.rn.f32 t0, p13, t0, p13;\n"
        "fma.rn.f32 t1, p15, t1, p15;\n"
        "cvt.rn.bf16x2.f32 r3, t1, t0;\n"
        "mma.sync.aligned.m16n8k16.row.col.f32.bf16.bf16.f32 {p12,p13,p14,p15}, {%173,%174,%175,%176}, {m2,m3}, {fz,fz,fz,fz};\n"
        "selp.u32 tq, lb, 5, w;\n"
        "brx.idx.uni tq, TB_%=;\n"
        "A2_%=:\n"
        "add.u32 xa, sa, %181;\n"
        "add.u32 ma, sa, %182;\n"
        "ldmatrix.sync.aligned.m8n8.x4.shared.b16 {m0,m1,m2,m3}, [ma];\n"
        "ld.shared.u16 tag, [tp+48];\n"
        "add.u32 tp, tp, 52;\n"
        "add.u32 sn, sa, 8832;\n"
        "setp.eq.u32 q, sa, last;\n"
        "selp.u32 sn, ring, sn, q;\n"
        "selp.u32 tq, 1, 0, q;\n"
        "xor.b32 ph, ph, tq;\n"
        "mbarrier.test_wait.parity.shared.b64 w, [sn+8704], ph;\n"
        "mma.sync.aligned.m16n8k16.row.col.f32.bf16.bf16.f32 {%64,%65,%66,%67}, {a0,a1,a2,a3}, {x0,x1}, {%64,%65,%66,%67};\n"
        "mma.sync.aligned.m16n8k16.row.col.f32.bf16.bf16.f32 {%68,%69,%70,%71}, {a0,a1,a2,a3}, {x2,x3}, {%68,%69,%70,%71};\n"
        "ld.shared.v4.u32 {x0,x1,x2,x3}, [xa+1024];\n"
        "tanh.approx.f32 t0, p1;\n"
        "tanh.approx.f32 t1, p3;\n"
        "fma.rn.f32 t0, p1, t0, p1;\n"
        "fma.rn.f32 t1, p3, t1, p3;\n"
        "cvt.rn.bf16x2.f32 r0, t1, t0;\n"
        "mma.sync.aligned.m16n8k16.row.col.f32.bf16.bf16.f32 {p0,p1,p2,p3}, {%161,%162,%163,%164}, {m2,m3}, {fz,fz,fz,fz};\n"
        "mma.sync.aligned.m16n8k16.row.col.f32.bf16.bf16.f32 {%72,%73,%74,%75}, {a0,a1,a2,a3}, {x4,x5}, {%72,%73,%74,%75};\n"
        "mma.sync.aligned.m16n8k16.row.col.f32.bf16.bf16.f32 {%76,%77,%78,%79}, {a0,a1,a2,a3}, {x6,x7}, {%76,%77,%78,%79};\n"
        "ld.shared.v4.u32 {x4,x5,x6,x7}, [xa+1152];\n"
        "mma.sync.aligned.m16n8k8.row.col.f32.bf16.bf16.f32 {d0,d1,d2,d3}, {%177,%178}, {m1}, {fz,fz,fz,fz};\n"
        "cvt.rn.bf16x2.f32 b0, d2, d0;\n"
        "cvt.rn.bf16x2.f32 b1, d3, d1;\n"
        "tanh.approx.f32 t0, p5;\n"
        "tanh.approx.f32 t1, p7;\n"
        "fma.rn.f32 t0, p5, t0, p5;\n"
        "fma.rn.f32 t1, p7, t1, p7;\n"
        "cvt.rn.bf16x2.f32 r1, t1, t0;\n"
        "mma.sync.aligned.m16n8k16.row.col.f32.bf16.bf16.f32 {p4,p5,p6,p7}, {%165,%166,%167,%168}, {m2,m3}, {fz,fz,fz,fz};\n"
        "mov.b32 {lo,hi}, r2;\n"
        "mov.b32 rl, {lo,lo};\n"
        "mov.b32 rh, {hi,hi};\n"
        "mul.bf16x2 x8, x8, rl;\n"
        "mul.bf16x2 x9, x9, rl;\n"
        "mul.bf16x2 x10, x10, rh;\n"
        "mul.bf16x2 x11, x11, rh;\n"
        "mma.sync.aligned.m16n8k16.row.col.f32.bf16.bf16.f32 {%80,%81,%82,%83}, {a0,a1,a2,a3}, {x8,x9}, {%80,%81,%82,%83};\n"
        "mma.sync.aligned.m16n8k16.row.col.f32.bf16.bf16.f32 {%84,%85,%86,%87}, {a0,a1,a2,a3}, {x10,x11}, {%84,%85,%86,%87};\n"
        "ld.shared.v4.u32 {x8,x9,x10,x11}, [xa+1280];\n"
        "mma.sync.aligned.m16n8k8.row.col.f32.bf16.bf16.f32 {d0,d1,d2,d3}, {%179,%180}, {m1}, {fz,fz,fz,fz};\n"
        "cvt.rn.bf16x2.f32 b2, d2, d0;\n"
        "cvt.rn.bf16x2.f32 b3, d3, d1;\n"
        "tanh.approx.f32 t0, p9;\n"
        "tanh.approx.f32 t1, p11;\n"
        "fma.rn.f32 t0, p9, t0, p9;\n"
        "fma.rn.f32 t1, p11, t1, p11;\n"
        "cvt.rn.bf16x2.f32 r2, t1, t0;\n"
        "mma.sync.aligned.m16n8k16.row.col.f32.bf16.bf16.f32 {p8,p9,p10,p11}, {%169,%170,%171,%172}, {m2,m3}, {fz,fz,fz,fz};\n"
        "mov.b32 {lo,hi}, r3;\n"
        "mov.b32 rl, {lo,lo};\n"
        "mov.b32 rh, {hi,hi};\n"
        "mul.bf16x2 x12, x12, rl;\n"
        "mul.bf16x2 x13, x13, rl;\n"
        "mul.bf16x2 x14, x14, rh;\n"
        "mul.bf16x2 x15, x15, rh;\n"
        "mma.sync.aligned.m16n8k16.row.col.f32.bf16.bf16.f32 {%88,%89,%90,%91}, {a0,a1,a2,a3}, {x12,x13}, {%88,%89,%90,%91};\n"
        "mma.sync.aligned.m16n8k16.row.col.f32.bf16.bf16.f32 {%92,%93,%94,%95}, {a0,a1,a2,a3}, {x14,x15}, {%92,%93,%94,%95};\n"
        "ld.shared.v4.u32 {x12,x13,x14,x15}, [xa+1408];\n"
        "@el mbarrier.arrive.shared.b64 _, [k0+8712];\n"
        "redux.sync.or.b32 ln, tag, 0xffffffff;\n"
        "mov.u32 sa, sn;\n"
        "add.u32 k0, sn, zz;\n"
        "tanh.approx.f32 t0, p13;\n"
        "tanh.approx.f32 t1, p15;\n"
        "fma.rn.f32 t0, p13, t0, p13;\n"
        "fma.rn.f32 t1, p15, t1, p15;\n"
        "cvt.rn.bf16x2.f32 r3, t1, t0;\n"
        "mma.sync.aligned.m16n8k16.row.col.f32.bf16.bf16.f32 {p12,p13,p14,p15}, {%173,%174,%175,%176}, {m2,m3}, {fz,fz,fz,fz};\n"
        "selp.u32 tq, lb, 5, w;\n"
        "brx.idx.uni tq, TB_%=;\n"
        "A3_%=:\n"
        "add.u32 xa, sa, %181;\n"
        "add.u32 ma, sa, %182;\n"
        "ldmatrix.sync.aligned.m8n8.x4.shared.b16 {m0,m1,m2,m3}, [ma];\n"
        "ld.shared.u16 tag, [tp+48];\n"
        "add.u32 tp, tp, 52;\n"
        "add.u32 sn, sa, 8832;\n"
        "setp.eq.u32 q, sa, last;\n"
        "selp.u32 sn, ring, sn, q;\n"
        "selp.u32 tq, 1, 0, q;\n"
        "xor.b32 ph, ph, tq;\n"
        "mbarrier.test_wait.parity.shared.b64 w, [sn+8704], ph;\n"
        "mma.sync.aligned.m16n8k16.row.col.f32.bf16.bf16.f32 {%96,%97,%98,%99}, {a0,a1,a2,a3}, {x0,x1}, {%96,%97,%98,%99};\n"
        "mma.sync.aligned.m16n8k16.row.col.f32.bf16.bf16.f32 {%100,%101,%102,%103}, {a0,a1,a2,a3}, {x2,x3}, {%100,%101,%102,%103};\n"
        "ld.shared.v4.u32 {x0,x1,x2,x3}, [xa+1024];\n"
        "tanh.approx.f32 t0, p1;\n"
        "tanh.approx.f32 t1, p3;\n"
        "fma.rn.f32 t0, p1, t0, p1;\n"
        "fma.rn.f32 t1, p3, t1, p3;\n"
        "cvt.rn.bf16x2.f32 r0, t1, t0;\n"
        "mma.sync.aligned.m16n8k16.row.col.f32.bf16.bf16.f32 {p0,p1,p2,p3}, {%161,%162,%163,%164}, {m2,m3}, {fz,fz,fz,fz};\n"
        "mma.sync.aligned.m16n8k16.row.col.f32.bf16.bf16.f32 {%104,%105,%106,%107}, {a0,a1,a2,a3}, {x4,x5}, {%104,%105,%106,%107};\n"
        "mma.sync.aligned.m16n8k16.row.col.f32.bf16.bf16.f32 {%108,%109,%110,%111}, {a0,a1,a2,a3}, {x6,x7}, {%108,%109,%110,%111};\n"
        "ld.shared.v4.u32 {x4,x5,x6,x7}, [xa+1152];\n"
        "mma.sync.aligned.m16n8k8.row.col.f32.bf16.bf16.f32 {d0,d1,d2,d3}, {%177,%178}, {m1}, {fz,fz,fz,fz};\n"
        "cvt.rn.bf16x2.f32 b0, d2, d0;\n"
        "cvt.rn.bf16x2.f32 b1, d3, d1;\n"
        "tanh.approx.f32 t0, p5;\n"
        "tanh.approx.f32 t1, p7;\n"
        "fma.rn.f32 t0, p5, t0, p5;\n"
        "fma.rn.f32 t1, p7, t1, p7;\n"
        "cvt.rn.bf16x2.f32 r1, t1, t0;\n"
        "mma.sync.aligned.m16n8k16.row.col.f32.bf16.bf16.f32 {p4,p5,p6,p7}, {%165,%166,%167,%168}, {m2,m3}, {fz,fz,fz,fz};\n"
        "mov.b32 {lo,hi}, r2;\n"
        "mov.b32 rl, {lo,lo};\n"
        "mov.b32 rh, {hi,hi};\n"
        "mul.bf16x2 x8, x8, rl;\n"
        "mul.bf16x2 x9, x9, rl;\n"
        "mul.bf16x2 x10, x10, rh;\n"
        "mul.bf16x2 x11, x11, rh;\n"
        "mma.sync.aligned.m16n8k16.row.col.f32.bf16.bf16.f32 {%112,%113,%114,%115}, {a0,a1,a2,a3}, {x8,x9}, {%112,%113,%114,%115};\n"
        "mma.sync.aligned.m16n8k16.row.col.f32.bf16.bf16.f32 {%116,%117,%118,%119}, {a0,a1,a2,a3}, {x10,x11}, {%116,%117,%118,%119};\n"
        "ld.shared.v4.u32 {x8,x9,x10,x11}, [xa+1280];\n"
        "mma.sync.aligned.m16n8k8.row.col.f32.bf16.bf16.f32 {d0,d1,d2,d3}, {%179,%180}, {m1}, {fz,fz,fz,fz};\n"
        "cvt.rn.bf16x2.f32 b2, d2, d0;\n"
        "cvt.rn.bf16x2.f32 b3, d3, d1;\n"
        "tanh.approx.f32 t0, p9;\n"
        "tanh.approx.f32 t1, p11;\n"
        "fma.rn.f32 t0, p9, t0, p9;\n"
        "fma.rn.f32 t1, p11, t1, p11;\n"
        "cvt.rn.bf16x2.f32 r2, t1, t0;\n"
        "mma.sync.aligned.m16n8k16.row.col.f32.bf16.bf16.f32 {p8,p9,p10,p11}, {%169,%170,%171,%172}, {m2,m3}, {fz,fz,fz,fz};\n"
        "mov.b32 {lo,hi}, r3;\n"
        "mov.b32 rl, {lo,lo};\n"
        "mov.b32 rh, {hi,hi};\n"
        "mul.bf16x2 x12, x12, rl;\n"
        "mul.bf16x2 x13, x13, rl;\n"
        "mul.bf16x2 x14, x14, rh;\n"
        "mul.bf16x2 x15, x15, rh;\n"
        "mma.sync.aligned.m16n8k16.row.col.f32.bf16.bf16.f32 {%120,%121,%122,%123}, {a0,a1,a2,a3}, {x12,x13}, {%120,%121,%122,%123};\n"
        "mma.sync.aligned.m16n8k16.row.col.f32.bf16.bf16.f32 {%124,%125,%126,%127}, {a0,a1,a2,a3}, {x14,x15}, {%124,%125,%126,%127};\n"
        "ld.shared.v4.u32 {x12,x13,x14,x15}, [xa+1408];\n"
        "@el mbarrier.arrive.shared.b64 _, [k0+8712];\n"
        "redux.sync.or.b32 ln, tag, 0xffffffff;\n"
        "mov.u32 sa, sn;\n"
        "add.u32 k0, sn, zz;\n"
        "tanh.approx.f32 t0, p13;\n"
        "tanh.approx.f32 t1, p15;\n"
        "fma.rn.f32 t0, p13, t0, p13;\n"
        "fma.rn.f32 t1, p15, t1, p15;\n"
        "cvt.rn.bf16x2.f32 r3, t1, t0;\n"
        "mma.sync.aligned.m16n8k16.row.col.f32.bf16.bf16.f32 {p12,p13,p14,p15}, {%173,%174,%175,%176}, {m2,m3}, {fz,fz,fz,fz};\n"
        "selp.u32 tq, lb, 5, w;\n"
        "brx.idx.uni tq, TB_%=;\n"
        "A4_%=:\n"
        "add.u32 xa, sa, %181;\n"
        "add.u32 ma, sa, %182;\n"
        "ldmatrix.sync.aligned.m8n8.x4.shared.b16 {m0,m1,m2,m3}, [ma];\n"
        "ld.shared.u16 tag, [tp+48];\n"
        "add.u32 tp, tp, 52;\n"
        "add.u32 sn, sa, 8832;\n"
        "setp.eq.u32 q, sa, last;\n"
        "selp.u32 sn, ring, sn, q;\n"
        "selp.u32 tq, 1, 0, q;\n"
        "xor.b32 ph, ph, tq;\n"
        "mbarrier.test_wait.parity.shared.b64 w, [sn+8704], ph;\n"
        "mma.sync.aligned.m16n8k16.row.col.f32.bf16.bf16.f32 {%128,%129,%130,%131}, {a0,a1,a2,a3}, {x0,x1}, {%128,%129,%130,%131};\n"
        "mma.sync.aligned.m16n8k16.row.col.f32.bf16.bf16.f32 {%132,%133,%134,%135}, {a0,a1,a2,a3}, {x2,x3}, {%132,%133,%134,%135};\n"
        "ld.shared.v4.u32 {x0,x1,x2,x3}, [xa+1024];\n"
        "tanh.approx.f32 t0, p1;\n"
        "tanh.approx.f32 t1, p3;\n"
        "fma.rn.f32 t0, p1, t0, p1;\n"
        "fma.rn.f32 t1, p3, t1, p3;\n"
        "cvt.rn.bf16x2.f32 r0, t1, t0;\n"
        "mma.sync.aligned.m16n8k16.row.col.f32.bf16.bf16.f32 {p0,p1,p2,p3}, {%161,%162,%163,%164}, {m2,m3}, {fz,fz,fz,fz};\n"
        "mma.sync.aligned.m16n8k16.row.col.f32.bf16.bf16.f32 {%136,%137,%138,%139}, {a0,a1,a2,a3}, {x4,x5}, {%136,%137,%138,%139};\n"
        "mma.sync.aligned.m16n8k16.row.col.f32.bf16.bf16.f32 {%140,%141,%142,%143}, {a0,a1,a2,a3}, {x6,x7}, {%140,%141,%142,%143};\n"
        "ld.shared.v4.u32 {x4,x5,x6,x7}, [xa+1152];\n"
        "mma.sync.aligned.m16n8k8.row.col.f32.bf16.bf16.f32 {d0,d1,d2,d3}, {%177,%178}, {m1}, {fz,fz,fz,fz};\n"
        "cvt.rn.bf16x2.f32 b0, d2, d0;\n"
        "cvt.rn.bf16x2.f32 b1, d3, d1;\n"
        "tanh.approx.f32 t0, p5;\n"
        "tanh.approx.f32 t1, p7;\n"
        "fma.rn.f32 t0, p5, t0, p5;\n"
        "fma.rn.f32 t1, p7, t1, p7;\n"
        "cvt.rn.bf16x2.f32 r1, t1, t0;\n"
        "mma.sync.aligned.m16n8k16.row.col.f32.bf16.bf16.f32 {p4,p5,p6,p7}, {%165,%166,%167,%168}, {m2,m3}, {fz,fz,fz,fz};\n"
        "mov.b32 {lo,hi}, r2;\n"
        "mov.b32 rl, {lo,lo};\n"
        "mov.b32 rh, {hi,hi};\n"
        "mul.bf16x2 x8, x8, rl;\n"
        "mul.bf16x2 x9, x9, rl;\n"
        "mul.bf16x2 x10, x10, rh;\n"
        "mul.bf16x2 x11, x11, rh;\n"
        "mma.sync.aligned.m16n8k16.row.col.f32.bf16.bf16.f32 {%144,%145,%146,%147}, {a0,a1,a2,a3}, {x8,x9}, {%144,%145,%146,%147};\n"
        "mma.sync.aligned.m16n8k16.row.col.f32.bf16.bf16.f32 {%148,%149,%150,%151}, {a0,a1,a2,a3}, {x10,x11}, {%148,%149,%150,%151};\n"
        "ld.shared.v4.u32 {x8,x9,x10,x11}, [xa+1280];\n"
        "mma.sync.aligned.m16n8k8.row.col.f32.bf16.bf16.f32 {d0,d1,d2,d3}, {%179,%180}, {m1}, {fz,fz,fz,fz};\n"
        "cvt.rn.bf16x2.f32 b2, d2, d0;\n"
        "cvt.rn.bf16x2.f32 b3, d3, d1;\n"
        "tanh.approx.f32 t0, p9;\n"
        "tanh.approx.f32 t1, p11;\n"
        "fma.rn.f32 t0, p9, t0, p9;\n"
        "fma.rn.f32 t1, p11, t1, p11;\n"
        "cvt.rn.bf16x2.f32 r2, t1, t0;\n"
        "mma.sync.aligned.m16n8k16.row.col.f32.bf16.bf16.f32 {p8,p9,p10,p11}, {%169,%170,%171,%172}, {m2,m3}, {fz,fz,fz,fz};\n"
        "mov.b32 {lo,hi}, r3;\n"
        "mov.b32 rl, {lo,lo};\n"
        "mov.b32 rh, {hi,hi};\n"
        "mul.bf16x2 x12, x12, rl;\n"
        "mul.bf16x2 x13, x13, rl;\n"
        "mul.bf16x2 x14, x14, rh;\n"
        "mul.bf16x2 x15, x15, rh;\n"
        "mma.sync.aligned.m16n8k16.row.col.f32.bf16.bf16.f32 {%152,%153,%154,%155}, {a0,a1,a2,a3}, {x12,x13}, {%152,%153,%154,%155};\n"
        "mma.sync.aligned.m16n8k16.row.col.f32.bf16.bf16.f32 {%156,%157,%158,%159}, {a0,a1,a2,a3}, {x14,x15}, {%156,%157,%158,%159};\n"
        "ld.shared.v4.u32 {x12,x13,x14,x15}, [xa+1408];\n"
        "@el mbarrier.arrive.shared.b64 _, [k0+8712];\n"
        "redux.sync.or.b32 ln, tag, 0xffffffff;\n"
        "mov.u32 sa, sn;\n"
        "add.u32 k0, sn, zz;\n"
        "tanh.approx.f32 t0, p13;\n"
        "tanh.approx.f32 t1, p15;\n"
        "fma.rn.f32 t0, p13, t0, p13;\n"
        "fma.rn.f32 t1, p15, t1, p15;\n"
        "cvt.rn.bf16x2.f32 r3, t1, t0;\n"
        "mma.sync.aligned.m16n8k16.row.col.f32.bf16.bf16.f32 {p12,p13,p14,p15}, {%173,%174,%175,%176}, {m2,m3}, {fz,fz,fz,fz};\n"
        "selp.u32 tq, lb, 5, w;\n"
        "brx.idx.uni tq, TB_%=;\n"
        "B0_%=:\n"
        "and.b32 la, ln, 255;\n"
        "shr.u32 lb, ln, 8;\n"
        "add.u32 ma, sa, %182;\n"
        "ldmatrix.sync.aligned.m8n8.x1.shared.b16 {yb}, [ma];\n"
        "add.u32 xa, sa, %181;\n"
        "mov.b32 {lo,hi}, r0;\n"
        "mov.b32 rl, {lo,lo};\n"
        "mov.b32 rh, {hi,hi};\n"
        "mul.bf16x2 x0, x0, rl;\n"
        "mul.bf16x2 x1, x1, rl;\n"
        "mul.bf16x2 x2, x2, rh;\n"
        "mul.bf16x2 x3, x3, rh;\n"
        "mma.sync.aligned.m16n8k16.row.col.f32.bf16.bf16.f32 {%0,%1,%2,%3}, {b0,b1,b2,b3}, {x0,x1}, {%0,%1,%2,%3};\n"
        "mma.sync.aligned.m16n8k16.row.col.f32.bf16.bf16.f32 {%4,%5,%6,%7}, {b0,b1,b2,b3}, {x2,x3}, {%4,%5,%6,%7};\n"
        "ld.shared.v4.u32 {x0,x1,x2,x3}, [xa+0];\n"
        "tanh.approx.f32 t0, p0;\n"
        "tanh.approx.f32 t1, p2;\n"
        "fma.rn.f32 t0, p0, t0, p0;\n"
        "fma.rn.f32 t1, p2, t1, p2;\n"
        "cvt.rn.bf16x2.f32 r0, t1, t0;\n"
        "mov.b32 {lo,hi}, r1;\n"
        "mov.b32 rl, {lo,lo};\n"
        "mov.b32 rh, {hi,hi};\n"
        "mul.bf16x2 x4, x4, rl;\n"
        "mul.bf16x2 x5, x5, rl;\n"
        "mul.bf16x2 x6, x6, rh;\n"
        "mul.bf16x2 x7, x7, rh;\n"
        "mma.sync.aligned.m16n8k16.row.col.f32.bf16.bf16.f32 {%8,%9,%10,%11}, {b0,b1,b2,b3}, {x4,x5}, {%8,%9,%10,%11};\n"
        "mma.sync.aligned.m16n8k16.row.col.f32.bf16.bf16.f32 {%12,%13,%14,%15}, {b0,b1,b2,b3}, {x6,x7}, {%12,%13,%14,%15};\n"
        "ld.shared.v4.u32 {x4,x5,x6,x7}, [xa+128];\n"
        "tanh.approx.f32 t0, p4;\n"
        "tanh.approx.f32 t1, p6;\n"
        "fma.rn.f32 t0, p4, t0, p4;\n"
        "fma.rn.f32 t1, p6, t1, p6;\n"
        "cvt.rn.bf16x2.f32 r1, t1, t0;\n"
        "mma.sync.aligned.m16n8k8.row.col.f32.bf16.bf16.f32 {d0,d1,d2,d3}, {%177,%178}, {yb}, {fz,fz,fz,fz};\n"
        "cvt.rn.bf16x2.f32 a0, d2, d0;\n"
        "cvt.rn.bf16x2.f32 a1, d3, d1;\n"
        "mov.b32 {lo,hi}, r2;\n"
        "mov.b32 rl, {lo,lo};\n"
        "mov.b32 rh, {hi,hi};\n"
        "mul.bf16x2 x8, x8, rl;\n"
        "mul.bf16x2 x9, x9, rl;\n"
        "mul.bf16x2 x10, x10, rh;\n"
        "mul.bf16x2 x11, x11, rh;\n"
        "mma.sync.aligned.m16n8k16.row.col.f32.bf16.bf16.f32 {%16,%17,%18,%19}, {b0,b1,b2,b3}, {x8,x9}, {%16,%17,%18,%19};\n"
        "mma.sync.aligned.m16n8k16.row.col.f32.bf16.bf16.f32 {%20,%21,%22,%23}, {b0,b1,b2,b3}, {x10,x11}, {%20,%21,%22,%23};\n"
        "ld.shared.v4.u32 {x8,x9,x10,x11}, [xa+256];\n"
        "tanh.approx.f32 t0, p8;\n"
        "tanh.approx.f32 t1, p10;\n"
        "fma.rn.f32 t0, p8, t0, p8;\n"
        "fma.rn.f32 t1, p10, t1, p10;\n"
        "cvt.rn.bf16x2.f32 r2, t1, t0;\n"
        "mma.sync.aligned.m16n8k8.row.col.f32.bf16.bf16.f32 {d0,d1,d2,d3}, {%179,%180}, {yb}, {fz,fz,fz,fz};\n"
        "cvt.rn.bf16x2.f32 a2, d2, d0;\n"
        "cvt.rn.bf16x2.f32 a3, d3, d1;\n"
        "mov.b32 {lo,hi}, r3;\n"
        "mov.b32 rl, {lo,lo};\n"
        "mov.b32 rh, {hi,hi};\n"
        "mul.bf16x2 x12, x12, rl;\n"
        "mul.bf16x2 x13, x13, rl;\n"
        "mul.bf16x2 x14, x14, rh;\n"
        "mul.bf16x2 x15, x15, rh;\n"
        "mma.sync.aligned.m16n8k16.row.col.f32.bf16.bf16.f32 {%24,%25,%26,%27}, {b0,b1,b2,b3}, {x12,x13}, {%24,%25,%26,%27};\n"
        "mma.sync.aligned.m16n8k16.row.col.f32.bf16.bf16.f32 {%28,%29,%30,%31}, {b0,b1,b2,b3}, {x14,x15}, {%28,%29,%30,%31};\n"
        "ld.shared.v4.u32 {x12,x13,x14,x15}, [xa+384];\n"
        "tanh.approx.f32 t0, p12;\n"
        "tanh.approx.f32 t1, p14;\n"
        "fma.rn.f32 t0, p12, t0, p12;\n"
        "fma.rn.f32 t1, p14, t1, p14;\n"
        "cvt.rn.bf16x2.f32 r3, t1, t0;\n"
        "mov.b32 {lo,hi}, r0;\n"
        "mov.b32 rl, {lo,lo};\n"
        "mov.b32 rh, {hi,hi};\n"
        "mul.bf16x2 x0, x0, rl;\n"
        "mul.bf16x2 x1, x1, rl;\n"
        "mul.bf16x2 x2, x2, rh;\n"
        "mul.bf16x2 x3, x3, rh;\n"
        "mov.b32 {lo,hi}, r1;\n"
        "mov.b32 rl, {lo,lo};\n"
        "mov.b32 rh, {hi,hi};\n"
        "mul.bf16x2 x4, x4, rl;\n"
        "mul.bf16x2 x5, x5, rl;\n"
        "mul.bf16x2 x6, x6, rh;\n"
        "mul.bf16x2 x7, x7, rh;\n"
        "brx.idx.uni la, TA_%=;\n"
        "B1_%=:\n"
        "and.b32 la, ln, 255;\n"
        "shr.u32 lb, ln, 8;\n"
        "add.u32 ma, sa, %182;\n"
        "ldmatrix.sync.aligned.m8n8.x1.shared.b16 {yb}, [ma];\n"
        "add.u32 xa, sa, %181;\n"
        "mov.b32 {lo,hi}, r0;\n"
        "mov.b32 rl, {lo,lo};\n"
        "mov.b32 rh, {hi,hi};\n"
        "mul.bf16x2 x0, x0, rl;\n"
        "mul.bf16x2 x1, x1, rl;\n"
        "mul.bf16x2 x2, x2, rh;\n"
        "mul.bf16x2 x3, x3, rh;\n"
        "mma.sync.aligned.m16n8k16.row.col.f32.bf16.bf16.f32 {%32,%33,%34,%35}, {b0,b1,b2,b3}, {x0,x1}, {%32,%33,%34,%35};\n"
        "mma.sync.aligned.m16n8k16.row.col.f32.bf16.bf16.f32 {%36,%37,%38,%39}, {b0,b1,b2,b3}, {x2,x3}, {%36,%37,%38,%39};\n"
        "ld.shared.v4.u32 {x0,x1,x2,x3}, [xa+0];\n"
        "tanh.approx.f32 t0, p0;\n"
        "tanh.approx.f32 t1, p2;\n"
        "fma.rn.f32 t0, p0, t0, p0;\n"
        "fma.rn.f32 t1, p2, t1, p2;\n"
        "cvt.rn.bf16x2.f32 r0, t1, t0;\n"
        "mov.b32 {lo,hi}, r1;\n"
        "mov.b32 rl, {lo,lo};\n"
        "mov.b32 rh, {hi,hi};\n"
        "mul.bf16x2 x4, x4, rl;\n"
        "mul.bf16x2 x5, x5, rl;\n"
        "mul.bf16x2 x6, x6, rh;\n"
        "mul.bf16x2 x7, x7, rh;\n"
        "mma.sync.aligned.m16n8k16.row.col.f32.bf16.bf16.f32 {%40,%41,%42,%43}, {b0,b1,b2,b3}, {x4,x5}, {%40,%41,%42,%43};\n"
        "mma.sync.aligned.m16n8k16.row.col.f32.bf16.bf16.f32 {%44,%45,%46,%47}, {b0,b1,b2,b3}, {x6,x7}, {%44,%45,%46,%47};\n"
        "ld.shared.v4.u32 {x4,x5,x6,x7}, [xa+128];\n"
        "tanh.approx.f32 t0, p4;\n"
        "tanh.approx.f32 t1, p6;\n"
        "fma.rn.f32 t0, p4, t0, p4;\n"
        "fma.rn.f32 t1, p6, t1, p6;\n"
        "cvt.rn.bf16x2.f32 r1, t1, t0;\n"
        "mma.sync.aligned.m16n8k8.row.col.f32.bf16.bf16.f32 {d0,d1,d2,d3}, {%177,%178}, {yb}, {fz,fz,fz,fz};\n"
        "cvt.rn.bf16x2.f32 a0, d2, d0;\n"
        "cvt.rn.bf16x2.f32 a1, d3, d1;\n"
        "mov.b32 {lo,hi}, r2;\n"
        "mov.b32 rl, {lo,lo};\n"
        "mov.b32 rh, {hi,hi};\n"
        "mul.bf16x2 x8, x8, rl;\n"
        "mul.bf16x2 x9, x9, rl;\n"
        "mul.bf16x2 x10, x10, rh;\n"
        "mul.bf16x2 x11, x11, rh;\n"
        "mma.sync.aligned.m16n8k16.row.col.f32.bf16.bf16.f32 {%48,%49,%50,%51}, {b0,b1,b2,b3}, {x8,x9}, {%48,%49,%50,%51};\n"
        "mma.sync.aligned.m16n8k16.row.col.f32.bf16.bf16.f32 {%52,%53,%54,%55}, {b0,b1,b2,b3}, {x10,x11}, {%52,%53,%54,%55};\n"
        "ld.shared.v4.u32 {x8,x9,x10,x11}, [xa+256];\n"
        "tanh.approx.f32 t0, p8;\n"
        "tanh.approx.f32 t1, p10;\n"
        "fma.rn.f32 t0, p8, t0, p8;\n"
        "fma.rn.f32 t1, p10, t1, p10;\n"
        "cvt.rn.bf16x2.f32 r2, t1, t0;\n"
        "mma.sync.aligned.m16n8k8.row.col.f32.bf16.bf16.f32 {d0,d1,d2,d3}, {%179,%180}, {yb}, {fz,fz,fz,fz};\n"
        "cvt.rn.bf16x2.f32 a2, d2, d0;\n"
        "cvt.rn.bf16x2.f32 a3, d3, d1;\n"
        "mov.b32 {lo,hi}, r3;\n"
        "mov.b32 rl, {lo,lo};\n"
        "mov.b32 rh, {hi,hi};\n"
        "mul.bf16x2 x12, x12, rl;\n"
        "mul.bf16x2 x13, x13, rl;\n"
        "mul.bf16x2 x14, x14, rh;\n"
        "mul.bf16x2 x15, x15, rh;\n"
        "mma.sync.aligned.m16n8k16.row.col.f32.bf16.bf16.f32 {%56,%57,%58,%59}, {b0,b1,b2,b3}, {x12,x13}, {%56,%57,%58,%59};\n"
        "mma.sync.aligned.m16n8k16.row.col.f32.bf16.bf16.f32 {%60,%61,%62,%63}, {b0,b1,b2,b3}, {x14,x15}, {%60,%61,%62,%63};\n"
        "ld.shared.v4.u32 {x12,x13,x14,x15}, [xa+384];\n"
        "tanh.approx.f32 t0, p12;\n"
        "tanh.approx.f32 t1, p14;\n"
        "fma.rn.f32 t0, p12, t0, p12;\n"
        "fma.rn.f32 t1, p14, t1, p14;\n"
        "cvt.rn.bf16x2.f32 r3, t1, t0;\n"
        "mov.b32 {lo,hi}, r0;\n"
        "mov.b32 rl, {lo,lo};\n"
        "mov.b32 rh, {hi,hi};\n"
        "mul.bf16x2 x0, x0, rl;\n"
        "mul.bf16x2 x1, x1, rl;\n"
        "mul.bf16x2 x2, x2, rh;\n"
        "mul.bf16x2 x3, x3, rh;\n"
        "mov.b32 {lo,hi}, r1;\n"
        "mov.b32 rl, {lo,lo};\n"
        "mov.b32 rh, {hi,hi};\n"
        "mul.bf16x2 x4, x4, rl;\n"
        "mul.bf16x2 x5, x5, rl;\n"
        "mul.bf16x2 x6, x6, rh;\n"
        "mul.bf16x2 x7, x7, rh;\n"
        "brx.idx.uni la, TA_%=;\n"
        "B2_%=:\n"
        "and.b32 la, ln, 255;\n"
        "shr.u32 lb, ln, 8;\n"
        "add.u32 ma, sa, %182;\n"
        "ldmatrix.sync.aligned.m8n8.x1.shared.b16 {yb}, [ma];\n"
        "add.u32 xa, sa, %181;\n"
        "mov.b32 {lo,hi}, r0;\n"
        "mov.b32 rl, {lo,lo};\n"
        "mov.b32 rh, {hi,hi};\n"
        "mul.bf16x2 x0, x0, rl;\n"
        "mul.bf16x2 x1, x1, rl;\n"
        "mul.bf16x2 x2, x2, rh;\n"
        "mul.bf16x2 x3, x3, rh;\n"
        "mma.sync.aligned.m16n8k16.row.col.f32.bf16.bf16.f32 {%64,%65,%66,%67}, {b0,b1,b2,b3}, {x0,x1}, {%64,%65,%66,%67};\n"
        "mma.sync.aligned.m16n8k16.row.col.f32.bf16.bf16.f32 {%68,%69,%70,%71}, {b0,b1,b2,b3}, {x2,x3}, {%68,%69,%70,%71};\n"
        "ld.shared.v4.u32 {x0,x1,x2,x3}, [xa+0];\n"
        "tanh.approx.f32 t0, p0;\n"
        "tanh.approx.f32 t1, p2;\n"
        "fma.rn.f32 t0, p0, t0, p0;\n"
        "fma.rn.f32 t1, p2, t1, p2;\n"
        "cvt.rn.bf16x2.f32 r0, t1, t0;\n"
        "mov.b32 {lo,hi}, r1;\n"
        "mov.b32 rl, {lo,lo};\n"
        "mov.b32 rh, {hi,hi};\n"
        "mul.bf16x2 x4, x4, rl;\n"
        "mul.bf16x2 x5, x5, rl;\n"
        "mul.bf16x2 x6, x6, rh;\n"
        "mul.bf16x2 x7, x7, rh;\n"
        "mma.sync.aligned.m16n8k16.row.col.f32.bf16.bf16.f32 {%72,%73,%74,%75}, {b0,b1,b2,b3}, {x4,x5}, {%72,%73,%74,%75};\n"
        "mma.sync.aligned.m16n8k16.row.col.f32.bf16.bf16.f32 {%76,%77,%78,%79}, {b0,b1,b2,b3}, {x6,x7}, {%76,%77,%78,%79};\n"
        "ld.shared.v4.u32 {x4,x5,x6,x7}, [xa+128];\n"
        "tanh.approx.f32 t0, p4;\n"
        "tanh.approx.f32 t1, p6;\n"
        "fma.rn.f32 t0, p4, t0, p4;\n"
        "fma.rn.f32 t1, p6, t1, p6;\n"
        "cvt.rn.bf16x2.f32 r1, t1, t0;\n"
        "mma.sync.aligned.m16n8k8.row.col.f32.bf16.bf16.f32 {d0,d1,d2,d3}, {%177,%178}, {yb}, {fz,fz,fz,fz};\n"
        "cvt.rn.bf16x2.f32 a0, d2, d0;\n"
        "cvt.rn.bf16x2.f32 a1, d3, d1;\n"
        "mov.b32 {lo,hi}, r2;\n"
        "mov.b32 rl, {lo,lo};\n"
        "mov.b32 rh, {hi,hi};\n"
        "mul.bf16x2 x8, x8, rl;\n"
        "mul.bf16x2 x9, x9, rl;\n"
        "mul.bf16x2 x10, x10, rh;\n"
        "mul.bf16x2 x11, x11, rh;\n"
        "mma.sync.aligned.m16n8k16.row.col.f32.bf16.bf16.f32 {%80,%81,%82,%83}, {b0,b1,b2,b3}, {x8,x9}, {%80,%81,%82,%83};\n"
        "mma.sync.aligned.m16n8k16.row.col.f32.bf16.bf16.f32 {%84,%85,%86,%87}, {b0,b1,b2,b3}, {x10,x11}, {%84,%85,%86,%87};\n"
        "ld.shared.v4.u32 {x8,x9,x10,x11}, [xa+256];\n"
        "tanh.approx.f32 t0, p8;\n"
        "tanh.approx.f32 t1, p10;\n"
        "fma.rn.f32 t0, p8, t0, p8;\n"
        "fma.rn.f32 t1, p10, t1, p10;\n"
        "cvt.rn.bf16x2.f32 r2, t1, t0;\n"
        "mma.sync.aligned.m16n8k8.row.col.f32.bf16.bf16.f32 {d0,d1,d2,d3}, {%179,%180}, {yb}, {fz,fz,fz,fz};\n"
        "cvt.rn.bf16x2.f32 a2, d2, d0;\n"
        "cvt.rn.bf16x2.f32 a3, d3, d1;\n"
        "mov.b32 {lo,hi}, r3;\n"
        "mov.b32 rl, {lo,lo};\n"
        "mov.b32 rh, {hi,hi};\n"
        "mul.bf16x2 x12, x12, rl;\n"
        "mul.bf16x2 x13, x13, rl;\n"
        "mul.bf16x2 x14, x14, rh;\n"
        "mul.bf16x2 x15, x15, rh;\n"
        "mma.sync.aligned.m16n8k16.row.col.f32.bf16.bf16.f32 {%88,%89,%90,%91}, {b0,b1,b2,b3}, {x12,x13}, {%88,%89,%90,%91};\n"
        "mma.sync.aligned.m16n8k16.row.col.f32.bf16.bf16.f32 {%92,%93,%94,%95}, {b0,b1,b2,b3}, {x14,x15}, {%92,%93,%94,%95};\n"
        "ld.shared.v4.u32 {x12,x13,x14,x15}, [xa+384];\n"
        "tanh.approx.f32 t0, p12;\n"
        "tanh.approx.f32 t1, p14;\n"
        "fma.rn.f32 t0, p12, t0, p12;\n"
        "fma.rn.f32 t1, p14, t1, p14;\n"
        "cvt.rn.bf16x2.f32 r3, t1, t0;\n"
        "mov.b32 {lo,hi}, r0;\n"
        "mov.b32 rl, {lo,lo};\n"
        "mov.b32 rh, {hi,hi};\n"
        "mul.bf16x2 x0, x0, rl;\n"
        "mul.bf16x2 x1, x1, rl;\n"
        "mul.bf16x2 x2, x2, rh;\n"
        "mul.bf16x2 x3, x3, rh;\n"
        "mov.b32 {lo,hi}, r1;\n"
        "mov.b32 rl, {lo,lo};\n"
        "mov.b32 rh, {hi,hi};\n"
        "mul.bf16x2 x4, x4, rl;\n"
        "mul.bf16x2 x5, x5, rl;\n"
        "mul.bf16x2 x6, x6, rh;\n"
        "mul.bf16x2 x7, x7, rh;\n"
        "brx.idx.uni la, TA_%=;\n"
        "B3_%=:\n"
        "and.b32 la, ln, 255;\n"
        "shr.u32 lb, ln, 8;\n"
        "add.u32 ma, sa, %182;\n"
        "ldmatrix.sync.aligned.m8n8.x1.shared.b16 {yb}, [ma];\n"
        "add.u32 xa, sa, %181;\n"
        "mov.b32 {lo,hi}, r0;\n"
        "mov.b32 rl, {lo,lo};\n"
        "mov.b32 rh, {hi,hi};\n"
        "mul.bf16x2 x0, x0, rl;\n"
        "mul.bf16x2 x1, x1, rl;\n"
        "mul.bf16x2 x2, x2, rh;\n"
        "mul.bf16x2 x3, x3, rh;\n"
        "mma.sync.aligned.m16n8k16.row.col.f32.bf16.bf16.f32 {%96,%97,%98,%99}, {b0,b1,b2,b3}, {x0,x1}, {%96,%97,%98,%99};\n"
        "mma.sync.aligned.m16n8k16.row.col.f32.bf16.bf16.f32 {%100,%101,%102,%103}, {b0,b1,b2,b3}, {x2,x3}, {%100,%101,%102,%103};\n"
        "ld.shared.v4.u32 {x0,x1,x2,x3}, [xa+0];\n"
        "tanh.approx.f32 t0, p0;\n"
        "tanh.approx.f32 t1, p2;\n"
        "fma.rn.f32 t0, p0, t0, p0;\n"
        "fma.rn.f32 t1, p2, t1, p2;\n"
        "cvt.rn.bf16x2.f32 r0, t1, t0;\n"
        "mov.b32 {lo,hi}, r1;\n"
        "mov.b32 rl, {lo,lo};\n"
        "mov.b32 rh, {hi,hi};\n"
        "mul.bf16x2 x4, x4, rl;\n"
        "mul.bf16x2 x5, x5, rl;\n"
        "mul.bf16x2 x6, x6, rh;\n"
        "mul.bf16x2 x7, x7, rh;\n"
        "mma.sync.aligned.m16n8k16.row.col.f32.bf16.bf16.f32 {%104,%105,%106,%107}, {b0,b1,b2,b3}, {x4,x5}, {%104,%105,%106,%107};\n"
        "mma.sync.aligned.m16n8k16.row.col.f32.bf16.bf16.f32 {%108,%109,%110,%111}, {b0,b1,b2,b3}, {x6,x7}, {%108,%109,%110,%111};\n"
        "ld.shared.v4.u32 {x4,x5,x6,x7}, [xa+128];\n"
        "tanh.approx.f32 t0, p4;\n"
        "tanh.approx.f32 t1, p6;\n"
        "fma.rn.f32 t0, p4, t0, p4;\n"
        "fma.rn.f32 t1, p6, t1, p6;\n"
        "cvt.rn.bf16x2.f32 r1, t1, t0;\n"
        "mma.sync.aligned.m16n8k8.row.col.f32.bf16.bf16.f32 {d0,d1,d2,d3}, {%177,%178}, {yb}, {fz,fz,fz,fz};\n"
        "cvt.rn.bf16x2.f32 a0, d2, d0;\n"
        "cvt.rn.bf16x2.f32 a1, d3, d1;\n"
        "mov.b32 {lo,hi}, r2;\n"
        "mov.b32 rl, {lo,lo};\n"
        "mov.b32 rh, {hi,hi};\n"
        "mul.bf16x2 x8, x8, rl;\n"
        "mul.bf16x2 x9, x9, rl;\n"
        "mul.bf16x2 x10, x10, rh;\n"
        "mul.bf16x2 x11, x11, rh;\n"
        "mma.sync.aligned.m16n8k16.row.col.f32.bf16.bf16.f32 {%112,%113,%114,%115}, {b0,b1,b2,b3}, {x8,x9}, {%112,%113,%114,%115};\n"
        "mma.sync.aligned.m16n8k16.row.col.f32.bf16.bf16.f32 {%116,%117,%118,%119}, {b0,b1,b2,b3}, {x10,x11}, {%116,%117,%118,%119};\n"
        "ld.shared.v4.u32 {x8,x9,x10,x11}, [xa+256];\n"
        "tanh.approx.f32 t0, p8;\n"
        "tanh.approx.f32 t1, p10;\n"
        "fma.rn.f32 t0, p8, t0, p8;\n"
        "fma.rn.f32 t1, p10, t1, p10;\n"
        "cvt.rn.bf16x2.f32 r2, t1, t0;\n"
        "mma.sync.aligned.m16n8k8.row.col.f32.bf16.bf16.f32 {d0,d1,d2,d3}, {%179,%180}, {yb}, {fz,fz,fz,fz};\n"
        "cvt.rn.bf16x2.f32 a2, d2, d0;\n"
        "cvt.rn.bf16x2.f32 a3, d3, d1;\n"
        "mov.b32 {lo,hi}, r3;\n"
        "mov.b32 rl, {lo,lo};\n"
        "mov.b32 rh, {hi,hi};\n"
        "mul.bf16x2 x12, x12, rl;\n"
        "mul.bf16x2 x13, x13, rl;\n"
        "mul.bf16x2 x14, x14, rh;\n"
        "mul.bf16x2 x15, x15, rh;\n"
        "mma.sync.aligned.m16n8k16.row.col.f32.bf16.bf16.f32 {%120,%121,%122,%123}, {b0,b1,b2,b3}, {x12,x13}, {%120,%121,%122,%123};\n"
        "mma.sync.aligned.m16n8k16.row.col.f32.bf16.bf16.f32 {%124,%125,%126,%127}, {b0,b1,b2,b3}, {x14,x15}, {%124,%125,%126,%127};\n"
        "ld.shared.v4.u32 {x12,x13,x14,x15}, [xa+384];\n"
        "tanh.approx.f32 t0, p12;\n"
        "tanh.approx.f32 t1, p14;\n"
        "fma.rn.f32 t0, p12, t0, p12;\n"
        "fma.rn.f32 t1, p14, t1, p14;\n"
        "cvt.rn.bf16x2.f32 r3, t1, t0;\n"
        "mov.b32 {lo,hi}, r0;\n"
        "mov.b32 rl, {lo,lo};\n"
        "mov.b32 rh, {hi,hi};\n"
        "mul.bf16x2 x0, x0, rl;\n"
        "mul.bf16x2 x1, x1, rl;\n"
        "mul.bf16x2 x2, x2, rh;\n"
        "mul.bf16x2 x3, x3, rh;\n"
        "mov.b32 {lo,hi}, r1;\n"
        "mov.b32 rl, {lo,lo};\n"
        "mov.b32 rh, {hi,hi};\n"
        "mul.bf16x2 x4, x4, rl;\n"
        "mul.bf16x2 x5, x5, rl;\n"
        "mul.bf16x2 x6, x6, rh;\n"
        "mul.bf16x2 x7, x7, rh;\n"
        "brx.idx.uni la, TA_%=;\n"
        "B4_%=:\n"
        "and.b32 la, ln, 255;\n"
        "shr.u32 lb, ln, 8;\n"
        "add.u32 ma, sa, %182;\n"
        "ldmatrix.sync.aligned.m8n8.x1.shared.b16 {yb}, [ma];\n"
        "add.u32 xa, sa, %181;\n"
        "mov.b32 {lo,hi}, r0;\n"
        "mov.b32 rl, {lo,lo};\n"
        "mov.b32 rh, {hi,hi};\n"
        "mul.bf16x2 x0, x0, rl;\n"
        "mul.bf16x2 x1, x1, rl;\n"
        "mul.bf16x2 x2, x2, rh;\n"
        "mul.bf16x2 x3, x3, rh;\n"
        "mma.sync.aligned.m16n8k16.row.col.f32.bf16.bf16.f32 {%128,%129,%130,%131}, {b0,b1,b2,b3}, {x0,x1}, {%128,%129,%130,%131};\n"
        "mma.sync.aligned.m16n8k16.row.col.f32.bf16.bf16.f32 {%132,%133,%134,%135}, {b0,b1,b2,b3}, {x2,x3}, {%132,%133,%134,%135};\n"
        "ld.shared.v4.u32 {x0,x1,x2,x3}, [xa+0];\n"
        "tanh.approx.f32 t0, p0;\n"
        "tanh.approx.f32 t1, p2;\n"
        "fma.rn.f32 t0, p0, t0, p0;\n"
        "fma.rn.f32 t1, p2, t1, p2;\n"
        "cvt.rn.bf16x2.f32 r0, t1, t0;\n"
        "mov.b32 {lo,hi}, r1;\n"
        "mov.b32 rl, {lo,lo};\n"
        "mov.b32 rh, {hi,hi};\n"
        "mul.bf16x2 x4, x4, rl;\n"
        "mul.bf16x2 x5, x5, rl;\n"
        "mul.bf16x2 x6, x6, rh;\n"
        "mul.bf16x2 x7, x7, rh;\n"
        "mma.sync.aligned.m16n8k16.row.col.f32.bf16.bf16.f32 {%136,%137,%138,%139}, {b0,b1,b2,b3}, {x4,x5}, {%136,%137,%138,%139};\n"
        "mma.sync.aligned.m16n8k16.row.col.f32.bf16.bf16.f32 {%140,%141,%142,%143}, {b0,b1,b2,b3}, {x6,x7}, {%140,%141,%142,%143};\n"
        "ld.shared.v4.u32 {x4,x5,x6,x7}, [xa+128];\n"
        "tanh.approx.f32 t0, p4;\n"
        "tanh.approx.f32 t1, p6;\n"
        "fma.rn.f32 t0, p4, t0, p4;\n"
        "fma.rn.f32 t1, p6, t1, p6;\n"
        "cvt.rn.bf16x2.f32 r1, t1, t0;\n"
        "mma.sync.aligned.m16n8k8.row.col.f32.bf16.bf16.f32 {d0,d1,d2,d3}, {%177,%178}, {yb}, {fz,fz,fz,fz};\n"
        "cvt.rn.bf16x2.f32 a0, d2, d0;\n"
        "cvt.rn.bf16x2.f32 a1, d3, d1;\n"
        "mov.b32 {lo,hi}, r2;\n"
        "mov.b32 rl, {lo,lo};\n"
        "mov.b32 rh, {hi,hi};\n"
        "mul.bf16x2 x8, x8, rl;\n"
        "mul.bf16x2 x9, x9, rl;\n"
        "mul.bf16x2 x10, x10, rh;\n"
        "mul.bf16x2 x11, x11, rh;\n"
        "mma.sync.aligned.m16n8k16.row.col.f32.bf16.bf16.f32 {%144,%145,%146,%147}, {b0,b1,b2,b3}, {x8,x9}, {%144,%145,%146,%147};\n"
        "mma.sync.aligned.m16n8k16.row.col.f32.bf16.bf16.f32 {%148,%149,%150,%151}, {b0,b1,b2,b3}, {x10,x11}, {%148,%149,%150,%151};\n"
        "ld.shared.v4.u32 {x8,x9,x10,x11}, [xa+256];\n"
        "tanh.approx.f32 t0, p8;\n"
        "tanh.approx.f32 t1, p10;\n"
        "fma.rn.f32 t0, p8, t0, p8;\n"
        "fma.rn.f32 t1, p10, t1, p10;\n"
        "cvt.rn.bf16x2.f32 r2, t1, t0;\n"
        "mma.sync.aligned.m16n8k8.row.col.f32.bf16.bf16.f32 {d0,d1,d2,d3}, {%179,%180}, {yb}, {fz,fz,fz,fz};\n"
        "cvt.rn.bf16x2.f32 a2, d2, d0;\n"
        "cvt.rn.bf16x2.f32 a3, d3, d1;\n"
        "mov.b32 {lo,hi}, r3;\n"
        "mov.b32 rl, {lo,lo};\n"
        "mov.b32 rh, {hi,hi};\n"
        "mul.bf16x2 x12, x12, rl;\n"
        "mul.bf16x2 x13, x13, rl;\n"
        "mul.bf16x2 x14, x14, rh;\n"
        "mul.bf16x2 x15, x15, rh;\n"
        "mma.sync.aligned.m16n8k16.row.col.f32.bf16.bf16.f32 {%152,%153,%154,%155}, {b0,b1,b2,b3}, {x12,x13}, {%152,%153,%154,%155};\n"
        "mma.sync.aligned.m16n8k16.row.col.f32.bf16.bf16.f32 {%156,%157,%158,%159}, {b0,b1,b2,b3}, {x14,x15}, {%156,%157,%158,%159};\n"
        "ld.shared.v4.u32 {x12,x13,x14,x15}, [xa+384];\n"
        "tanh.approx.f32 t0, p12;\n"
        "tanh.approx.f32 t1, p14;\n"
        "fma.rn.f32 t0, p12, t0, p12;\n"
        "fma.rn.f32 t1, p14, t1, p14;\n"
        "cvt.rn.bf16x2.f32 r3, t1, t0;\n"
        "mov.b32 {lo,hi}, r0;\n"
        "mov.b32 rl, {lo,lo};\n"
        "mov.b32 rh, {hi,hi};\n"
        "mul.bf16x2 x0, x0, rl;\n"
        "mul.bf16x2 x1, x1, rl;\n"
        "mul.bf16x2 x2, x2, rh;\n"
        "mul.bf16x2 x3, x3, rh;\n"
        "mov.b32 {lo,hi}, r1;\n"
        "mov.b32 rl, {lo,lo};\n"
        "mov.b32 rh, {hi,hi};\n"
        "mul.bf16x2 x4, x4, rl;\n"
        "mul.bf16x2 x5, x5, rl;\n"
        "mul.bf16x2 x6, x6, rh;\n"
        "mul.bf16x2 x7, x7, rh;\n"
        "brx.idx.uni la, TA_%=;\n"
        "EXIT_%=:\n"
        "mov.u32 %160, ring;\n"
        "}\n"
        : "+f"(acc[0][0][0][0]), "+f"(acc[0][0][0][1]), "+f"(acc[0][0][0][2]), "+f"(acc[0][0][0][3]), "+f"(acc[0][0][1][0]),
          "+f"(acc[0][0][1][1]), "+f"(acc[0][0][1][2]), "+f"(acc[0][0][1][3]), "+f"(acc[0][1][0][0]), "+f"(acc[0][1][0][1]),
          "+f"(acc[0][1][0][2]), "+f"(acc[0][1][0][3]), "+f"(acc[0][1][1][0]), "+f"(acc[0][1][1][1]), "+f"(acc[0][1][1][2]),
          "+f"(acc[0][1][1][3]), "+f"(acc[0][2][0][0]), "+f"(acc[0][2][0][1]), "+f"(acc[0][2][0][2]), "+f"(acc[0][2][0][3]),
          "+f"(acc[0][2][1][0]), "+f"(acc[0][2][1][1]), "+f"(acc[0][2][1][2]), "+f"(acc[0][2][1][3]), "+f"(acc[0][3][0][0]),
          "+f"(acc[0][3][0][1]), "+f"(acc[0][3][0][2]), "+f"(acc[0][3][0][3]), "+f"(acc[0][3][1][0]), "+f"(acc[0][3][1][1]),
          "+f"(acc[0][3][1][2]), "+f"(acc[0][3][1][3]), "+f"(acc[1][0][0][0]), "+f"(acc[1][0][0][1]), "+f"(acc[1][0][0][2]),
          "+f"(acc[1][0][0][3]), "+f"(acc[1][0][1][0]), "+f"(acc[1][0][1][1]), "+f"(acc[1][0][1][2]), "+f"(acc[1][0][1][3]),
          "+f"(acc[1][1][0][0]), "+f"(acc[1][1][0][1]), "+f"(acc[1][1][0][2]), "+f"(acc[1][1][0][3]), "+f"(acc[1][1][1][0]),
          "+f"(acc[1][1][1][1]), "+f"(acc[1][1][1][2]), "+f"(acc[1][1][1][3]), "+f"(acc[1][2][0][0]), "+f"(acc[1][2][0][1]),
          "+f"(acc[1][2][0][2]), "+f"(acc[1][2][0][3]), "+f"(acc[1][2][1][0]), "+f"(acc[1][2][1][1]), "+f"(acc[1][2][1][2]),
          "+f"(acc[1][2][1][3]), "+f"(acc[1][3][0][0]), "+f"(acc[1][3][0][1]), "+f"(acc[1][3][0][2]), "+f"(acc[1][3][0][3]),
          "+f"(acc[1][3][1][0]), "+f"(acc[1][3][1][1]), "+f"(acc[1][3][1][2]), "+f"(acc[1][3][1][3]), "+f"(acc[2][0][0][0]),
          "+f"(acc[2][0][0][1]), "+f"(acc[2][0][0][2]), "+f"(acc[2][0][0][3]), "+f"(acc[2][0][1][0]), "+f"(acc[2][0][1][1]),
          "+f"(acc[2][0][1][2]), "+f"(acc[2][0][1][3]), "+f"(acc[2][1][0][0]), "+f"(acc[2][1][0][1]), "+f"(acc[2][1][0][2]),
          "+f"(acc[2][1][0][3]), "+f"(acc[2][1][1][0]), "+f"(acc[2][1][1][1]), "+f"(acc[2][1][1][2]), "+f"(acc[2][1][1][3]),
          "+f"(acc[2][2][0][0]), "+f"(acc[2][2][0][1]), "+f"(acc[2][2][0][2]), "+f"(acc[2][2][0][3]), "+f"(acc[2][2][1][0]),
          "+f"(acc[2][2][1][1]), "+f"(acc[2][2][1][2]), "+f"(acc[2][2][1][3]), "+f"(acc[2][3][0][0]), "+f"(acc[2][3][0][1]),
          "+f"(acc[2][3][0][2]), "+f"(acc[2][3][0][3]), "+f"(acc[2][3][1][0]), "+f"(acc[2][3][1][1]), "+f"(acc[2][3][1][2]),
          "+f"(acc[2][3][1][3]), "+f"(acc[3][0][0][0]), "+f"(acc[3][0][0][1]), "+f"(acc[3][0][0][2]), "+f"(acc[3][0][0][3]),
          "+f"(acc[3][0][1][0]), "+f"(acc[3][0][1][1]), "+f"(acc[3][0][1][2]), "+f"(acc[3][0][1][3]), "+f"(acc[3][1][0][0]),
          "+f"(acc[3][1][0][1]), "+f"(acc[3][1][0][2]), "+f"(acc[3][1][0][3]), "+f"(acc[3][1][1][0]), "+f"(acc[3][1][1][1]),
          "+f"(acc[3][1][1][2]), "+f"(acc[3][1][1][3]), "+f"(acc[3][2][0][0]), "+f"(acc[3][2][0][1]), "+f"(acc[3][2][0][2]),
          "+f"(acc[3][2][0][3]), "+f"(acc[3][2][1][0]), "+f"(acc[3][2][1][1]), "+f"(acc[3][2][1][2]), "+f"(acc[3][2][1][3]),
          "+f"(acc[3][3][0][0]), "+f"(acc[3][3][0][1]), "+f"(acc[3][3][0][2]), "+f"(acc[3][3][0][3]), "+f"(acc[3][3][1][0]),
          "+f"(acc[3][3][1][1]), "+f"(acc[3][3][1][2]), "+f"(acc[3][3][1][3]), "+f"(acc[4][0][0][0]), "+f"(acc[4][0][0][1]),
          "+f"(acc[4][0][0][2]), "+f"(acc[4][0][0][3]), "+f"(acc[4][0][1][0]), "+f"(acc[4][0][1][1]), "+f"(acc[4][0][1][2]),
          "+f"(acc[4][0][1][3]), "+f"(acc[4][1][0][0]), "+f"(acc[4][1][0][1]), "+f"(acc[4][1][0][2]), "+f"(acc[4][1][0][3]),
          "+f"(acc[4][1][1][0]), "+f"(acc[4][1][1][1]), "+f"(acc[4][1][1][2]), "+f"(acc[4][1][1][3]), "+f"(acc[4][2][0][0]),
          "+f"(acc[4][2][0][1]), "+f"(acc[4][2][0][2]), "+f"(acc[4][2][0][3]), "+f"(acc[4][2][1][0]), "+f"(acc[4][2][1][1]),
          "+f"(acc[4][2][1][2]), "+f"(acc[4][2][1][3]), "+f"(acc[4][3][0][0]), "+f"(acc[4][3][0][1]), "+f"(acc[4][3][0][2]),
          "+f"(acc[4][3][0][3]), "+f"(acc[4][3][1][0]), "+f"(acc[4][3][1][1]), "+f"(acc[4][3][1][2]), "+f"(acc[4][3][1][3]),
          "+r"(ring)
        : "r"(wf[0][0]), "r"(wf[0][1]), "r"(wf[0][2]), "r"(wf[0][3]), "r"(wf[1][0]), "r"(wf[1][1]), "r"(wf[1][2]), "r"(wf[1][3]),
          "r"(wf[2][0]), "r"(wf[2][1]), "r"(wf[2][2]), "r"(wf[2][3]), "r"(wf[3][0]), "r"(wf[3][1]), "r"(wf[3][2]), "r"(wf[3][3]),
          "r"(cgf[0]), "r"(cgf[1]), "r"(cgf[2]), "r"(cgf[3]), "r"(xoff), "r"(moff), "r"(rec)
        : "memory");
}

__device__ __noinline__ void generic_path(float* sagg, const __nv_bfloat16* x, const int* src, const int* dst,
                                          const __nv_bfloat16* Y, const __nv_bfloat16* ef, const __nv_bfloat16* w_rad,
                                          const __nv_bfloat16* cg, int x0, int x1) {
    const int tid = threadIdx.x, lane = tid & 31, blk = blockIdx.x;
    for (int k = 0; k < 2; k++)
        for (int r = 0; r < min(k == 0 ? x0 : x1, 32); r++) {
            uint32_t* p2 = g_mail2 + (blk * NSRC + ((tid + k * NTHR) >> 3)) * 32 + r;
            uint32_t v;
            int it = 0;
            do {
                asm volatile("ld.relaxed.gpu.global.u32 %0, [%1];" : "=r"(v) : "l"(p2) : "memory");
                if (++it > (1 << 20)) __trap();
            } while (v == 0);
            *p2 = 0;
        }
    if (tid < 8 * NG) mbar_inval(smem_u32(sagg) + (tid >> 1) * STAGE + 4 * ROWP + (tid & 1) * 8);
    __syncthreads();
    for (int i = tid; i < NPB * 512; i += NTHR) sagg[i] = 0.f;
    __syncthreads();
    for (int e0 = tid & ~31; e0 < N_EDGES; e0 += NTHR) {
        uint32_t bm = __ballot_sync(~0u, dst[e0 + lane] / NPB == blk);
        while (bm) {
            const int e = e0 + __ffs(bm) - 1, s = src[e], loc = dst[e] - blk * NPB;
            bm &= bm - 1;
            float a[4][4];
            for (int i = 0; i < 4; i++)
                for (int o = 0; o < 4; o++) {
                    a[i][o] = 0.f;
                    for (int f = 0; f < 4; f++)
                        a[i][o] += __bfloat162float(Y[e * 4 + f]) * __bfloat162float(cg[i * 16 + f * 4 + o]);
                }
#pragma unroll 1
            for (int c = lane; c < 128; c += 32) {
                float pre = 0.f;
                for (int k = 0; k < 16; k++)
                    pre += __bfloat162float(ef[e * 16 + k]) * __bfloat162float(w_rad[k * 128 + c]);
                const float R = pre / (1.f + __expf(-pre));
                for (int o = 0; o < 4; o++) {
                    float acc = 0.f;
                    for (int i = 0; i < 4; i++) acc += __bfloat162float(x[(size_t)s * 512 + c * 4 + i]) * a[i][o];
                    atomicAdd(&sagg[loc * 512 + c * 4 + o], R * acc);
                }
            }
        }
    }
    __syncthreads();
}

__device__ __forceinline__ void init_barriers() {
    extern __shared__ __align__(1024) uint8_t smem[];
    const uint32_t sb = smem_u32(smem);
#pragma unroll
    for (int i = 0; i < 4 * NG; i++) {
        mbar_init(sb + i * STAGE + 4 * ROWP, 32);
        mbar_init(sb + i * STAGE + 4 * ROWP + 8, 2);
    }
}

template <int PHASES>
__global__ void __launch_bounds__(NTHR, 1)
tfn_kernel(const __nv_bfloat16* __restrict__ x, const int* __restrict__ src, const int* __restrict__ dst,
           const __nv_bfloat16* __restrict__ Y, const __nv_bfloat16* __restrict__ ef,
           const __nv_bfloat16* __restrict__ w_rad, const __nv_bfloat16* __restrict__ cg,
           const __nv_bfloat16* __restrict__ w_mix, __nv_bfloat16* __restrict__ out) {
    extern __shared__ __align__(1024) uint8_t smem[];
    const int tid = threadIdx.x, lane = tid & 31;
    const int warp = __shfl_sync(~0u, tid >> 5, 0);
    const int blk = blockIdx.x;
    uint32_t sb = smem_u32(smem);
    asm volatile("" : "+r"(sb));
    int* mi = reinterpret_cast<int*>(smem + SM_MISC);

    const int g = lane >> 2, t = lane & 3;
    const uint32_t dump = sb + SC_DUMP + lane * 4;
    int4 d1[2], s1[2];
    constexpr int nq = EPC / 4;
    const bool binner = (PHASES & 1) && blk < NSRC;
    if (binner) {
#pragma unroll
        for (int k = 0; k < 2; k++) {
            const int q = tid + k * NTHR;
            if (q < nq) {
                d1[k] = __ldg(reinterpret_cast<const int4*>(dst + blk * EPC) + q);
                s1[k] = __ldg(reinterpret_cast<const int4*>(src + blk * EPC) + q);
            }
        }
    }
    if (binner) {
        const uint32_t dmy = ((((blk & 3) * 8 + (tid & 7)) << 25) | (80 * 2560 + 1));
#pragma unroll
        for (int k = 0; k < 3; k++)
            if (k < 2 || warp < 1) sts128(sb + SC_MAIL + (tid + k * NTHR) * 16, dmy, dmy + (1u << 30), dmy, dmy + (1u << 30));
        if (tid <= NB / 4) sts128(sb + SC_CNT + tid * 16, 0, 0, 0, 0);
    }
    if (PHASES & 2) {
        if (tid == 160) { sts128(sb + SM_MISC, 0, 0, 0, 0); sts128(sb + SM_MISC + MI_NU * 4, 0, 0, 0, 0); }
        if (tid == 161) {
            mi[MI_SHIFT] = 0;
            *reinterpret_cast<int**>(mi + MI_SHIFT + 4) = g_lag[blk];
        }
        if (tid == 162) g_lag[blk][0] = g_lag[NB + blk][0] = 0;
        if (tid <= 21 * HS / 4) sts128(sb + SC_HIST + tid * 16, 0, 0, 0, 0);
        if (tid < 4 * UCAP) {
#pragma unroll
            for (int k = 0; k < 12; k++) sts32(sb + SM_REC + tid * REC + k * 4, k < 4 ? ~0u : (uint32_t)(blk * 4096 + tid * 8 + 7));
        }
    }
    __syncthreads();
    if (PHASES & 2) {
        if (warp >= 8) cp16(sb + SC_WR + ((tid - 256) ^ ((tid >> 4) & 6)) * 16, w_rad + (tid - 256) * 8);
        if (tid < 8) cp16(sb + SC_WR + 4096 + tid * 16, cg + tid * 8);
        asm volatile("cp.async.commit_group;" ::: "memory");
#pragma unroll
        for (int k = 0; k < 4; k++) {
            const int i = tid + k * NTHR, c = i >> 4;
            cp16(sb + SM_W + c * 256 + (((i & 15) ^ ((c & 2) | (((c >> 4) & 1) << 2))) << 4), w_mix + i * 8);
        }
    }
    if (binner) {
#pragma unroll
        for (int k = 0; k < 2; k++) {
            if (tid + k * NTHR < nq) {
                const uint32_t dd[4] = {(uint32_t)d1[k].x, (uint32_t)d1[k].y, (uint32_t)d1[k].z, (uint32_t)d1[k].w};
                const uint32_t ss[4] = {(uint32_t)s1[k].x, (uint32_t)s1[k].y, (uint32_t)s1[k].z, (uint32_t)s1[k].w};
                uint32_t own[4], rk[4], v[4];
#pragma unroll
                for (int j = 0; j < 4; j++) { own[j] = dd[j] / NPB; rk[j] = atoms_inc(sb + SC_CNT + own[j] * 4); }
#pragma unroll
                for (int j = 0; j < 4; j++) {
                    const uint32_t loc = dd[j] - own[j] * NPB, code = loc + ((loc * 216) >> 12);
                    v[j] = (ss[j] << 18) + code * 2560 + (tid + k * NTHR) * 4 + j + 1;
                    sts32(sb + SC_MAIL + own[j] * 128 + ((min(rk[j], 31u) * 4) ^ ((own[j] & 7) << 4)), v[j]);
                }
                if (max(max(rk[0], rk[1]), max(rk[2], rk[3])) >= 31) {
#pragma unroll
                    for (int j = 0; j < 4; j++)
                        if (rk[j] - 31 < 32)
                            asm volatile("st.relaxed.gpu.global.u32 [%0], %1;" ::"l"(g_mail2 + (own[j] * NSRC + blk) * 32 + rk[j] - 31), "r"(v[j]) : "memory");
                }
            }
        }
        __syncwarp();
        asm volatile("red.shared.max.u32 [%0], %1;" ::"r"(lane == 0 ? sb + SC_CNT + NB * 4 : dump), "r"(gtime()) : "memory");
        STAMP(1);
    }
    asm volatile("cp.async.wait_group 0;" ::: "memory");
    __syncthreads();
    if (binner) {
        const uint32_t hdr = 0xc0000000u | ((lds32(sb + SC_CNT + NB * 4) << 7) & 0x3ffff000u);
        uint4 mv[3];
        uint32_t mc[3];
#pragma unroll
        for (int k = 0; k < 3; k++)
            if (k < 2 || warp < 1) {
                const int j = tid + k * NTHR, own = j >> 3;
                mv[k] = lds128(sb + SC_MAIL + own * 128 + (((j ^ own) & 7) << 4));
                mc[k] = lds32(sb + SC_CNT + own * 4);
            }
#pragma unroll
        for (int k = 0; k < 3; k++)
            if (k < 2 || warp < 1) {
                const int j = tid + k * NTHR;
                asm volatile("st.relaxed.gpu.global.v4.u32 [%0], {%1,%2,%3,%4};" ::"l"(g_mail + ((j >> 3) * NSRC + blk) * 8 + (j & 7)),
                             "r"(mv[k].x), "r"(mv[k].y), "r"(mv[k].z), "r"((j & 7) == 7 ? hdr | mc[k] : mv[k].w) : "memory");
            }
        STAMP(2);
    }
    if (!(PHASES & 2)) return;
    const uint32_t tpub = (uint32_t)clock() + (blk < NSRC ? 0 : IDLE_EST);
    if (warp >= 7) {
        uint32_t f[4];
        if (warp >= 8) {
            uint32_t w[4];
#pragma unroll
            for (int j = 0; j < 4; j++)
                w[j] = mul_lo(lds32(sb + SC_WR + (2 * t + (j & 1) + (j >> 1) * 8) * 256 + ((((warp - 8) * 8 + g) * 4) ^ (t << 5))), 0x3f003f00u);
            f[0] = __byte_perm(w[0], w[1], 0x5410); f[1] = __byte_perm(w[0], w[1], 0x7632);
            f[2] = __byte_perm(w[2], w[3], 0x5410); f[3] = __byte_perm(w[2], w[3], 0x7632);
        } else {
#pragma unroll
            for (int i = 0; i < 4; i++) {
                const uint32_t ca = sb + SC_WR + 4096 + (i * 16 + (t & 1) * 8 + (g & 3)) * 2;
                f[i] = (lds16(ca) | (lds16(ca + 8) << 16)) & ((t >> 1) == (g >> 2) ? ~0u : 0u);
            }
        }
        const uint32_t d = sb + (warp == 7 ? 2 * ROWP : ((warp - 8) >> 2) * ROWP + (warp & 3) * 512) + lane * 16;
#pragma unroll
        for (int k = 0; k < 4; k++) sts128(d + k * NG * STAGE, f[0], f[1], f[2], f[3]);
    }
    asm volatile("cp.async.wait_all;" ::: "memory");
    __syncwarp();
#pragma unroll
    for (int k = 0; k < 2; k++) {
        const int i = (tid & ~1) + ((tid & 1) * 2 + k) * NTHR, c = i >> 4;
        const uint32_t a0 = sb + SM_W + c * 256 + (((i & 15) ^ ((c & 3) | (((c >> 4) & 1) << 2))) << 4);
        const uint32_t o = (tid & 1) << 4;
        uint4 u = lds128((a0 & ~16u) ^ o), v = lds128((a0 | 16u) ^ o);
        if (tid & 1) { const uint4 w = u; u = v; v = w; }
        const uint32_t s0 = (tid & 1) ? 0x7632 : 0x5410, s1 = s0 ^ 0x2222;
        sts128(a0 ^ o, __byte_perm(u.x, u.y, s0), __byte_perm(u.z, u.w, s0), __byte_perm(v.x, v.y, s0), __byte_perm(v.z, v.w, s0));
        sts128(a0 ^ o ^ 16, __byte_perm(u.x, u.y, s1), __byte_perm(u.z, u.w, s1), __byte_perm(v.x, v.y, s1), __byte_perm(v.z, v.w, s1));
    }

    uint32_t en[8], hr[8], rk[8], em[8];
    int xc[2];
    const uint32_t tref = __shfl_sync(~0u, gtime() >> 5, 0);
    {
        uint4* mp = g_mail + blk * NSRC * 8 + tid;
        int it = 0;
        bool ok;
        while ((int)((uint32_t)clock() - tpub) < POLL_DELAY) {}
        do {
#pragma unroll
            for (int k = 0; k < 2; k++)
                    asm volatile("ld.relaxed.gpu.global.v4.u32 {%0,%1,%2,%3}, [%4];"
                                 : "=r"(en[4 * k]), "=r"(en[4 * k + 1]), "=r"(en[4 * k + 2]), "=r"(en[4 * k + 3])
                                 : "l"(mp + k * NTHR) : "memory");
            uint32_t m = ~0u;
#pragma unroll
            for (int i = 0; i < 8; i++) m = min(m, en[i]);
            ok = __all_sync(~0u, m != 0);
            if (++it > (1 << 20)) __trap();
        } while (!ok);
        STAMP(3);
        const bool hd = (lane & 7) == 7;
        const uint32_t h0 = en[3], h1 = en[7];
        if (hd) en[3] = en[7] = ((64 + (tid >> 5)) << 25) | (80 * 2560 + 1);
        const uint32_t e0 = (tid >> 3) * EPC * 8 - 8;
#pragma unroll
        for (int i = 0; i < 8; i++) {
            const uint32_t w = en[i] & 0x3ffff, code = ((w >> 9) * 13108) >> 16;
            hr[i] = sb + SC_HIST + ((code >> 2) * HS + (en[i] >> 25)) * 4;
            rk[i] = atoms_inc(hr[i]);
            em[i] = (e0 + (i >> 2) * (NTHR / 8 * EPC * 8) + (w - code * 2560) * 8) | (code & 3);
        }
        int dt = hd ? max((int)(((h0 >> 12) - tref) << 14), (int)(((h1 >> 12) - tref) << 14)) >> 14 : -(1 << 20);
        xc[0] = hd ? max((int)(h0 & 0xfff) - 31, 0) : 0;
        xc[1] = hd ? max((int)(h1 & 0xfff) - 31, 0) : 0;
        dt = __reduce_max_sync(~0u, dt);
        asm volatile("red.shared.max.u32 [%0], %1;" ::"r"(lane == 0 ? sb + SM_MISC + MI_TMAX * 4 : dump + 128), "r"(tref + dt + (1u << 27)) : "memory");
        if (xc[0] | xc[1]) {
#pragma unroll
            for (int k = 0; k < 2; k++) {
                const int slot = atomicAdd(&mi[MI_XN], xc[k]);
                for (int r = 0; r < xc[k] && slot + r < 32; r++)
                    reinterpret_cast<uint32_t*>(smem + SC_XTRA)[slot + r] = ((tid + k * NTHR) >> 3) * 32 + r;
            }
        }
#pragma unroll
        for (int k = 0; k < 2; k++)
            mp[k * NTHR] = make_uint4(0, 0, 0, 0);
    }
    __syncthreads();
    STAMP(4);
    uint32_t* hist = reinterpret_cast<uint32_t*>(smem + SC_HIST);
    const int xn = mi[MI_XN];
    uint32_t xi = 0, xv = 1;
    if (warp < 10) {
        uint32_t* hp = hist + (warp * 2 + (lane >> 4)) * HS + (lane & 15) * 5;
        int c[5], s = 0;
#pragma unroll
        for (int j = 0; j < 5; j++) { c[j] = hp[j]; s += c[j]; }
        int inc = s;
#pragma unroll
        for (int o = 1; o < 16; o <<= 1) { int v = __shfl_up_sync(~0u, inc, o, 16); if ((lane & 15) >= o) inc += v; }
        int base = 0;
        if ((lane & 15) == 15) {
            const int tm = (warp * 2 + (lane >> 4)) / 5;
            base = tm * 256 + atomicAdd(&mi[MI_NU + tm], (inc + 3) >> 2);
            hp[5] = (base + ((inc + 3) >> 2)) << 16;
        }
        const int tot = __shfl_sync(~0u, inc, 15, 16);
        base = __shfl_sync(~0u, base, 15, 16);
        int ex = inc - s;
#pragma unroll
        for (int j = 0; j < 5; j++) {
            hp[j] = (base * 4 + ex) | ((base + ((ex == tot ? ex + 3 : ex + 1) >> 2)) << 16);
            ex += c[j];
        }
    } else if (warp == 10) {
        if (lane < xn) {
            xi = reinterpret_cast<const uint32_t*>(smem + SC_XTRA)[lane];
            asm volatile("ld.relaxed.gpu.global.u32 %0, [%1];" : "=r"(xv) : "l"(g_mail2 + blk * NSRC * 32 + xi) : "memory");
        }
    } else if (warp == 12) {
        if (lane == 0) init_barriers();
    } else if (warp == 11) {
        sts32(sb + SC_GPOS + (GDUMMY + lane) * 4, (uint32_t)(4 * UCAP * REC + 128) * 0x10001u);
#pragma unroll
        for (int k = 0; k < 3; k++) hist[20 * HS + min(lane + 32 * k, NBK)] = GDUMMY * 4;
        constexpr int start_ns = START_NS;
        if (lane == 0) mi[MI_T0] = (uint32_t)clock() + (((int)(((uint32_t)mi[MI_TMAX] << 5) + start_ns - gtime()) * 31) >> 4);
    }
    constexpr int pace = PACE_Q8, p1 = PACE_HEAD, b1 = HEAD_BK, p2 = PACE_TAIL, b2 = TAIL_BK, lead = PACE_LEAD;
    auto sched = [&](int b) { return b * pace - min(b, b1) * (pace - p1) - max(b - b2, 0) * (pace - p2) - lead; };
    const int mteam = tid / NBK, mb = tid - mteam * NBK;
    int tb0 = sched(mb);
    float tbw = (float)(sched(mb + 1) - tb0);
    uint32_t mh = sb + SC_HIST + (mteam * 5 * HS + mb) * 4 + 2, mh0 = sb + SC_HIST + mteam * 5 * HS * 4 + 2;
    asm volatile("" : "+r"(tb0), "+f"(tbw), "+r"(mh), "+r"(mh0));
    __syncthreads();
    STAMP(10);
    int myng = mi[MI_NU + (lane & 3)];
    const bool ovf = __any_sync(~0u, myng + xn > 2 * (UCAP - 4) || xn > 32);
    if (!ovf) {
        if (warp < 10) {
            int lo[5], n[5], pos = mteam * UCAP * 2, nsum = 0;
#pragma unroll
            for (int q = 0; q < 5; q++) {
                lo[q] = lds16(mh + q * HS * 4);
                n[q] = lds16(mh + q * HS * 4 + 4) - lo[q];
                pos += lo[q] - lds16(mh0 + q * HS * 4);
                nsum += n[q];
            }
            const int step = __float2int_rz(__fdividef(tbw, (float)max(nsum, 1)));
            const int tb = tb0 + (step >> 1) - pos * step;
            const uint32_t t0 = mi[MI_T0];
            auto emit = [&](int q, int r, int pq) {
                const uint32_t ro = (pq >> 1) * REC, par = pq & 1;
                asm volatile("{\n.reg .pred p, e;\nsetp.lt.s32 p, %0, %1;\nsetp.eq.and.u32 e, %2, 0, p;\n"
                             "@p st.shared.u32 [%3], %4;\n@p st.shared.u8 [%5+48], %6;\n@e st.shared.u16 [%5+102], %7;\n}"
                             ::"r"(r), "r"(n[q]), "r"(par), "r"(sb + SC_GPOS + (lo[q] + r) * 4),
                               "r"(ro * 0x10001u + par * 0x40002u + (REC | (16 << 16))), "r"(sb + SM_REC + ro + par), "r"(q),
                               "h"((uint16_t)((t0 + max(tb + pq * step, 0)) >> 2)) : "memory");
            };
#pragma unroll
            for (int q = 0, pq = pos; q < 5; pq += n[q], q++) emit(q, 0, pq);
#pragma unroll
            for (int q = 0; q < 5; pos += n[q], q++)
#pragma unroll 1
                for (int r = 1; __any_sync(~0u, r < n[q]); r++) emit(q, r, pos + r);
        } else if (warp == 10) {
            for (int n = 0; __any_sync(~0u, xv == 0); n++) {
                if (xv == 0) asm volatile("ld.relaxed.gpu.global.u32 %0, [%1];" : "=r"(xv) : "l"(g_mail2 + blk * NSRC * 32 + xi) : "memory");
                if (n > (1 << 20)) __trap();
            }
            const uint32_t w = xv & 0x3ffff, code = ((w >> 9) * 13108) >> 16, xt = lane < xn ? code / 20 : 4;
            const uint32_t same = __match_any_sync(~0u, xt);
            const int pq = __shfl_sync(~0u, myng, xt & 3) + __popc(same & ((1u << lane) - 1));
#pragma unroll
            for (int q = 0; q < 4; q++) {
                const int c = __popc(__ballot_sync(~0u, xt == q));
                if (lane == q) myng += c;
            }
            if (lane < xn) {
                g_mail2[blk * NSRC * 32 + xi] = 0;
                const uint32_t a = sb + SM_REC + (xt * UCAP + (pq >> 1)) * REC;
                sts16(a + REC + (pq & 1) * 2, xv >> 18);
                sts32(a + 16 + (pq & 1) * 4, (((xi >> 5) * EPC + w - code * 2560 - 1) * 8) | (code & 3));
                sts8(a + 48 + (pq & 1), (code >> 2) - xt * 5);
                if (!(pq & 1)) sts16(a + REC + 50, ((uint32_t)mi[MI_T0] + sched(NBK - 2)) >> 2);
            }
            if (lane < 4) {
                const uint32_t a = sb + SM_REC + (lane * UCAP + (myng >> 1)) * REC + 48;
                if (myng & 1) sts8(a + 1, 0);
                sts16(a + (myng & 1) * REC, 5);
                mi[MI_END + lane] = (myng + 1) >> 1;
            }
        }
#pragma unroll
        for (int i = 0; i < 8; i++) {
            const uint32_t p = rk[i] + lds16(hr[i]);
            hr[i] = sb + SC_GPOS + (p & ~3u);
            rk[i] = (p & 3) * 0x80004u;
        }
        __syncthreads();
        STAMP(11);
#pragma unroll
        for (int i = 0; i < 8; i++) rk[i] += lds32(hr[i]);
#pragma unroll
        for (int i = 0; i < 8; i++) {
            sts16(sb + SM_REC + (rk[i] & 0xffff), en[i] >> 18);
            sts32(sb + SM_REC + (rk[i] >> 16), em[i]);
        }
    } else {
        if (tid < 4) {
            sts16(sb + SM_REC + tid * UCAP * REC + 48, 5);
            mi[MI_END + tid] = 0;
        }
        generic_path(reinterpret_cast<float*>(smem), x, src, dst, Y, ef, w_rad, cg, xc[0], xc[1]);
    }

    __syncwarp();
    if (warp >= 8) {
        asm volatile("bar.sync 3, 512;" ::: "memory");
        asm volatile("setmaxnreg.dec.sync.aligned.u32 24;");
        const int team = warp & 3;
        if (ovf) {
            asm volatile("bar.sync 2;" ::: "memory");
            if (tid == 256) init_barriers();
            asm volatile("bar.sync 2;" ::: "memory");
        }
        STAMP(5);
        const uint32_t ring = sb + SM_RING + team * NG * STAGE;
        const uint32_t q = lane >> 3, c = lane & 7, rec = sb + SM_REC + team * UCAP * REC;
        __syncwarp();
        producer_loop(reinterpret_cast<const char*>(x) + (lane & 15) * 16, reinterpret_cast<const char*>(ef) + (c & 1) * 16, Y,
                      q * ROWP + ((c ^ (q << 1)) << 4), q * 4 + (c & 2) * 8, (c & 1) * 2 + (c >> 2), ring, rec,
                      rec + (mi[MI_END + team] + 1) * REC, warp - 8, sb + SM_MISC + MI_SHIFT * 4,
                      (lane >> 4) * ROWP + (((lane & 15) ^ ((lane >> 4) << 1)) << 4));
        uint32_t ln, sb2, cta;
        asm volatile("mov.u32 %0, %%tid.x;\nmov.u32 %1, %%ctaid.x;\nmov.u32 %2, %%dynamic_smem_size;" : "=r"(ln), "=r"(cta), "=r"(sb2));
        asm volatile("bar.arrive %0, 128;" ::"r"(4 + ((ln >> 5) & 3)) : "memory");
        if (cta == NB - 1 && ln >= NTHR - 32) {
            ln &= 31;
            sb2 += smem_u32(smem) - SM_TOTAL + SM_MISC;
            constexpr int lead = LEAD_CLK >> 2;
            const uint32_t tend = lds32(sb2 + MI_T0 * 4) + 70 * PACE_Q8;
            int sh = 0;
            for (int n = 0; n < 199 && (int)((uint32_t)clock() - tend - (sh >> 14)) < 0; n++) {
                int v;
                asm volatile("ld.relaxed.gpu.global.s32 %0, [%1];" : "=r"(v) : "l"(g_lag[ln * 4]) : "memory");
                const int err = (__reduce_add_sync(~0u, max(v, 0)) >> 5) - lead;
                const int old = sh;
                sh = min(max((sh >> 16) + (err * (err > 0 ? FB_GAIN : FB_DOWN) >> 3), FB_MIN), 2500) << 16;
                if (sh == old) continue;
#pragma unroll
                for (int k = 0; k < 5; k++)
                    asm volatile("st.relaxed.gpu.global.s32 [%0], %1;" ::"l"(g_lag[NB + min(ln + 32 * k, NB - 1u)]), "r"(sh) : "memory");
            }
        }
    } else {
        asm volatile("bar.arrive 3, 512;" ::: "memory");
        int team;
        {
            const int n0 = mi[MI_END], n1 = mi[MI_END + 1], n2 = mi[MI_END + 2], n3 = mi[MI_END + 3];
            const int d1 = abs(n0 + n1 - n2 - n3), d2 = abs(n0 + n2 - n1 - n3), d3 = abs(n0 + n3 - n1 - n2);
            const uint32_t perm = d1 < min(d2, d3) ? 0x3120 : d3 < d2 ? 0x2310 : 0x3210;
            team = __shfl_sync(~0u, (perm >> ((warp >> 1) * 4)) & 3, 0);
        }
        const int h = warp & 1;
        asm volatile("setmaxnreg.inc.sync.aligned.u32 232;");
        uint32_t ring = sb + SM_RING + team * NG * STAGE;
        uint32_t wf[4][4], cgf[4];
#pragma unroll
        for (int m = 0; m < 5; m++) {
            const uint4 v = lds128(ring + (m < 4 ? h * ROWP + m * 512 : 2 * ROWP) + lane * 16);
            uint32_t* f = m < 4 ? wf[m] : cgf;
            f[0] = v.x; f[1] = v.y; f[2] = v.z; f[3] = v.w;
        }
        float acc[5][4][2][4];
        if (!ovf) {
#pragma unroll
            for (int l = 0; l < 5; l++)
#pragma unroll
                for (int m = 0; m < 4; m++)
#pragma unroll
                    for (int p = 0; p < 2; p++)
#pragma unroll
                        for (int r = 0; r < 4; r++) acc[l][m][p][r] = 0.f;
        } else {
            const float* sagg = reinterpret_cast<const float*>(smem);
#pragma unroll
            for (int l = 0; l < 5; l++)
#pragma unroll
                for (int m = 0; m < 4; m++)
#pragma unroll
                    for (int p = 0; p < 2; p++)
#pragma unroll
                        for (int r = 0; r < 4; r++) {
                            int nd = l * 4 + (g >> 2) + (r >> 1) * 2;
                            int ch = h * 64 + m * 16 + 4 * t + (r & 1) * 2 + p;
                            acc[l][m][p][r] = nd < 19 ? sagg[(team * 19 + nd) * 512 + ch * 4 + (g & 3)] : 0.f;
                        }
            asm volatile("bar.sync 2;" ::: "memory");
            asm volatile("bar.sync 2;" ::: "memory");
        }
        const uint32_t xoff = t * ROWP + h * 512 + ((g ^ (t << 1)) << 4);
        const uint32_t mat = lane >> 3, mhi = (lane >> 2) & 1;
        const bool isy = mat < 2;
        const uint32_t ml = isy ? (t & 2) + (mat & 1) : t;
        const uint32_t moff = ml * ROWP + 2048 + (((isy ? 4 + 2 * mhi + (t & 1) : 2 * mhi + mat - 2) ^ (ml << 1)) << 4);
        __syncwarp();
        consumer_loop(acc, wf, cgf, xoff, ring, moff, sb + SM_REC + team * UCAP * REC);
        {
        int lane_;
        asm volatile("mov.u32 %0, %%laneid;" : "=r"(lane_));
        const int lane = lane_, g = lane >> 2, t = lane & 3;
        const uint32_t sb = ring - team * NG * STAGE;
        STAMP(7);
        asm volatile("bar.sync %0, 128;" ::"r"(4 + team) : "memory");
        if (lane == 0) {
            mbar_inval(ring + h * STAGE + 4 * ROWP);
            mbar_inval(ring + h * STAGE + 4 * ROWP + 8);
        }
        __syncwarp();
        {
            const int rr = ((g & 3) >> 1) * 8 + (g >> 2) * 2 + (g & 1);
#pragma unroll
            for (int l = 0; l < 5; l++)
#pragma unroll
                for (int hi = 0; hi < 2; hi++) {
                    const int R = l * 16 + rr + hi * 4;
                    const uint32_t a = sb + team * AGGT + h * 10240 + R * 128;
#pragma unroll
                    for (int c = 0; c < 2; c++) {
                        const int m = 2 * c;
                        sts128(a + (((2 * t + c) ^ (R & 7)) << 4),
                               pack_bf16(acc[l][m][0][2 * hi], acc[l][m][1][2 * hi]),
                               pack_bf16(acc[l][m][0][2 * hi + 1], acc[l][m][1][2 * hi + 1]),
                               pack_bf16(acc[l][m + 1][0][2 * hi], acc[l][m + 1][1][2 * hi]),
                               pack_bf16(acc[l][m + 1][0][2 * hi + 1], acc[l][m + 1][1][2 * hi + 1]));
                    }
                }
        }
        asm volatile("fence.proxy.async.shared::cta;" ::: "memory");
        uint32_t wa[8][4];
        {
            const int r = lane & 7, k = (lane >> 4) * 8 + r;
            const int chunk = (2 * warp + ((lane >> 3) & 1)) ^ r;
#pragma unroll
            for (int ks = 0; ks < 8; ks++) {
                const int c = (ks >> 2) * 64 + 16 * (k >> 2) + 4 * (ks & 3) + (k & 3);
                asm volatile("ldmatrix.sync.aligned.m8n8.x4.trans.shared.b16 {%0,%1,%2,%3}, [%4];"
                             : "=r"(wa[ks][0]), "=r"(wa[ks][1]), "=r"(wa[ks][2]), "=r"(wa[ks][3])
                             : "r"(sb + SM_W + c * 256 + (chunk << 4)));
            }
        }
        asm volatile("bar.sync 1, 256;" ::: "memory");
        STAMP(8);
        const int sl = (lane & 7) * 4 + (lane >> 3);
        __nv_bfloat16* op = out + (size_t)(blk * NPB + (lane >> 3)) * 512 + warp * 64 + (lane & 7) * 8;
        const int nleft = N_NODES - blk * NPB - (lane >> 3);
        uint32_t pk[20];
        auto store = [&](int tm) {
#pragma unroll
            for (int l = 0; l < 5; l++) {
                uint4 v;
                v.x = __shfl_sync(~0u, pk[4 * l + 0], sl);
                v.y = __shfl_sync(~0u, pk[4 * l + 1], sl);
                v.z = __shfl_sync(~0u, pk[4 * l + 2], sl);
                v.w = __shfl_sync(~0u, pk[4 * l + 3], sl);
                asm volatile("{\n.reg .pred p;\nsetp.lt.u32 p, %5, %6;\n@p st.global.v4.u32 [%0], {%1,%2,%3,%4};\n}"
                             ::"l"(op + (tm * 19 + l * 4) * 512), "r"(v.x), "r"(v.y), "r"(v.z), "r"(v.w), "r"(tm * 19 + l * 4),
                               "r"(l < 4 || lane < 24 ? nleft : 0) : "memory");
            }
        };
        if (warp >= 4) asm volatile("bar.sync 10, 256;" ::: "memory");
#pragma unroll 1
        for (int tm = 0; tm < 4; tm++) {
            float o[40];
            asm volatile("wgmma.fence.sync.aligned;" ::: "memory");
#pragma unroll
            for (int ks = 0; ks < 8; ks++) {
                const uint32_t a = sb + tm * AGGT + (ks >> 2) * 10240 + (ks & 3) * 32;
                const uint64_t desc = (uint64_t)((a & 0x3ffff) >> 4) | (1ull << 16) | (64ull << 32) | (1ull << 62);
                wgmma_n80(o, wa[ks], desc, ks);
            }
            asm volatile("wgmma.commit_group.sync.aligned;" ::: "memory");
            if (tm == 0 && warp < 4) asm volatile("bar.arrive 10, 256;" ::: "memory");
            asm volatile("wgmma.wait_group.sync.aligned 0;" ::: "memory");
#pragma unroll
            for (int i = 0; i < 40; i++) asm volatile("" : "+f"(o[i])::"memory");
#pragma unroll
            for (int l = 0; l < 5; l++) {
                pk[4 * l + 0] = pack_bf16(o[8 * l + 0], o[8 * l + 1]);
                pk[4 * l + 1] = pack_bf16(o[8 * l + 4], o[8 * l + 5]);
                pk[4 * l + 2] = pack_bf16(o[8 * l + 2], o[8 * l + 3]);
                pk[4 * l + 3] = pack_bf16(o[8 * l + 6], o[8 * l + 7]);
            }
            store(tm);
        }
        STAMP(9);
        }
    }
}

}

extern "C" void kernel_launch(void* const* d_in, const int* in_sizes, int n_in, void* d_out, int out_size) {
    (void)in_sizes; (void)n_in; (void)out_size;
    const __nv_bfloat16* x = (const __nv_bfloat16*)d_in[0];
    const int* src = (const int*)d_in[1];
    const int* dst = (const int*)d_in[2];
    const __nv_bfloat16* Y = (const __nv_bfloat16*)d_in[3];
    const __nv_bfloat16* ef = (const __nv_bfloat16*)d_in[4];
    const __nv_bfloat16* w_rad = (const __nv_bfloat16*)d_in[5];
    const __nv_bfloat16* cg = (const __nv_bfloat16*)d_in[6];
    const __nv_bfloat16* w_mix = (const __nv_bfloat16*)d_in[7];
    __nv_bfloat16* out = (__nv_bfloat16*)d_out;

    static int sms = 0;
    if (sms == 0) {
        int dev = 0;
        cudaGetDevice(&dev);
        cudaDeviceGetAttribute(&sms, cudaDevAttrMultiProcessorCount, dev);
        cudaFuncSetAttribute(tfn_kernel<3>, cudaFuncAttributeMaxDynamicSharedMemorySize, SM_TOTAL);
        cudaFuncSetAttribute(tfn_kernel<1>, cudaFuncAttributeMaxDynamicSharedMemorySize, SM_TOTAL);
        cudaFuncSetAttribute(tfn_kernel<2>, cudaFuncAttributeMaxDynamicSharedMemorySize, SM_TOTAL);
    }
    if (sms >= NB) {
        tfn_kernel<3><<<NB, NTHR, SM_TOTAL>>>(x, src, dst, Y, ef, w_rad, cg, w_mix, out);
    } else {
        tfn_kernel<1><<<NB, NTHR, SM_TOTAL>>>(x, src, dst, Y, ef, w_rad, cg, w_mix, out);
        tfn_kernel<2><<<NB, NTHR, SM_TOTAL>>>(x, src, dst, Y, ef, w_rad, cg, w_mix, out);
    }
}
```

```cpp
#include <cuda_runtime.h>
#include <cuda_bf16.h>
#include <stdint.h>

namespace {

constexpr int N_NODES = 10000;
constexpr int N_EDGES = 320000;
constexpr int NB      = 132;
constexpr int NPB     = 76;
constexpr int NSRC    = 128;
constexpr int EPC     = N_EDGES / NSRC;
constexpr int NTHR    = 512;
constexpr int NG      = 5;
constexpr int ROWP    = 2176;
constexpr int STAGE   = 4 * ROWP + 128;
constexpr int UCAP    = 104;
constexpr int REC     = 52;
constexpr int NBK     = 80;
constexpr int HS      = 81;

#define PACE_Q8 630
#define PACE_LEAD 300
#define PACE_HEAD 690
#define HEAD_BK 10
#define PACE_TAIL 595
#define TAIL_BK 68
#define IDLE_EST 700
#define POLL_DELAY 1280
#define LEAD_CLK 110
#define FB_GAIN 24
#define FB_DOWN 4
#define FB_MIN 0
#define START_NS 3680

constexpr int SM_RING  = 0;
constexpr int SM_W     = 4 * NG * STAGE;
constexpr int SM_REC   = SM_W + 32768;
constexpr int SM_MISC  = SM_REC + 4 * UCAP * REC;
constexpr int SM_TOTAL = SM_MISC + 224;
constexpr int SC_MAIL  = 1 * STAGE;
constexpr int SC_CNT   = 3 * STAGE + 4096;
constexpr int SC_DUMP  = 3 * STAGE + 3072;
constexpr int SC_XTRA  = 3 * STAGE + 2048;
constexpr int SC_HIST  = 4 * STAGE;
constexpr int SC_GPOS  = 6 * STAGE;
constexpr int SC_WR    = 7 * STAGE;
constexpr int GDUMMY   = 1024;
constexpr int AGGT     = (NG * STAGE + 1023) / 1024 * 1024;
static_assert(3 * AGGT + 20480 <= 4 * NG * STAGE, "agg tile inside the team's ring");
static_assert(4 * ROWP + 16 <= 10240 && STAGE + 4 * ROWP >= 3 * (AGGT - NG * STAGE) + 10240 && STAGE + 4 * ROWP + 16 <= 20480 &&
              2 * STAGE + 4 * ROWP >= 3 * (AGGT - NG * STAGE) + 20480, "half h of the tile covers the barriers of stage h only");
static_assert(NB * 144 <= 2 * STAGE + 2048 && (GDUMMY + 32) * 8 <= 4 * ROWP && 21 * HS <= 2048, "scratch");
static_assert(NPB * 512 * 4 <= 4 * NG * STAGE, "slow tile");
static_assert(SM_TOTAL <= 232448, "smem");
static_assert(SM_REC % 16 == 0 && (4 * UCAP * REC) % 16 == 0 && SM_MISC % 16 == 0, "align");
constexpr int MI_XN = 0;
constexpr int MI_TMAX = 2;
constexpr int MI_SHIFT = 48;
constexpr int MI_NU = 8;
constexpr int MI_END = 28;
constexpr int MI_GREF = 1;
constexpr int MI_T0 = 3;

__device__ __align__(128) uint4 g_mail[NB * NSRC * 8];
__device__ __align__(128) uint32_t g_mail2[NB * NSRC * 32];
__device__ __align__(128) int g_lag[2 * NB][32];
#define STAMP(k)

__device__ __forceinline__ uint32_t smem_u32(const void* p) { return (uint32_t)__cvta_generic_to_shared(p); }
__device__ __forceinline__ uint32_t atoms_inc(uint32_t a) {
    uint32_t r;
    asm volatile("atom.shared.add.u32 %0, [%1], 1;" : "=r"(r) : "r"(a) : "memory");
    return r;
}
__device__ __forceinline__ void sts32(uint32_t a, uint32_t v) { asm volatile("st.shared.u32 [%0], %1;" ::"r"(a), "r"(v) : "memory"); }
__device__ __forceinline__ void sts16(uint32_t a, uint32_t v) { asm volatile("st.shared.u16 [%0], %1;" ::"r"(a), "h"((uint16_t)v) : "memory"); }
__device__ __forceinline__ void sts8(uint32_t a, uint32_t v) { asm volatile("st.shared.u8 [%0], %1;" ::"r"(a), "r"(v) : "memory"); }
__device__ __forceinline__ uint32_t lds32(uint32_t a) { uint32_t v; asm volatile("ld.shared.u32 %0, [%1];" : "=r"(v) : "r"(a)); return v; }
__device__ __forceinline__ uint32_t lds16(uint32_t a) { uint32_t v; asm volatile("ld.shared.u16 %0, [%1];" : "=r"(v) : "r"(a)); return v; }
__device__ __forceinline__ void cp16(uint32_t d, const void* p) {
    asm volatile("cp.async.cg.shared.global [%0], [%1], 16;" ::"r"(d), "l"(p) : "memory");
}
__device__ __forceinline__ uint32_t gtime() {
    uint32_t t;
    asm volatile("mov.u32 %0, %%globaltimer_lo;" : "=r"(t));
    return t;
}
__device__ __forceinline__ void mbar_init(uint32_t bar, int cnt) {
    asm volatile("mbarrier.init.shared.b64 [%0], %1;" ::"r"(bar), "r"(cnt) : "memory");
}
__device__ __forceinline__ void mbar_inval(uint32_t bar) {
    asm volatile("mbarrier.inval.shared.b64 [%0];" ::"r"(bar) : "memory");
}
__device__ __forceinline__ uint4 lds128(uint32_t a) {
    uint4 v;
    asm volatile("ld.shared.v4.u32 {%0,%1,%2,%3}, [%4];" : "=r"(v.x), "=r"(v.y), "=r"(v.z), "=r"(v.w) : "r"(a));
    return v;
}
__device__ __forceinline__ void sts128(uint32_t a, uint32_t x, uint32_t y, uint32_t z, uint32_t w) {
    asm volatile("st.shared.v4.u32 [%0], {%1,%2,%3,%4};" ::"r"(a), "r"(x), "r"(y), "r"(z), "r"(w) : "memory");
}
__device__ __forceinline__ uint32_t pack_bf16(float lo, float hi) {
    uint32_t r;
    asm("cvt.rn.bf16x2.f32 %0, %1, %2;" : "=r"(r) : "f"(hi), "f"(lo));
    return r;
}
__device__ __forceinline__ uint32_t mul_lo(uint32_t v, uint32_t r) {
    __nv_bfloat162 a = *reinterpret_cast<__nv_bfloat162*>(&v), b = *reinterpret_cast<__nv_bfloat162*>(&r);
    __nv_bfloat162 c = __hmul2(a, __low2bfloat162(b));
    return *reinterpret_cast<uint32_t*>(&c);
}
__device__ __forceinline__ void wgmma_n80(float (&d)[40], const uint32_t (&a)[4], uint64_t desc, int scale_d) {
    asm volatile("{\n.reg .pred p;\nsetp.ne.b32 p, %45, 0;\n"
        "wgmma.mma_async.sync.aligned.m64n80k16.f32.bf16.bf16 "
        "{%0,%1,%2,%3,%4,%5,%6,%7,%8,%9,%10,%11,%12,%13,%14,%15,%16,%17,%18,%19,"
        "%20,%21,%22,%23,%24,%25,%26,%27,%28,%29,%30,%31,%32,%33,%34,%35,%36,%37,%38,%39}, "
        "{%40,%41,%42,%43}, %44, p, 1, 1, 0;\n}"
        : "+f"(d[0]), "+f"(d[1]), "+f"(d[2]), "+f"(d[3]), "+f"(d[4]), "+f"(d[5]), "+f"(d[6]), "+f"(d[7]),
          "+f"(d[8]), "+f"(d[9]), "+f"(d[10]), "+f"(d[11]), "+f"(d[12]), "+f"(d[13]), "+f"(d[14]), "+f"(d[15]),
          "+f"(d[16]), "+f"(d[17]), "+f"(d[18]), "+f"(d[19]), "+f"(d[20]), "+f"(d[21]), "+f"(d[22]), "+f"(d[23]),
          "+f"(d[24]), "+f"(d[25]), "+f"(d[26]), "+f"(d[27]), "+f"(d[28]), "+f"(d[29]), "+f"(d[30]), "+f"(d[31]),
          "+f"(d[32]), "+f"(d[33]), "+f"(d[34]), "+f"(d[35]), "+f"(d[36]), "+f"(d[37]), "+f"(d[38]), "+f"(d[39])
        : "r"(a[0]), "r"(a[1]), "r"(a[2]), "r"(a[3]), "l"(desc), "r"(scale_d));
}

__device__ __forceinline__ void producer_loop(const void* xl, const void* efl, const void* Y, uint32_t xd, uint32_t oef,
                                              uint32_t ysel, uint32_t ring, uint32_t rec, uint32_t rlast, uint32_t odd,
                                              uint32_t lag, uint32_t xh) {
    asm volatile(
        "{\n"
        ".reg .b32 w, em, ey, cu, d, t, u, n, sa, ph, rp, rend, rlast, dy, sv, lag, lv, w2, w3, w4;\n"
        ".reg .b16 tg;\n"
        ".reg .b64 pa, pb, pc, pd;\n"
        ".reg .pred lo, z, q, e, zb, fbk;\n"
        "redux.sync.or.b32 sa, %6, 0xffffffff;\n"
        "redux.sync.or.b32 rp, %7, 0xffffffff;\n"
        "redux.sync.or.b32 rlast, %8, 0xffffffff;\n"
        "redux.sync.or.b32 lag, %11, 0xffffffff;\n"
        "setp.eq.u32 fbk, %9, 0;\n"
        "add.u32 rend, sa, 44160;\n"
        "and.b32 t, %5, 1;\n"
        "setp.eq.u32 lo, t, 0;\n"
        "mov.u32 ph, 1;\n"
        "setp.ge.u32 q, %9, 4;\n"
        "@q bra.uni PODD_%=;\n"
        "add.u32 t, rp, %4;\n"
        "ld.shared.u32 em, [t+16];\n"
        "and.b32 t, em, 0x7ffffffc;\n"
        "mad.wide.u32 pa, t, 8, %1;\n"
        "add.u32 d, sa, %3;\n"
        "@lo cp.async.cg.shared.global.L2::128B [d+2048], [pa], 16;\n"
        "cp.async.mbarrier.arrive.noinc.shared.b64 [sa+8704];\n"
        "add.u32 rp, rp, 52;\n"
        "add.u32 sa, sa, 8832;\n"
        "PODD_%=:\n"
        "add.u32 rp, rp, 52;\n"
        "add.u32 sa, sa, 8832;\n"
        "shr.u32 t, %4, 1;\n"
        "and.b32 t, t, 4;\n"
        "add.u32 t, t, rp;\n"
        "ld.shared.u32 w, [t];\n"
        "ld.shared.u32 w2, [t+8];\n"
        "add.u32 t, rp, %4;\n"
        "ld.shared.u32 em, [t+16];\n"
        "ld.shared.u32 ey, [t+-36];\n"
        "ld.shared.u32 cu, [rp+48];\n"
        "ld.volatile.shared.u32 sv, [lag];\n"
        "setp.eq.u32 e, sa, sa;\n"
        "setp.lt.u32 q, rp, rlast;\n"
        "@!q bra.uni PF_%=;\n"
        "PL_%=:\n"
        "add.u32 cu, cu, sv;\n"
        "mov.u32 u, %%clock;\n"
        "shl.b32 u, u, 14;\n"
        "sub.u32 u, u, cu;\n"
        "setp.ge.and.s32 q, u, 0, e;\n"
        "@q bra.uni PGO_%=;\n"
        "mov.u32 n, 0;\n"
        "PW1_%=:\n"
        "@e bra.uni PW2_%=;\n"
        "mbarrier.try_wait.parity.shared.b64 e, [sa+8712], ph;\n"
        "add.u32 n, n, 1;\n"
        "setp.lt.u32 q, n, 4194304;\n"
        "@q bra.uni PW1_%=;\n"
        "trap;\n"
        "PW2_%=:\n"
        "mov.u32 u, %%clock;\n"
        "shl.b32 u, u, 14;\n"
        "sub.u32 u, u, cu;\n"
        "setp.lt.s32 q, u, 0;\n"
        "@q bra.uni PW2_%=;\n"
        "PGO_%=:\n"
        "st.volatile.shared.u32 [lag+24], u;\n"
        "and.b32 t, em, 0x7ffffffc;\n"
        "mad.wide.u32 pa, t, 8, %1;\n"
        "and.b32 t, w, 0xffff;\n"
        "mad.wide.u32 pc, t, 1024, %0;\n"
        "shr.u32 t, w, 16;\n"
        "mad.wide.u32 pd, t, 1024, %0;\n"
        "add.u32 d, sa, %3;\n"
        "@lo cp.async.cg.shared.global.L2::128B [d+2048], [pa], 16;\n"
        "xor.b32 t, ey, %5;\n"
        "and.b32 t, t, 0x80000003;\n"
        "setp.ne.u32 zb, t, 0;\n"
        "and.b32 t, ey, 0x7ffffffc;\n"
        "mad.wide.u32 pb, t, 2, %2;\n"
        "selp.u32 dy, 64, 8, lo;\n"
        "xor.b32 dy, dy, d;\n"
        "cp.async.ca.shared.global.L2::128B [dy+2048], [pb], 8, zb;\n"
        "add.u32 d, sa, %12;\n"
        "and.b32 t, w, 0xffff;\n"
        "setp.eq.u32 zb, t, 0xffff;\n"
        "cp.async.cg.shared.global [d+0], [pc+0], 16, zb;\n"
        "cp.async.cg.shared.global [d+256], [pc+256], 16, zb;\n"
        "cp.async.cg.shared.global [d+512], [pc+512], 16, zb;\n"
        "cp.async.cg.shared.global [d+768], [pc+768], 16, zb;\n"
        "setp.lt.s32 zb, w, 0;\n"
        "cp.async.cg.shared.global [d+1024], [pd+0], 16, zb;\n"
        "cp.async.cg.shared.global [d+1280], [pd+256], 16, zb;\n"
        "cp.async.cg.shared.global [d+1536], [pd+512], 16, zb;\n"
        "cp.async.cg.shared.global [d+1792], [pd+768], 16, zb;\n"
        "xor.b32 dy, d, 64;\n"
        "and.b32 t, w2, 0xffff;\n"
        "mad.wide.u32 pa, t, 1024, %0;\n"
        "and.b32 t, w2, 0xffff;\n"
        "setp.eq.u32 zb, t, 0xffff;\n"
        "cp.async.cg.shared.global [dy+4352], [pa+0], 16, zb;\n"
        "cp.async.cg.shared.global [dy+4608], [pa+256], 16, zb;\n"
        "cp.async.cg.shared.global [dy+4864], [pa+512], 16, zb;\n"
        "cp.async.cg.shared.global [dy+5120], [pa+768], 16, zb;\n"
        "shr.u32 t, w2, 16;\n"
        "mad.wide.u32 pb, t, 1024, %0;\n"
        "setp.lt.s32 zb, w2, 0;\n"
        "cp.async.cg.shared.global [dy+5376], [pb+0], 16, zb;\n"
        "cp.async.cg.shared.global [dy+5632], [pb+256], 16, zb;\n"
        "cp.async.cg.shared.global [dy+5888], [pb+512], 16, zb;\n"
        "cp.async.cg.shared.global [dy+6144], [pb+768], 16, zb;\n"
        "add.u32 rp, rp, 104;\n"
        "shr.u32 t, %4, 1;\n"
        "and.b32 t, t, 4;\n"
        "add.u32 t, t, rp;\n"
        "ld.shared.u32 w, [t];\n"
        "ld.shared.u32 w2, [t+8];\n"
        "add.u32 t, rp, %4;\n"
        "ld.shared.u32 em, [t+16];\n"
        "ld.shared.u32 ey, [t+-36];\n"
        "ld.shared.u32 cu, [rp+48];\n"
        "ld.volatile.shared.u32 sv, [lag];\n"
        "cp.async.mbarrier.arrive.noinc.shared.b64 [sa+8704];\n"
        "add.u32 sa, sa, 17664;\n"
        "sub.u32 t, sa, 44160;\n"
        "setp.ge.u32 q, sa, rend;\n"
        "selp.u32 sa, t, sa, q;\n"
        "selp.u32 t, 1, 0, q;\n"
        "xor.b32 ph, ph, t;\n"
        "mbarrier.test_wait.parity.shared.b64 e, [sa+8712], ph;\n"
        "@!fbk bra.uni PC_%=;\n"
        "ld.volatile.shared.u32 u, [lag+24];\n"
        "shr.s32 u, u, 16;\n"
        "ld.volatile.shared.u64 pa, [lag+16];\n"
        "elect.sync _|z, 0xffffffff;\n"
        "@z st.relaxed.gpu.global.u32 [pa], u;\n"
        "@z cp.async.cg.shared.global [lag], [pa+16896], 16;\n"
        "PC_%=:\n"
        "setp.lt.u32 q, rp, rlast;\n"
        "@q bra.uni PL_%=;\n"
        "PF_%=:\n"
        "setp.ne.u32 q, rp, rlast;\n"
        "@q bra.uni PX_%=;\n"
        "mov.u32 n, 0;\n"
        "PE1_%=:\n"
        "@e bra.uni PE2_%=;\n"
        "mbarrier.try_wait.parity.shared.b64 e, [sa+8712], ph;\n"
        "add.u32 n, n, 1;\n"
        "setp.lt.u32 q, n, 4194304;\n"
        "@q bra.uni PE1_%=;\n"
        "trap;\n"
        "PE2_%=:\n"
        "cp.async.mbarrier.arrive.noinc.shared.b64 [sa+8704];\n"
        "PX_%=:\n"
        "}\n"
        ::"l"(xl), "l"(efl), "l"(Y), "r"(xd), "r"(oef), "r"(ysel), "r"(ring), "r"(rec), "r"(rlast), "r"(odd),
          "n"(0), "r"(lag), "r"(xh) : "memory");
}

__device__ __forceinline__ void consumer_loop(float (&acc)[5][4][2][4], const uint32_t (&wf)[4][4], const uint32_t (&cgf)[4],
                                              uint32_t xoff, uint32_t& ring, uint32_t moff, uint32_t rec) {
    asm volatile(
        "{\n"
        ".reg .b32 x<16>, a<4>, b<4>, r<4>, m<4>, rl, rh, tag, la, lb, sa, last, ph, tq, xa, ma, n, ring, sn, ln, yb, zz, k<4>, tp, s<4>;\n"
        ".reg .b16 lo, hi;\n"
        ".reg .f32 p<16>, d<4>, t0, t1, fz;\n"
        ".reg .pred q, w, el, c<5>;\n"
        "TA_%=: .branchtargets A0_%=, A1_%=, A2_%=, A3_%=, A4_%=, EXIT_%=;\n"
        "TB_%=: .branchtargets B0_%=, B1_%=, B2_%=, B3_%=, B4_%=, SPIN_%=;\n"
        "mov.f32 fz, 0f00000000;\n"
        "redux.sync.or.b32 ring, %160, 0xffffffff;\n"
        "mov.u32 sa, ring;\n"
        "add.u32 last, ring, 35328;\n"
        "mov.u32 ph, 0;\n"
        "redux.sync.xor.b32 zz, %160, 0xffffffff;\n"
        "redux.sync.or.b32 tp, %183, 0xffffffff;\n"
        "elect.sync _|el, 0xffffffff;\n"
        "mov.u32 k0, sa;\n"
        "mov.u32 k1, sa;\n"
        "mov.u32 k2, sa;\n"
        "mov.u32 k3, sa;\n"
        "mov.b32 x0, 0;\n"
        "mov.b32 x1, 0;\n"
        "mov.b32 x2, 0;\n"
        "mov.b32 x3, 0;\n"
        "mov.b32 x4, 0;\n"
        "mov.b32 x5, 0;\n"
        "mov.b32 x6, 0;\n"
        "mov.b32 x7, 0;\n"
        "mov.b32 x8, 0;\n"
        "mov.b32 x9, 0;\n"
        "mov.b32 x10, 0;\n"
        "mov.b32 x11, 0;\n"
        "mov.b32 x12, 0;\n"
        "mov.b32 x13, 0;\n"
        "mov.b32 x14, 0;\n"
        "mov.b32 x15, 0;\n"
        "mov.b32 b0, 0;\n"
        "mov.b32 r0, 0;\n"
        "mov.b32 b1, 0;\n"
        "mov.b32 r1, 0;\n"
        "mov.b32 b2, 0;\n"
        "mov.b32 r2, 0;\n"
        "mov.b32 b3, 0;\n"
        "mov.b32 r3, 0;\n"
        "mov.u32 lb, 0;\n"
        "mov.u32 n, 0;\n"
        "W0_%=:\n"
        "mbarrier.try_wait.parity.shared.b64 w, [sa+8704], 0;\n"
        "@w bra.uni W0D_%=;\n"
        "add.u32 n, n, 1;\n"
        "setp.lt.u32 q, n, 4194304;\n"
        "@q bra.uni W0_%=;\n"
        "trap;\n"
        "W0D_%=:\n"
        "add.u32 ma, sa, %182;\n"
        "ldmatrix.sync.aligned.m8n8.x4.shared.b16 {m0,m1,m2,m3}, [ma];\n"
        "ld.shared.u16 tag, [tp+48];\n"
        "add.u32 tp, tp, 52;\n"
        "add.u32 sn, sa, 8832;\n"
        "setp.eq.u32 q, sa, last;\n"
        "selp.u32 sn, ring, sn, q;\n"
        "selp.u32 tq, 1, 0, q;\n"
        "xor.b32 ph, ph, tq;\n"
        "mbarrier.test_wait.parity.shared.b64 w, [sn+8704], ph;\n"
        "mma.sync.aligned.m16n8k16.row.col.f32.bf16.bf16.f32 {p0,p1,p2,p3}, {%161,%162,%163,%164}, {m2,m3}, {fz,fz,fz,fz};\n"
        "mma.sync.aligned.m16n8k16.row.col.f32.bf16.bf16.f32 {p4,p5,p6,p7}, {%165,%166,%167,%168}, {m2,m3}, {fz,fz,fz,fz};\n"
        "mma.sync.aligned.m16n8k16.row.col.f32.bf16.bf16.f32 {p8,p9,p10,p11}, {%169,%170,%171,%172}, {m2,m3}, {fz,fz,fz,fz};\n"
        "mma.sync.aligned.m16n8k16.row.col.f32.bf16.bf16.f32 {p12,p13,p14,p15}, {%173,%174,%175,%176}, {m2,m3}, {fz,fz,fz,fz};\n"
        "@el mbarrier.arrive.shared.b64 _, [k0+8712];\n"
        "redux.sync.or.b32 ln, tag, 0xffffffff;\n"
        "mov.u32 sa, sn;\n"
        "add.u32 k0, sn, zz;\n"
        "SPIN_%=:\n"
        "mov.u32 n, 0;\n"
        "SP1_%=:\n"
        "mbarrier.try_wait.parity.shared.b64 w, [sa+8704], ph;\n"
        "@w bra.uni SP2_%=;\n"
        "add.u32 n, n, 1;\n"
        "setp.lt.u32 q, n, 4194304;\n"
        "@q bra.uni SP1_%=;\n"
        "trap;\n"
        "SP2_%=:\n"
        "brx.idx.uni lb, TB_%=;\n"
        "A0_%=:\n"
        "add.u32 xa, sa, %181;\n"
        "add.u32 ma, sa, %182;\n"
        "ldmatrix.sync.aligned.m8n8.x4.shared.b16 {m0,m1,m2,m3}, [ma];\n"
        "ld.shared.u16 tag, [tp+48];\n"
        "add.u32 tp, tp, 52;\n"
        "add.u32 sn, sa, 8832;\n"
        "setp.eq.u32 q, sa, last;\n"
        "selp.u32 sn, ring, sn, q;\n"
        "selp.u32 tq, 1, 0, q;\n"
        "xor.b32 ph, ph, tq;\n"
        "mbarrier.test_wait.parity.shared.b64 w, [sn+8704], ph;\n"
        "mma.sync.aligned.m16n8k16.row.col.f32.bf16.bf16.f32 {%0,%1,%2,%3}, {a0,a1,a2,a3}, {x0,x1}, {%0,%1,%2,%3};\n"
        "mma.sync.aligned.m16n8k16.row.col.f32.bf16.bf16.f32 {%4,%5,%6,%7}, {a0,a1,a2,a3}, {x2,x3}, {%4,%5,%6,%7};\n"
        "ld.shared.v4.u32 {x0,x1,x2,x3}, [xa+1024];\n"
        "tanh.approx.f32 t0, p1;\n"
        "tanh.approx.f32 t1, p3;\n"
        "fma.rn.f32 t0, p1, t0, p1;\n"
        "fma.rn.f32 t1, p3, t1, p3;\n"
        "cvt.rn.bf16x2.f32 r0, t1, t0;\n"
        "mma.sync.aligned.m16n8k16.row.col.f32.bf16.bf16.f32 {p0,p1,p2,p3}, {%161,%162,%163,%164}, {m2,m3}, {fz,fz,fz,fz};\n"
        "mma.sync.aligned.m16n8k16.row.col.f32.bf16.bf16.f32 {%8,%9,%10,%11}, {a0,a1,a2,a3}, {x4,x5}, {%8,%9,%10,%11};\n"
        "mma.sync.aligned.m16n8k16.row.col.f32.bf16.bf16.f32 {%12,%13,%14,%15}, {a0,a1,a2,a3}, {x6,x7}, {%12,%13,%14,%15};\n"
        "ld.shared.v4.u32 {x4,x5,x6,x7}, [xa+1152];\n"
        "mma.sync.aligned.m16n8k8.row.col.f32.bf16.bf16.f32 {d0,d1,d2,d3}, {%177,%178}, {m1}, {fz,fz,fz,fz};\n"
        "cvt.rn.bf16x2.f32 b0, d2, d0;\n"
        "cvt.rn.bf16x2.f32 b1, d3, d1;\n"
        "tanh.approx.f32 t0, p5;\n"
        "tanh.approx.f32 t1, p7;\n"
        "fma.rn.f32 t0, p5, t0, p5;\n"
        "fma.rn.f32 t1, p7, t1, p7;\n"
        "cvt.rn.bf16x2.f32 r1, t1, t0;\n"
        "mma.sync.aligned.m16n8k16.row.col.f32.bf16.bf16.f32 {p4,p5,p6,p7}, {%165,%166,%167,%168}, {m2,m3}, {fz,fz,fz,fz};\n"
        "mov.b32 {lo,hi}, r2;\n"
        "mov.b32 rl, {lo,lo};\n"
        "mov.b32 rh, {hi,hi};\n"
        "mul.bf16x2 x8, x8, rl;\n"
        "mul.bf16x2 x9, x9, rl;\n"
        "mul.bf16x2 x10, x10, rh;\n"
        "mul.bf16x2 x11, x11, rh;\n"
        "mma.sync.aligned.m16n8k16.row.col.f32.bf16.bf16.f32 {%16,%17,%18,%19}, {a0,a1,a2,a3}, {x8,x9}, {%16,%17,%18,%19};\n"
        "mma.sync.aligned.m16n8k16.row.col.f32.bf16.bf16.f32 {%20,%21,%22,%23}, {a0,a1,a2,a3}, {x10,x11}, {%20,%21,%22,%23};\n"
        "ld.shared.v4.u32 {x8,x9,x10,x11}, [xa+1280];\n"
        "mma.sync.aligned.m16n8k8.row.col.f32.bf16.bf16.f32 {d0,d1,d2,d3}, {%179,%180}, {m1}, {fz,fz,fz,fz};\n"
        "cvt.rn.bf16x2.f32 b2, d2, d0;\n"
        "cvt.rn.bf16x2.f32 b3, d3, d1;\n"
        "tanh.approx.f32 t0, p9;\n"
        "tanh.approx.f32 t1, p11;\n"
        "fma.rn.f32 t0, p9, t0, p9;\n"
        "fma.rn.f32 t1, p11, t1, p11;\n"
        "cvt.rn.bf16x2.f32 r2, t1, t0;\n"
        "mma.sync.aligned.m16n8k16.row.col.f32.bf16.bf16.f32 {p8,p9,p10,p11}, {%169,%170,%171,%172}, {m2,m3}, {fz,fz,fz,fz};\n"
        "mov.b32 {lo,hi}, r3;\n"
        "mov.b32 rl, {lo,lo};\n"
        "mov.b32 rh, {hi,hi};\n"
        "mul.bf16x2 x12, x12, rl;\n"
        "mul.bf16x2 x13, x13, rl;\n"
        "mul.bf16x2 x14, x14, rh;\n"
        "mul.bf16x2 x15, x15, rh;\n"
        "mma.sync.aligned.m16n8k16.row.col.f32.bf16.bf16.f32 {%24,%25,%26,%27}, {a0,a1,a2,a3}, {x12,x13}, {%24,%25,%26,%27};\n"
        "mma.sync.aligned.m16n8k16.row.col.f32.bf16.bf16.f32 {%28,%29,%30,%31}, {a0,a1,a2,a3}, {x14,x15}, {%28,%29,%30,%31};\n"
        "ld.shared.v4.u32 {x12,x13,x14,x15}, [xa+1408];\n"
        "@el mbarrier.arrive.shared.b64 _, [k0+8712];\n"
        "redux.sync.or.b32 ln, tag, 0xffffffff;\n"
        "mov.u32 sa, sn;\n"
        "add.u32 k0, sn, zz;\n"
        "tanh.approx.f32 t0, p13;\n"
        "tanh.approx.f32 t1, p15;\n"
        "fma.rn.f32 t0, p13, t0, p13;\n"
        "fma.rn.f32 t1, p15, t1, p15;\n"
        "cvt.rn.bf16x2.f32 r3, t1, t0;\n"
        "mma.sync.aligned.m16n8k16.row.col.f32.bf16.bf16.f32 {p12,p13,p14,p15}, {%173,%174,%175,%176}, {m2,m3}, {fz,fz,fz,fz};\n"
        "selp.u32 tq, lb, 5, w;\n"
        "brx.idx.uni tq, TB_%=;\n"
        "A1_%=:\n"
        "add.u32 xa, sa, %181;\n"
        "add.u32 ma, sa, %182;\n"
        "ldmatrix.sync.aligned.m8n8.x4.shared.b16 {m0,m1,m2,m3}, [ma];\n"
        "ld.shared.u16 tag, [tp+48];\n"
        "add.u32 tp, tp, 52;\n"
        "add.u32 sn, sa, 8832;\n"
        "setp.eq.u32 q, sa, last;\n"
        "selp.u32 sn, ring, sn, q;\n"
        "selp.u32 tq, 1, 0, q;\n"
        "xor.b32 ph, ph, tq;\n"
        "mbarrier.test_wait.parity.shared.b64 w, [sn+8704], ph;\n"
        "mma.sync.aligned.m16n8k16.row.col.f32.bf16.bf16.f32 {%32,%33,%34,%35}, {a0,a1,a2,a3}, {x0,x1}, {%32,%33,%34,%35};\n"
        "mma.sync.aligned.m16n8k16.row.col.f32.bf16.bf16.f32 {%36,%37,%38,%39}, {a0,a1,a2,a3}, {x2,x3}, {%36,%37,%38,%39};\n"
        "ld.shared.v4.u32 {x0,x1,x2,x3}, [xa+1024];\n"
        "tanh.approx.f32 t0, p1;\n"
        "tanh.approx.f32 t1, p3;\n"
        "fma.rn.f32 t0, p1, t0, p1;\n"
        "fma.rn.f32 t1, p3, t1, p3;\n"
        "cvt.rn.bf16x2.f32 r0, t1, t0;\n"
        "mma.sync.aligned.m16n8k16.row.col.f32.bf16.bf16.f32 {p0,p1,p2,p3}, {%161,%162,%163,%164}, {m2,m3}, {fz,fz,fz,fz};\n"
        "mma.sync.aligned.m16n8k16.row.col.f32.bf16.bf16.f32 {%40,%41,%42,%43}, {a0,a1,a2,a3}, {x4,x5}, {%40,%41,%42,%43};\n"
        "mma.sync.aligned.m16n8k16.row.col.f32.bf16.bf16.f32 {%44,%45,%46,%47}, {a0,a1,a2,a3}, {x6,x7}, {%44,%45,%46,%47};\n"
        "ld.shared.v4.u32 {x4,x5,x6,x7}, [xa+1152];\n"
        "mma.sync.aligned.m16n8k8.row.col.f32.bf16.bf16.f32 {d0,d1,d2,d3}, {%177,%178}, {m1}, {fz,fz,fz,fz};\n"
        "cvt.rn.bf16x2.f32 b0, d2, d0;\n"
        "cvt.rn.bf16x2.f32 b1, d3, d1;\n"
        "tanh.approx.f32 t0, p5;\n"
        "tanh.approx.f32 t1, p7;\n"
        "fma.rn.f32 t0, p5, t0, p5;\n"
        "fma.rn.f32 t1, p7, t1, p7;\n"
        "cvt.rn.bf16x2.f32 r1, t1, t0;\n"
        "mma.sync.aligned.m16n8k16.row.col.f32.bf16.bf16.f32 {p4,p5,p6,p7}, {%165,%166,%167,%168}, {m2,m3}, {fz,fz,fz,fz};\n"
        "mov.b32 {lo,hi}, r2;\n"
        "mov.b32 rl, {lo,lo};\n"
        "mov.b32 rh, {hi,hi};\n"
        "mul.bf16x2 x8, x8, rl;\n"
        "mul.bf16x2 x9, x9, rl;\n"
        "mul.bf16x2 x10, x10, rh;\n"
        "mul.bf16x2 x11, x11, rh;\n"
        "mma.sync.aligned.m16n8k16.row.col.f32.bf16.bf16.f32 {%48,%49,%50,%51}, {a0,a1,a2,a3}, {x8,x9}, {%48,%49,%50,%51};\n"
        "mma.sync.aligned.m16n8k16.row.col.f32.bf16.bf16.f32 {%52,%53,%54,%55}, {a0,a1,a2,a3}, {x10,x11}, {%52,%53,%54,%55};\n"
        "ld.shared.v4.u32 {x8,x9,x10,x11}, [xa+1280];\n"
        "mma.sync.aligned.m16n8k8.row.col.f32.bf16.bf16.f32 {d0,d1,d2,d3}, {%179,%180}, {m1}, {fz,fz,fz,fz};\n"
        "cvt.rn.bf16x2.f32 b2, d2, d0;\n"
        "cvt.rn.bf16x2.f32 b3, d3, d1;\n"
        "tanh.approx.f32 t0, p9;\n"
        "tanh.approx.f32 t1, p11;\n"
        "fma.rn.f32 t0, p9, t0, p9;\n"
        "fma.rn.f32 t1, p11, t1, p11;\n"
        "cvt.rn.bf16x2.f32 r2, t1, t0;\n"
        "mma.sync.aligned.m16n8k16.row.col.f32.bf16.bf16.f32 {p8,p9,p10,p11}, {%169,%170,%171,%172}, {m2,m3}, {fz,fz,fz,fz};\n"
        "mov.b32 {lo,hi}, r3;\n"
        "mov.b32 rl, {lo,lo};\n"
        "mov.b32 rh, {hi,hi};\n"
        "mul.bf16x2 x12, x12, rl;\n"
        "mul.bf16x2 x13, x13, rl;\n"
        "mul.bf16x2 x14, x14, rh;\n"
        "mul.bf16x2 x15, x15, rh;\n"
        "mma.sync.aligned.m16n8k16.row.col.f32.bf16.bf16.f32 {%56,%57,%58,%59}, {a0,a1,a2,a3}, {x12,x13}, {%56,%57,%58,%59};\n"
        "mma.sync.aligned.m16n8k16.row.col.f32.bf16.bf16.f32 {%60,%61,%62,%63}, {a0,a1,a2,a3}, {x14,x15}, {%60,%61,%62,%63};\n"
        "ld.shared.v4.u32 {x12,x13,x14,x15}, [xa+1408];\n"
        "@el mbarrier.arrive.shared.b64 _, [k0+8712];\n"
        "redux.sync.or.b32 ln, tag, 0xffffffff;\n"
        "mov.u32 sa, sn;\n"
        "add.u32 k0, sn, zz;\n"
        "tanh.approx.f32 t0, p13;\n"
        "tanh.approx.f32 t1, p15;\n"
        "fma.rn.f32 t0, p13, t0, p13;\n"
        "fma.rn.f32 t1, p15, t1, p15;\n"
        "cvt.rn.bf16x2.f32 r3, t1, t0;\n"
        "mma.sync.aligned.m16n8k16.row.col.f32.bf16.bf16.f32 {p12,p13,p14,p15}, {%173,%174,%175,%176}, {m2,m3}, {fz,fz,fz,fz};\n"
        "selp.u32 tq, lb, 5, w;\n"
        "brx.idx.uni tq, TB_%=;\n"
        "A2_%=:\n"
        "add.u32 xa, sa, %181;\n"
        "add.u32 ma, sa, %182;\n"
        "ldmatrix.sync.aligned.m8n8.x4.shared.b16 {m0,m1,m2,m3}, [ma];\n"
        "ld.shared.u16 tag, [tp+48];\n"
        "add.u32 tp, tp, 52;\n"
        "add.u32 sn, sa, 8832;\n"
        "setp.eq.u32 q, sa, last;\n"
        "selp.u32 sn, ring, sn, q;\n"
        "selp.u32 tq, 1, 0, q;\n"
        "xor.b32 ph, ph, tq;\n"
        "mbarrier.test_wait.parity.shared.b64 w, [sn+8704], ph;\n"
        "mma.sync.aligned.m16n8k16.row.col.f32.bf16.bf16.f32 {%64,%65,%66,%67}, {a0,a1,a2,a3}, {x0,x1}, {%64,%65,%66,%67};\n"
        "mma.sync.aligned.m16n8k16.row.col.f32.bf16.bf16.f32 {%68,%69,%70,%71}, {a0,a1,a2,a3}, {x2,x3}, {%68,%69,%70,%71};\n"
        "ld.shared.v4.u32 {x0,x1,x2,x3}, [xa+1024];\n"
        "tanh.approx.f32 t0, p1;\n"
        "tanh.approx.f32 t1, p3;\n"
        "fma.rn.f32 t0, p1, t0, p1;\n"
        "fma.rn.f32 t1, p3, t1, p3;\n"
        "cvt.rn.bf16x2.f32 r0, t1, t0;\n"
        "mma.sync.aligned.m16n8k16.row.col.f32.bf16.bf16.f32 {p0,p1,p2,p3}, {%161,%162,%163,%164}, {m2,m3}, {fz,fz,fz,fz};\n"
        "mma.sync.aligned.m16n8k16.row.col.f32.bf16.bf16.f32 {%72,%73,%74,%75}, {a0,a1,a2,a3}, {x4,x5}, {%72,%73,%74,%75};\n"
        "mma.sync.aligned.m16n8k16.row.col.f32.bf16.bf16.f32 {%76,%77,%78,%79}, {a0,a1,a2,a3}, {x6,x7}, {%76,%77,%78,%79};\n"
        "ld.shared.v4.u32 {x4,x5,x6,x7}, [xa+1152];\n"
        "mma.sync.aligned.m16n8k8.row.col.f32.bf16.bf16.f32 {d0,d1,d2,d3}, {%177,%178}, {m1}, {fz,fz,fz,fz};\n"
        "cvt.rn.bf16x2.f32 b0, d2, d0;\n"
        "cvt.rn.bf16x2.f32 b1, d3, d1;\n"
        "tanh.approx.f32 t0, p5;\n"
        "tanh.approx.f32 t1, p7;\n"
        "fma.rn.f32 t0, p5, t0, p5;\n"
        "fma.rn.f32 t1, p7, t1, p7;\n"
        "cvt.rn.bf16x2.f32 r1, t1, t0;\n"
        "mma.sync.aligned.m16n8k16.row.col.f32.bf16.bf16.f32 {p4,p5,p6,p7}, {%165,%166,%167,%168}, {m2,m3}, {fz,fz,fz,fz};\n"
        "mov.b32 {lo,hi}, r2;\n"
        "mov.b32 rl, {lo,lo};\n"
        "mov.b32 rh, {hi,hi};\n"
        "mul.bf16x2 x8, x8, rl;\n"
        "mul.bf16x2 x9, x9, rl;\n"
        "mul.bf16x2 x10, x10, rh;\n"
        "mul.bf16x2 x11, x11, rh;\n"
        "mma.sync.aligned.m16n8k16.row.col.f32.bf16.bf16.f32 {%80,%81,%82,%83}, {a0,a1,a2,a3}, {x8,x9}, {%80,%81,%82,%83};\n"
        "mma.sync.aligned.m16n8k16.row.col.f32.bf16.bf16.f32 {%84,%85,%86,%87}, {a0,a1,a2,a3}, {x10,x11}, {%84,%85,%86,%87};\n"
        "ld.shared.v4.u32 {x8,x9,x10,x11}, [xa+1280];\n"
        "mma.sync.aligned.m16n8k8.row.col.f32.bf16.bf16.f32 {d0,d1,d2,d3}, {%179,%180}, {m1}, {fz,fz,fz,fz};\n"
        "cvt.rn.bf16x2.f32 b2, d2, d0;\n"
        "cvt.rn.bf16x2.f32 b3, d3, d1;\n"
        "tanh.approx.f32 t0, p9;\n"
        "tanh.approx.f32 t1, p11;\n"
        "fma.rn.f32 t0, p9, t0, p9;\n"
        "fma.rn.f32 t1, p11, t1, p11;\n"
        "cvt.rn.bf16x2.f32 r2, t1, t0;\n"
        "mma.sync.aligned.m16n8k16.row.col.f32.bf16.bf16.f32 {p8,p9,p10,p11}, {%169,%170,%171,%172}, {m2,m3}, {fz,fz,fz,fz};\n"
        "mov.b32 {lo,hi}, r3;\n"
        "mov.b32 rl, {lo,lo};\n"
        "mov.b32 rh, {hi,hi};\n"
        "mul.bf16x2 x12, x12, rl;\n"
        "mul.bf16x2 x13, x13, rl;\n"
        "mul.bf16x2 x14, x14, rh;\n"
        "mul.bf16x2 x15, x15, rh;\n"
        "mma.sync.aligned.m16n8k16.row.col.f32.bf16.bf16.f32 {%88,%89,%90,%91}, {a0,a1,a2,a3}, {x12,x13}, {%88,%89,%90,%91};\n"
        "mma.sync.aligned.m16n8k16.row.col.f32.bf16.bf16.f32 {%92,%93,%94,%95}, {a0,a1,a2,a3}, {x14,x15}, {%92,%93,%94,%95};\n"
        "ld.shared.v4.u32 {x12,x13,x14,x15}, [xa+1408];\n"
        "@el mbarrier.arrive.shared.b64 _, [k0+8712];\n"
        "redux.sync.or.b32 ln, tag, 0xffffffff;\n"
        "mov.u32 sa, sn;\n"
        "add.u32 k0, sn, zz;\n"
        "tanh.approx.f32 t0, p13;\n"
        "tanh.approx.f32 t1, p15;\n"
        "fma.rn.f32 t0, p13, t0, p13;\n"
        "fma.rn.f32 t1, p15, t1, p15;\n"
        "cvt.rn.bf16x2.f32 r3, t1, t0;\n"
        "mma.sync.aligned.m16n8k16.row.col.f32.bf16.bf16.f32 {p12,p13,p14,p15}, {%173,%174,%175,%176}, {m2,m3}, {fz,fz,fz,fz};\n"
        "selp.u32 tq, lb, 5, w;\n"
        "brx.idx.uni tq, TB_%=;\n"
        "A3_%=:\n"
        "add.u32 xa, sa, %181;\n"
        "add.u32 ma, sa, %182;\n"
        "ldmatrix.sync.aligned.m8n8.x4.shared.b16 {m0,m1,m2,m3}, [ma];\n"
        "ld.shared.u16 tag, [tp+48];\n"
        "add.u32 tp, tp, 52;\n"
        "add.u32 sn, sa, 8832;\n"
        "setp.eq.u32 q, sa, last;\n"
        "selp.u32 sn, ring, sn, q;\n"
        "selp.u32 tq, 1, 0, q;\n"
        "xor.b32 ph, ph, tq;\n"
        "mbarrier.test_wait.parity.shared.b64 w, [sn+8704], ph;\n"
        "mma.sync.aligned.m16n8k16.row.col.f32.bf16.bf16.f32 {%96,%97,%98,%99}, {a0,a1,a2,a3}, {x0,x1}, {%96,%97,%98,%99};\n"
        "mma.sync.aligned.m16n8k16.row.col.f32.bf16.bf16.f32 {%100,%101,%102,%103}, {a0,a1,a2,a3}, {x2,x3}, {%100,%101,%102,%103};\n"
        "ld.shared.v4.u32 {x0,x1,x2,x3}, [xa+1024];\n"
        "tanh.approx.f32 t0, p1;\n"
        "tanh.approx.f32 t1, p3;\n"
        "fma.rn.f32 t0, p1, t0, p1;\n"
        "fma.rn.f32 t1, p3, t1, p3;\n"
        "cvt.rn.bf16x2.f32 r0, t1, t0;\n"
        "mma.sync.aligned.m16n8k16.row.col.f32.bf16.bf16.f32 {p0,p1,p2,p3}, {%161,%162,%163,%164}, {m2,m3}, {fz,fz,fz,fz};\n"
        "mma.sync.aligned.m16n8k16.row.col.f32.bf16.bf16.f32 {%104,%105,%106,%107}, {a0,a1,a2,a3}, {x4,x5}, {%104,%105,%106,%107};\n"
        "mma.sync.aligned.m16n8k16.row.col.f32.bf16.bf16.f32 {%108,%109,%110,%111}, {a0,a1,a2,a3}, {x6,x7}, {%108,%109,%110,%111};\n"
        "ld.shared.v4.u32 {x4,x5,x6,x7}, [xa+1152];\n"
        "mma.sync.aligned.m16n8k8.row.col.f32.bf16.bf16.f32 {d0,d1,d2,d3}, {%177,%178}, {m1}, {fz,fz,fz,fz};\n"
        "cvt.rn.bf16x2.f32 b0, d2, d0;\n"
        "cvt.rn.bf16x2.f32 b1, d3, d1;\n"
        "tanh.approx.f32 t0, p5;\n"
        "tanh.approx.f32 t1, p7;\n"
        "fma.rn.f32 t0, p5, t0, p5;\n"
        "fma.rn.f32 t1, p7, t1, p7;\n"
        "cvt.rn.bf16x2.f32 r1, t1, t0;\n"
        "mma.sync.aligned.m16n8k16.row.col.f32.bf16.bf16.f32 {p4,p5,p6,p7}, {%165,%166,%167,%168}, {m2,m3}, {fz,fz,fz,fz};\n"
        "mov.b32 {lo,hi}, r2;\n"
        "mov.b32 rl, {lo,lo};\n"
        "mov.b32 rh, {hi,hi};\n"
        "mul.bf16x2 x8, x8, rl;\n"
        "mul.bf16x2 x9, x9, rl;\n"
        "mul.bf16x2 x10, x10, rh;\n"
        "mul.bf16x2 x11, x11, rh;\n"
        "mma.sync.aligned.m16n8k16.row.col.f32.bf16.bf16.f32 {%112,%113,%114,%115}, {a0,a1,a2,a3}, {x8,x9}, {%112,%113,%114,%115};\n"
        "mma.sync.aligned.m16n8k16.row.col.f32.bf16.bf16.f32 {%116,%117,%118,%119}, {a0,a1,a2,a3}, {x10,x11}, {%116,%117,%118,%119};\n"
        "ld.shared.v4.u32 {x8,x9,x10,x11}, [xa+1280];\n"
        "mma.sync.aligned.m16n8k8.row.col.f32.bf16.bf16.f32 {d0,d1,d2,d3}, {%179,%180}, {m1}, {fz,fz,fz,fz};\n"
        "cvt.rn.bf16x2.f32 b2, d2, d0;\n"
        "cvt.rn.bf16x2.f32 b3, d3, d1;\n"
        "tanh.approx.f32 t0, p9;\n"
        "tanh.approx.f32 t1, p11;\n"
        "fma.rn.f32 t0, p9, t0, p9;\n"
        "fma.rn.f32 t1, p11, t1, p11;\n"
        "cvt.rn.bf16x2.f32 r2, t1, t0;\n"
        "mma.sync.aligned.m16n8k16.row.col.f32.bf16.bf16.f32 {p8,p9,p10,p11}, {%169,%170,%171,%172}, {m2,m3}, {fz,fz,fz,fz};\n"
        "mov.b32 {lo,hi}, r3;\n"
        "mov.b32 rl, {lo,lo};\n"
        "mov.b32 rh, {hi,hi};\n"
        "mul.bf16x2 x12, x12, rl;\n"
        "mul.bf16x2 x13, x13, rl;\n"
        "mul.bf16x2 x14, x14, rh;\n"
        "mul.bf16x2 x15, x15, rh;\n"
        "mma.sync.aligned.m16n8k16.row.col.f32.bf16.bf16.f32 {%120,%121,%122,%123}, {a0,a1,a2,a3}, {x12,x13}, {%120,%121,%122,%123};\n"
        "mma.sync.aligned.m16n8k16.row.col.f32.bf16.bf16.f32 {%124,%125,%126,%127}, {a0,a1,a2,a3}, {x14,x15}, {%124,%125,%126,%127};\n"
        "ld.shared.v4.u32 {x12,x13,x14,x15}, [xa+1408];\n"
        "@el mbarrier.arrive.shared.b64 _, [k0+8712];\n"
        "redux.sync.or.b32 ln, tag, 0xffffffff;\n"
        "mov.u32 sa, sn;\n"
        "add.u32 k0, sn, zz;\n"
        "tanh.approx.f32 t0, p13;\n"
        "tanh.approx.f32 t1, p15;\n"
        "fma.rn.f32 t0, p13, t0, p13;\n"
        "fma.rn.f32 t1, p15, t1, p15;\n"
        "cvt.rn.bf16x2.f32 r3, t1, t0;\n"
        "mma.sync.aligned.m16n8k16.row.col.f32.bf16.bf16.f32 {p12,p13,p14,p15}, {%173,%174,%175,%176}, {m2,m3}, {fz,fz,fz,fz};\n"
        "selp.u32 tq, lb, 5, w;\n"
        "brx.idx.uni tq, TB_%=;\n"
        "A4_%=:\n"
        "add.u32 xa, sa, %181;\n"
        "add.u32 ma, sa, %182;\n"
        "ldmatrix.sync.aligned.m8n8.x4.shared.b16 {m0,m1,m2,m3}, [ma];\n"
        "ld.shared.u16 tag, [tp+48];\n"
        "add.u32 tp, tp, 52;\n"
        "add.u32 sn, sa, 8832;\n"
        "setp.eq.u32 q, sa, last;\n"
        "selp.u32 sn, ring, sn, q;\n"
        "selp.u32 tq, 1, 0, q;\n"
        "xor.b32 ph, ph, tq;\n"
        "mbarrier.test_wait.parity.shared.b64 w, [sn+8704], ph;\n"
        "mma.sync.aligned.m16n8k16.row.col.f32.bf16.bf16.f32 {%128,%129,%130,%131}, {a0,a1,a2,a3}, {x0,x1}, {%128,%129,%130,%131};\n"
        "mma.sync.aligned.m16n8k16.row.col.f32.bf16.bf16.f32 {%132,%133,%134,%135}, {a0,a1,a2,a3}, {x2,x3}, {%132,%133,%134,%135};\n"
        "ld.shared.v4.u32 {x0,x1,x2,x3}, [xa+1024];\n"
        "tanh.approx.f32 t0, p1;\n"
        "tanh.approx.f32 t1, p3;\n"
        "fma.rn.f32 t0, p1, t0, p1;\n"
        "fma.rn.f32 t1, p3, t1, p3;\n"
        "cvt.rn.bf16x2.f32 r0, t1, t0;\n"
        "mma.sync.aligned.m16n8k16.row.col.f32.bf16.bf16.f32 {p0,p1,p2,p3}, {%161,%162,%163,%164}, {m2,m3}, {fz,fz,fz,fz};\n"
        "mma.sync.aligned.m16n8k16.row.col.f32.bf16.bf16.f32 {%136,%137,%138,%139}, {a0,a1,a2,a3}, {x4,x5}, {%136,%137,%138,%139};\n"
        "mma.sync.aligned.m16n8k16.row.col.f32.bf16.bf16.f32 {%140,%141,%142,%143}, {a0,a1,a2,a3}, {x6,x7}, {%140,%141,%142,%143};\n"
        "ld.shared.v4.u32 {x4,x5,x6,x7}, [xa+1152];\n"
        "mma.sync.aligned.m16n8k8.row.col.f32.bf16.bf16.f32 {d0,d1,d2,d3}, {%177,%178}, {m1}, {fz,fz,fz,fz};\n"
        "cvt.rn.bf16x2.f32 b0, d2, d0;\n"
        "cvt.rn.bf16x2.f32 b1, d3, d1;\n"
        "tanh.approx.f32 t0, p5;\n"
        "tanh.approx.f32 t1, p7;\n"
        "fma.rn.f32 t0, p5, t0, p5;\n"
        "fma.rn.f32 t1, p7, t1, p7;\n"
        "cvt.rn.bf16x2.f32 r1, t1, t0;\n"
        "mma.sync.aligned.m16n8k16.row.col.f32.bf16.bf16.f32 {p4,p5,p6,p7}, {%165,%166,%167,%168}, {m2,m3}, {fz,fz,fz,fz};\n"
        "mov.b32 {lo,hi}, r2;\n"
        "mov.b32 rl, {lo,lo};\n"
        "mov.b32 rh, {hi,hi};\n"
        "mul.bf16x2 x8, x8, rl;\n"
        "mul.bf16x2 x9, x9, rl;\n"
        "mul.bf16x2 x10, x10, rh;\n"
        "mul.bf16x2 x11, x11, rh;\n"
        "mma.sync.aligned.m16n8k16.row.col.f32.bf16.bf16.f32 {%144,%145,%146,%147}, {a0,a1,a2,a3}, {x8,x9}, {%144,%145,%146,%147};\n"
        "mma.sync.aligned.m16n8k16.row.col.f32.bf16.bf16.f32 {%148,%149,%150,%151}, {a0,a1,a2,a3}, {x10,x11}, {%148,%149,%150,%151};\n"
        "ld.shared.v4.u32 {x8,x9,x10,x11}, [xa+1280];\n"
        "mma.sync.aligned.m16n8k8.row.col.f32.bf16.bf16.f32 {d0,d1,d2,d3}, {%179,%180}, {m1}, {fz,fz,fz,fz};\n"
        "cvt.rn.bf16x2.f32 b2, d2, d0;\n"
        "cvt.rn.bf16x2.f32 b3, d3, d1;\n"
        "tanh.approx.f32 t0, p9;\n"
        "tanh.approx.f32 t1, p11;\n"
        "fma.rn.f32 t0, p9, t0, p9;\n"
        "fma.rn.f32 t1, p11, t1, p11;\n"
        "cvt.rn.bf16x2.f32 r2, t1, t0;\n"
        "mma.sync.aligned.m16n8k16.row.col.f32.bf16.bf16.f32 {p8,p9,p10,p11}, {%169,%170,%171,%172}, {m2,m3}, {fz,fz,fz,fz};\n"
        "mov.b32 {lo,hi}, r3;\n"
        "mov.b32 rl, {lo,lo};\n"
        "mov.b32 rh, {hi,hi};\n"
        "mul.bf16x2 x12, x12, rl;\n"
        "mul.bf16x2 x13, x13, rl;\n"
        "mul.bf16x2 x14, x14, rh;\n"
        "mul.bf16x2 x15, x15, rh;\n"
        "mma.sync.aligned.m16n8k16.row.col.f32.bf16.bf16.f32 {%152,%153,%154,%155}, {a0,a1,a2,a3}, {x12,x13}, {%152,%153,%154,%155};\n"
        "mma.sync.aligned.m16n8k16.row.col.f32.bf16.bf16.f32 {%156,%157,%158,%159}, {a0,a1,a2,a3}, {x14,x15}, {%156,%157,%158,%159};\n"
        "ld.shared.v4.u32 {x12,x13,x14,x15}, [xa+1408];\n"
        "@el mbarrier.arrive.shared.b64 _, [k0+8712];\n"
        "redux.sync.or.b32 ln, tag, 0xffffffff;\n"
        "mov.u32 sa, sn;\n"
        "add.u32 k0, sn, zz;\n"
        "tanh.approx.f32 t0, p13;\n"
        "tanh.approx.f32 t1, p15;\n"
        "fma.rn.f32 t0, p13, t0, p13;\n"
        "fma.rn.f32 t1, p15, t1, p15;\n"
        "cvt.rn.bf16x2.f32 r3, t1, t0;\n"
        "mma.sync.aligned.m16n8k16.row.col.f32.bf16.bf16.f32 {p12,p13,p14,p15}, {%173,%174,%175,%176}, {m2,m3}, {fz,fz,fz,fz};\n"
        "selp.u32 tq, lb, 5, w;\n"
        "brx.idx.uni tq, TB_%=;\n"
        "B0_%=:\n"
        "and.b32 la, ln, 255;\n"
        "shr.u32 lb, ln, 8;\n"
        "add.u32 ma, sa, %182;\n"
        "ldmatrix.sync.aligned.m8n8.x1.shared.b16 {yb}, [ma];\n"
        "add.u32 xa, sa, %181;\n"
        "mov.b32 {lo,hi}, r0;\n"
        "mov.b32 rl, {lo,lo};\n"
        "mov.b32 rh, {hi,hi};\n"
        "mul.bf16x2 x0, x0, rl;\n"
        "mul.bf16x2 x1, x1, rl;\n"
        "mul.bf16x2 x2, x2, rh;\n"
        "mul.bf16x2 x3, x3, rh;\n"
        "mma.sync.aligned.m16n8k16.row.col.f32.bf16.bf16.f32 {%0,%1,%2,%3}, {b0,b1,b2,b3}, {x0,x1}, {%0,%1,%2,%3};\n"
        "mma.sync.aligned.m16n8k16.row.col.f32.bf16.bf16.f32 {%4,%5,%6,%7}, {b0,b1,b2,b3}, {x2,x3}, {%4,%5,%6,%7};\n"
        "ld.shared.v4.u32 {x0,x1,x2,x3}, [xa+0];\n"
        "tanh.approx.f32 t0, p0;\n"
        "tanh.approx.f32 t1, p2;\n"
        "fma.rn.f32 t0, p0, t0, p0;\n"
        "fma.rn.f32 t1, p2, t1, p2;\n"
        "cvt.rn.bf16x2.f32 r0, t1, t0;\n"
        "mov.b32 {lo,hi}, r1;\n"
        "mov.b32 rl, {lo,lo};\n"
        "mov.b32 rh, {hi,hi};\n"
        "mul.bf16x2 x4, x4, rl;\n"
        "mul.bf16x2 x5, x5, rl;\n"
        "mul.bf16x2 x6, x6, rh;\n"
        "mul.bf16x2 x7, x7, rh;\n"
        "mma.sync.aligned.m16n8k16.row.col.f32.bf16.bf16.f32 {%8,%9,%10,%11}, {b0,b1,b2,b3}, {x4,x5}, {%8,%9,%10,%11};\n"
        "mma.sync.aligned.m16n8k16.row.col.f32.bf16.bf16.f32 {%12,%13,%14,%15}, {b0,b1,b2,b3}, {x6,x7}, {%12,%13,%14,%15};\n"
        "ld.shared.v4.u32 {x4,x5,x6,x7}, [xa+128];\n"
        "tanh.approx.f32 t0, p4;\n"
        "tanh.approx.f32 t1, p6;\n"
        "fma.rn.f32 t0, p4, t0, p4;\n"
        "fma.rn.f32 t1, p6, t1, p6;\n"
        "cvt.rn.bf16x2.f32 r1, t1, t0;\n"
        "mma.sync.aligned.m16n8k8.row.col.f32.bf16.bf16.f32 {d0,d1,d2,d3}, {%177,%178}, {yb}, {fz,fz,fz,fz};\n"
        "cvt.rn.bf16x2.f32 a0, d2, d0;\n"
        "cvt.rn.bf16x2.f32 a1, d3, d1;\n"
        "mov.b32 {lo,hi}, r2;\n"
        "mov.b32 rl, {lo,lo};\n"
        "mov.b32 rh, {hi,hi};\n"
        "mul.bf16x2 x8, x8, rl;\n"
        "mul.bf16x2 x9, x9, rl;\n"
        "mul.bf16x2 x10, x10, rh;\n"
        "mul.bf16x2 x11, x11, rh;\n"
        "mma.sync.aligned.m16n8k16.row.col.f32.bf16.bf16.f32 {%16,%17,%18,%19}, {b0,b1,b2,b3}, {x8,x9}, {%16,%17,%18,%19};\n"
        "mma.sync.aligned.m16n8k16.row.col.f32.bf16.bf16.f32 {%20,%21,%22,%23}, {b0,b1,b2,b3}, {x10,x11}, {%20,%21,%22,%23};\n"
        "ld.shared.v4.u32 {x8,x9,x10,x11}, [xa+256];\n"
        "tanh.approx.f32 t0, p8;\n"
        "tanh.approx.f32 t1, p10;\n"
        "fma.rn.f32 t0, p8, t0, p8;\n"
        "fma.rn.f32 t1, p10, t1, p10;\n"
        "cvt.rn.bf16x2.f32 r2, t1, t0;\n"
        "mma.sync.aligned.m16n8k8.row.col.f32.bf16.bf16.f32 {d0,d1,d2,d3}, {%179,%180}, {yb}, {fz,fz,fz,fz};\n"
        "cvt.rn.bf16x2.f32 a2, d2, d0;\n"
        "cvt.rn.bf16x2.f32 a3, d3, d1;\n"
        "mov.b32 {lo,hi}, r3;\n"
        "mov.b32 rl, {lo,lo};\n"
        "mov.b32 rh, {hi,hi};\n"
        "mul.bf16x2 x12, x12, rl;\n"
        "mul.bf16x2 x13, x13, rl;\n"
        "mul.bf16x2 x14, x14, rh;\n"
        "mul.bf16x2 x15, x15, rh;\n"
        "mma.sync.aligned.m16n8k16.row.col.f32.bf16.bf16.f32 {%24,%25,%26,%27}, {b0,b1,b2,b3}, {x12,x13}, {%24,%25,%26,%27};\n"
        "mma.sync.aligned.m16n8k16.row.col.f32.bf16.bf16.f32 {%28,%29,%30,%31}, {b0,b1,b2,b3}, {x14,x15}, {%28,%29,%30,%31};\n"
        "ld.shared.v4.u32 {x12,x13,x14,x15}, [xa+384];\n"
        "tanh.approx.f32 t0, p12;\n"
        "tanh.approx.f32 t1, p14;\n"
        "fma.rn.f32 t0, p12, t0, p12;\n"
        "fma.rn.f32 t1, p14, t1, p14;\n"
        "cvt.rn.bf16x2.f32 r3, t1, t0;\n"
        "mov.b32 {lo,hi}, r0;\n"
        "mov.b32 rl, {lo,lo};\n"
        "mov.b32 rh, {hi,hi};\n"
        "mul.bf16x2 x0, x0, rl;\n"
        "mul.bf16x2 x1, x1, rl;\n"
        "mul.bf16x2 x2, x2, rh;\n"
        "mul.bf16x2 x3, x3, rh;\n"
        "mov.b32 {lo,hi}, r1;\n"
        "mov.b32 rl, {lo,lo};\n"
        "mov.b32 rh, {hi,hi};\n"
        "mul.bf16x2 x4, x4, rl;\n"
        "mul.bf16x2 x5, x5, rl;\n"
        "mul.bf16x2 x6, x6, rh;\n"
        "mul.bf16x2 x7, x7, rh;\n"
        "brx.idx.uni la, TA_%=;\n"
        "B1_%=:\n"
        "and.b32 la, ln, 255;\n"
        "shr.u32 lb, ln, 8;\n"
        "add.u32 ma, sa, %182;\n"
        "ldmatrix.sync.aligned.m8n8.x1.shared.b16 {yb}, [ma];\n"
        "add.u32 xa, sa, %181;\n"
        "mov.b32 {lo,hi}, r0;\n"
        "mov.b32 rl, {lo,lo};\n"
        "mov.b32 rh, {hi,hi};\n"
        "mul.bf16x2 x0, x0, rl;\n"
        "mul.bf16x2 x1, x1, rl;\n"
        "mul.bf16x2 x2, x2, rh;\n"
        "mul.bf16x2 x3, x3, rh;\n"
        "mma.sync.aligned.m16n8k16.row.col.f32.bf16.bf16.f32 {%32,%33,%34,%35}, {b0,b1,b2,b3}, {x0,x1}, {%32,%33,%34,%35};\n"
        "mma.sync.aligned.m16n8k16.row.col.f32.bf16.bf16.f32 {%36,%37,%38,%39}, {b0,b1,b2,b3}, {x2,x3}, {%36,%37,%38,%39};\n"
        "ld.shared.v4.u32 {x0,x1,x2,x3}, [xa+0];\n"
        "tanh.approx.f32 t0, p0;\n"
        "tanh.approx.f32 t1, p2;\n"
        "fma.rn.f32 t0, p0, t0, p0;\n"
        "fma.rn.f32 t1, p2, t1, p2;\n"
        "cvt.rn.bf16x2.f32 r0, t1, t0;\n"
        "mov.b32 {lo,hi}, r1;\n"
        "mov.b32 rl, {lo,lo};\n"
        "mov.b32 rh, {hi,hi};\n"
        "mul.bf16x2 x4, x4, rl;\n"
        "mul.bf16x2 x5, x5, rl;\n"
        "mul.bf16x2 x6, x6, rh;\n"
        "mul.bf16x2 x7, x7, rh;\n"
        "mma.sync.aligned.m16n8k16.row.col.f32.bf16.bf16.f32 {%40,%41,%42,%43}, {b0,b1,b2,b3}, {x4,x5}, {%40,%41,%42,%43};\n"
        "mma.sync.aligned.m16n8k16.row.col.f32.bf16.bf16.f32 {%44,%45,%46,%47}, {b0,b1,b2,b3}, {x6,x7}, {%44,%45,%46,%47};\n"
        "ld.shared.v4.u32 {x4,x5,x6,x7}, [xa+128];\n"
        "tanh.approx.f32 t0, p4;\n"
        "tanh.approx.f32 t1, p6;\n"
        "fma.rn.f32 t0, p4, t0, p4;\n"
        "fma.rn.f32 t1, p6, t1, p6;\n"
        "cvt.rn.bf16x2.f32 r1, t1, t0;\n"
        "mma.sync.aligned.m16n8k8.row.col.f32.bf16.bf16.f32 {d0,d1,d2,d3}, {%177,%178}, {yb}, {fz,fz,fz,fz};\n"
        "cvt.rn.bf16x2.f32 a0, d2, d0;\n"
        "cvt.rn.bf16x2.f32 a1, d3, d1;\n"
        "mov.b32 {lo,hi}, r2;\n"
        "mov.b32 rl, {lo,lo};\n"
        "mov.b32 rh, {hi,hi};\n"
        "mul.bf16x2 x8, x8, rl;\n"
        "mul.bf16x2 x9, x9, rl;\n"
        "mul.bf16x2 x10, x10, rh;\n"
        "mul.bf16x2 x11, x11, rh;\n"
        "mma.sync.aligned.m16n8k16.row.col.f32.bf16.bf16.f32 {%48,%49,%50,%51}, {b0,b1,b2,b3}, {x8,x9}, {%48,%49,%50,%51};\n"
        "mma.sync.aligned.m16n8k16.row.col.f32.bf16.bf16.f32 {%52,%53,%54,%55}, {b0,b1,b2,b3}, {x10,x11}, {%52,%53,%54,%55};\n"
        "ld.shared.v4.u32 {x8,x9,x10,x11}, [xa+256];\n"
        "tanh.approx.f32 t0, p8;\n"
        "tanh.approx.f32 t1, p10;\n"
        "fma.rn.f32 t0, p8, t0, p8;\n"
        "fma.rn.f32 t1, p10, t1, p10;\n"
        "cvt.rn.bf16x2.f32 r2, t1, t0;\n"
        "mma.sync.aligned.m16n8k8.row.col.f32.bf16.bf16.f32 {d0,d1,d2,d3}, {%179,%180}, {yb}, {fz,fz,fz,fz};\n"
        "cvt.rn.bf16x2.f32 a2, d2, d0;\n"
        "cvt.rn.bf16x2.f32 a3, d3, d1;\n"
        "mov.b32 {lo,hi}, r3;\n"
        "mov.b32 rl, {lo,lo};\n"
        "mov.b32 rh, {hi,hi};\n"
        "mul.bf16x2 x12, x12, rl;\n"
        "mul.bf16x2 x13, x13, rl;\n"
        "mul.bf16x2 x14, x14, rh;\n"
        "mul.bf16x2 x15, x15, rh;\n"
        "mma.sync.aligned.m16n8k16.row.col.f32.bf16.bf16.f32 {%56,%57,%58,%59}, {b0,b1,b2,b3}, {x12,x13}, {%56,%57,%58,%59};\n"
        "mma.sync.aligned.m16n8k16.row.col.f32.bf16.bf16.f32 {%60,%61,%62,%63}, {b0,b1,b2,b3}, {x14,x15}, {%60,%61,%62,%63};\n"
        "ld.shared.v4.u32 {x12,x13,x14,x15}, [xa+384];\n"
        "tanh.approx.f32 t0, p12;\n"
        "tanh.approx.f32 t1, p14;\n"
        "fma.rn.f32 t0, p12, t0, p12;\n"
        "fma.rn.f32 t1, p14, t1, p14;\n"
        "cvt.rn.bf16x2.f32 r3, t1, t0;\n"
        "mov.b32 {lo,hi}, r0;\n"
        "mov.b32 rl, {lo,lo};\n"
        "mov.b32 rh, {hi,hi};\n"
        "mul.bf16x2 x0, x0, rl;\n"
        "mul.bf16x2 x1, x1, rl;\n"
        "mul.bf16x2 x2, x2, rh;\n"
        "mul.bf16x2 x3, x3, rh;\n"
        "mov.b32 {lo,hi}, r1;\n"
        "mov.b32 rl, {lo,lo};\n"
        "mov.b32 rh, {hi,hi};\n"
        "mul.bf16x2 x4, x4, rl;\n"
        "mul.bf16x2 x5, x5, rl;\n"
        "mul.bf16x2 x6, x6, rh;\n"
        "mul.bf16x2 x7, x7, rh;\n"
        "brx.idx.uni la, TA_%=;\n"
        "B2_%=:\n"
        "and.b32 la, ln, 255;\n"
        "shr.u32 lb, ln, 8;\n"
        "add.u32 ma, sa, %182;\n"
        "ldmatrix.sync.aligned.m8n8.x1.shared.b16 {yb}, [ma];\n"
        "add.u32 xa, sa, %181;\n"
        "mov.b32 {lo,hi}, r0;\n"
        "mov.b32 rl, {lo,lo};\n"
        "mov.b32 rh, {hi,hi};\n"
        "mul.bf16x2 x0, x0, rl;\n"
        "mul.bf16x2 x1, x1, rl;\n"
        "mul.bf16x2 x2, x2, rh;\n"
        "mul.bf16x2 x3, x3, rh;\n"
        "mma.sync.aligned.m16n8k16.row.col.f32.bf16.bf16.f32 {%64,%65,%66,%67}, {b0,b1,b2,b3}, {x0,x1}, {%64,%65,%66,%67};\n"
        "mma.sync.aligned.m16n8k16.row.col.f32.bf16.bf16.f32 {%68,%69,%70,%71}, {b0,b1,b2,b3}, {x2,x3}, {%68,%69,%70,%71};\n"
        "ld.shared.v4.u32 {x0,x1,x2,x3}, [xa+0];\n"
        "tanh.approx.f32 t0, p0;\n"
        "tanh.approx.f32 t1, p2;\n"
        "fma.rn.f32 t0, p0, t0, p0;\n"
        "fma.rn.f32 t1, p2, t1, p2;\n"
        "cvt.rn.bf16x2.f32 r0, t1, t0;\n"
        "mov.b32 {lo,hi}, r1;\n"
        "mov.b32 rl, {lo,lo};\n"
        "mov.b32 rh, {hi,hi};\n"
        "mul.bf16x2 x4, x4, rl;\n"
        "mul.bf16x2 x5, x5, rl;\n"
        "mul.bf16x2 x6, x6, rh;\n"
        "mul.bf16x2 x7, x7, rh;\n"
        "mma.sync.aligned.m16n8k16.row.col.f32.bf16.bf16.f32 {%72,%73,%74,%75}, {b0,b1,b2,b3}, {x4,x5}, {%72,%73,%74,%75};\n"
        "mma.sync.aligned.m16n8k16.row.col.f32.bf16.bf16.f32 {%76,%77,%78,%79}, {b0,b1,b2,b3}, {x6,x7}, {%76,%77,%78,%79};\n"
        "ld.shared.v4.u32 {x4,x5,x6,x7}, [xa+128];\n"
        "tanh.approx.f32 t0, p4;\n"
        "tanh.approx.f32 t1, p6;\n"
        "fma.rn.f32 t0, p4, t0, p4;\n"
        "fma.rn.f32 t1, p6, t1, p6;\n"
        "cvt.rn.bf16x2.f32 r1, t1, t0;\n"
        "mma.sync.aligned.m16n8k8.row.col.f32.bf16.bf16.f32 {d0,d1,d2,d3}, {%177,%178}, {yb}, {fz,fz,fz,fz};\n"
        "cvt.rn.bf16x2.f32 a0, d2, d0;\n"
        "cvt.rn.bf16x2.f32 a1, d3, d1;\n"
        "mov.b32 {lo,hi}, r2;\n"
        "mov.b32 rl, {lo,lo};\n"
        "mov.b32 rh, {hi,hi};\n"
        "mul.bf16x2 x8, x8, rl;\n"
        "mul.bf16x2 x9, x9, rl;\n"
        "mul.bf16x2 x10, x10, rh;\n"
        "mul.bf16x2 x11, x11, rh;\n"
        "mma.sync.aligned.m16n8k16.row.col.f32.bf16.bf16.f32 {%80,%81,%82,%83}, {b0,b1,b2,b3}, {x8,x9}, {%80,%81,%82,%83};\n"
        "mma.sync.aligned.m16n8k16.row.col.f32.bf16.bf16.f32 {%84,%85,%86,%87}, {b0,b1,b2,b3}, {x10,x11}, {%84,%85,%86,%87};\n"
        "ld.shared.v4.u32 {x8,x9,x10,x11}, [xa+256];\n"
        "tanh.approx.f32 t0, p8;\n"
        "tanh.approx.f32 t1, p10;\n"
        "fma.rn.f32 t0, p8, t0, p8;\n"
        "fma.rn.f32 t1, p10, t1, p10;\n"
        "cvt.rn.bf16x2.f32 r2, t1, t0;\n"
        "mma.sync.aligned.m16n8k8.row.col.f32.bf16.bf16.f32 {d0,d1,d2,d3}, {%179,%180}, {yb}, {fz,fz,fz,fz};\n"
        "cvt.rn.bf16x2.f32 a2, d2, d0;\n"
        "cvt.rn.bf16x2.f32 a3, d3, d1;\n"
        "mov.b32 {lo,hi}, r3;\n"
        "mov.b32 rl, {lo,lo};\n"
        "mov.b32 rh, {hi,hi};\n"
        "mul.bf16x2 x12, x12, rl;\n"
        "mul.bf16x2 x13, x13, rl;\n"
        "mul.bf16x2 x14, x14, rh;\n"
        "mul.bf16x2 x15, x15, rh;\n"
        "mma.sync.aligned.m16n8k16.row.col.f32.bf16.bf16.f32 {%88,%89,%90,%91}, {b0,b1,b2,b3}, {x12,x13}, {%88,%89,%90,%91};\n"
        "mma.sync.aligned.m16n8k16.row.col.f32.bf16.bf16.f32 {%92,%93,%94,%95}, {b0,b1,b2,b3}, {x14,x15}, {%92,%93,%94,%95};\n"
        "ld.shared.v4.u32 {x12,x13,x14,x15}, [xa+384];\n"
        "tanh.approx.f32 t0, p12;\n"
        "tanh.approx.f32 t1, p14;\n"
        "fma.rn.f32 t0, p12, t0, p12;\n"
        "fma.rn.f32 t1, p14, t1, p14;\n"
        "cvt.rn.bf16x2.f32 r3, t1, t0;\n"
        "mov.b32 {lo,hi}, r0;\n"
        "mov.b32 rl, {lo,lo};\n"
        "mov.b32 rh, {hi,hi};\n"
        "mul.bf16x2 x0, x0, rl;\n"
        "mul.bf16x2 x1, x1, rl;\n"
        "mul.bf16x2 x2, x2, rh;\n"
        "mul.bf16x2 x3, x3, rh;\n"
        "mov.b32 {lo,hi}, r1;\n"
        "mov.b32 rl, {lo,lo};\n"
        "mov.b32 rh, {hi,hi};\n"
        "mul.bf16x2 x4, x4, rl;\n"
        "mul.bf16x2 x5, x5, rl;\n"
        "mul.bf16x2 x6, x6, rh;\n"
        "mul.bf16x2 x7, x7, rh;\n"
        "brx.idx.uni la, TA_%=;\n"
        "B3_%=:\n"
        "and.b32 la, ln, 255;\n"
        "shr.u32 lb, ln, 8;\n"
        "add.u32 ma, sa, %182;\n"
        "ldmatrix.sync.aligned.m8n8.x1.shared.b16 {yb}, [ma];\n"
        "add.u32 xa, sa, %181;\n"
        "mov.b32 {lo,hi}, r0;\n"
        "mov.b32 rl, {lo,lo};\n"
        "mov.b32 rh, {hi,hi};\n"
        "mul.bf16x2 x0, x0, rl;\n"
        "mul.bf16x2 x1, x1, rl;\n"
        "mul.bf16x2 x2, x2, rh;\n"
        "mul.bf16x2 x3, x3, rh;\n"
        "mma.sync.aligned.m16n8k16.row.col.f32.bf16.bf16.f32 {%96,%97,%98,%99}, {b0,b1,b2,b3}, {x0,x1}, {%96,%97,%98,%99};\n"
        "mma.sync.aligned.m16n8k16.row.col.f32.bf16.bf16.f32 {%100,%101,%102,%103}, {b0,b1,b2,b3}, {x2,x3}, {%100,%101,%102,%103};\n"
        "ld.shared.v4.u32 {x0,x1,x2,x3}, [xa+0];\n"
        "tanh.approx.f32 t0, p0;\n"
        "tanh.approx.f32 t1, p2;\n"
        "fma.rn.f32 t0, p0, t0, p0;\n"
        "fma.rn.f32 t1, p2, t1, p2;\n"
        "cvt.rn.bf16x2.f32 r0, t1, t0;\n"
        "mov.b32 {lo,hi}, r1;\n"
        "mov.b32 rl, {lo,lo};\n"
        "mov.b32 rh, {hi,hi};\n"
        "mul.bf16x2 x4, x4, rl;\n"
        "mul.bf16x2 x5, x5, rl;\n"
        "mul.bf16x2 x6, x6, rh;\n"
        "mul.bf16x2 x7, x7, rh;\n"
        "mma.sync.aligned.m16n8k16.row.col.f32.bf16.bf16.f32 {%104,%105,%106,%107}, {b0,b1,b2,b3}, {x4,x5}, {%104,%105,%106,%107};\n"
        "mma.sync.aligned.m16n8k16.row.col.f32.bf16.bf16.f32 {%108,%109,%110,%111}, {b0,b1,b2,b3}, {x6,x7}, {%108,%109,%110,%111};\n"
        "ld.shared.v4.u32 {x4,x5,x6,x7}, [xa+128];\n"
        "tanh.approx.f32 t0, p4;\n"
        "tanh.approx.f32 t1, p6;\n"
        "fma.rn.f32 t0, p4, t0, p4;\n"
        "fma.rn.f32 t1, p6, t1, p6;\n"
        "cvt.rn.bf16x2.f32 r1, t1, t0;\n"
        "mma.sync.aligned.m16n8k8.row.col.f32.bf16.bf16.f32 {d0,d1,d2,d3}, {%177,%178}, {yb}, {fz,fz,fz,fz};\n"
        "cvt.rn.bf16x2.f32 a0, d2, d0;\n"
        "cvt.rn.bf16x2.f32 a1, d3, d1;\n"
        "mov.b32 {lo,hi}, r2;\n"
        "mov.b32 rl, {lo,lo};\n"
        "mov.b32 rh, {hi,hi};\n"
        "mul.bf16x2 x8, x8, rl;\n"
        "mul.bf16x2 x9, x9, rl;\n"
        "mul.bf16x2 x10, x10, rh;\n"
        "mul.bf16x2 x11, x11, rh;\n"
        "mma.sync.aligned.m16n8k16.row.col.f32.bf16.bf16.f32 {%112,%113,%114,%115}, {b0,b1,b2,b3}, {x8,x9}, {%112,%113,%114,%115};\n"
        "mma.sync.aligned.m16n8k16.row.col.f32.bf16.bf16.f32 {%116,%117,%118,%119}, {b0,b1,b2,b3}, {x10,x11}, {%116,%117,%118,%119};\n"
        "ld.shared.v4.u32 {x8,x9,x10,x11}, [xa+256];\n"
        "tanh.approx.f32 t0, p8;\n"
        "tanh.approx.f32 t1, p10;\n"
        "fma.rn.f32 t0, p8, t0, p8;\n"
        "fma.rn.f32 t1, p10, t1, p10;\n"
        "cvt.rn.bf16x2.f32 r2, t1, t0;\n"
        "mma.sync.aligned.m16n8k8.row.col.f32.bf16.bf16.f32 {d0,d1,d2,d3}, {%179,%180}, {yb}, {fz,fz,fz,fz};\n"
        "cvt.rn.bf16x2.f32 a2, d2, d0;\n"
        "cvt.rn.bf16x2.f32 a3, d3, d1;\n"
        "mov.b32 {lo,hi}, r3;\n"
        "mov.b32 rl, {lo,lo};\n"
        "mov.b32 rh, {hi,hi};\n"
        "mul.bf16x2 x12, x12, rl;\n"
        "mul.bf16x2 x13, x13, rl;\n"
        "mul.bf16x2 x14, x14, rh;\n"
        "mul.bf16x2 x15, x15, rh;\n"
        "mma.sync.aligned.m16n8k16.row.col.f32.bf16.bf16.f32 {%120,%121,%122,%123}, {b0,b1,b2,b3}, {x12,x13}, {%120,%121,%122,%123};\n"
        "mma.sync.aligned.m16n8k16.row.col.f32.bf16.bf16.f32 {%124,%125,%126,%127}, {b0,b1,b2,b3}, {x14,x15}, {%124,%125,%126,%127};\n"
        "ld.shared.v4.u32 {x12,x13,x14,x15}, [xa+384];\n"
        "tanh.approx.f32 t0, p12;\n"
        "tanh.approx.f32 t1, p14;\n"
        "fma.rn.f32 t0, p12, t0, p12;\n"
        "fma.rn.f32 t1, p14, t1, p14;\n"
        "cvt.rn.bf16x2.f32 r3, t1, t0;\n"
        "mov.b32 {lo,hi}, r0;\n"
        "mov.b32 rl, {lo,lo};\n"
        "mov.b32 rh, {hi,hi};\n"
        "mul.bf16x2 x0, x0, rl;\n"
        "mul.bf16x2 x1, x1, rl;\n"
        "mul.bf16x2 x2, x2, rh;\n"
        "mul.bf16x2 x3, x3, rh;\n"
        "mov.b32 {lo,hi}, r1;\n"
        "mov.b32 rl, {lo,lo};\n"
        "mov.b32 rh, {hi,hi};\n"
        "mul.bf16x2 x4, x4, rl;\n"
        "mul.bf16x2 x5, x5, rl;\n"
        "mul.bf16x2 x6, x6, rh;\n"
        "mul.bf16x2 x7, x7, rh;\n"
        "brx.idx.uni la, TA_%=;\n"
        "B4_%=:\n"
        "and.b32 la, ln, 255;\n"
        "shr.u32 lb, ln, 8;\n"
        "add.u32 ma, sa, %182;\n"
        "ldmatrix.sync.aligned.m8n8.x1.shared.b16 {yb}, [ma];\n"
        "add.u32 xa, sa, %181;\n"
        "mov.b32 {lo,hi}, r0;\n"
        "mov.b32 rl, {lo,lo};\n"
        "mov.b32 rh, {hi,hi};\n"
        "mul.bf16x2 x0, x0, rl;\n"
        "mul.bf16x2 x1, x1, rl;\n"
        "mul.bf16x2 x2, x2, rh;\n"
        "mul.bf16x2 x3, x3, rh;\n"
        "mma.sync.aligned.m16n8k16.row.col.f32.bf16.bf16.f32 {%128,%129,%130,%131}, {b0,b1,b2,b3}, {x0,x1}, {%128,%129,%130,%131};\n"
        "mma.sync.aligned.m16n8k16.row.col.f32.bf16.bf16.f32 {%132,%133,%134,%135}, {b0,b1,b2,b3}, {x2,x3}, {%132,%133,%134,%135};\n"
        "ld.shared.v4.u32 {x0,x1,x2,x3}, [xa+0];\n"
        "tanh.approx.f32 t0, p0;\n"
        "tanh.approx.f32 t1, p2;\n"
        "fma.rn.f32 t0, p0, t0, p0;\n"
        "fma.rn.f32 t1, p2, t1, p2;\n"
        "cvt.rn.bf16x2.f32 r0, t1, t0;\n"
        "mov.b32 {lo,hi}, r1;\n"
        "mov.b32 rl, {lo,lo};\n"
        "mov.b32 rh, {hi,hi};\n"
        "mul.bf16x2 x4, x4, rl;\n"
        "mul.bf16x2 x5, x5, rl;\n"
        "mul.bf16x2 x6, x6, rh;\n"
        "mul.bf16x2 x7, x7, rh;\n"
        "mma.sync.aligned.m16n8k16.row.col.f32.bf16.bf16.f32 {%136,%137,%138,%139}, {b0,b1,b2,b3}, {x4,x5}, {%136,%137,%138,%139};\n"
        "mma.sync.aligned.m16n8k16.row.col.f32.bf16.bf16.f32 {%140,%141,%142,%143}, {b0,b1,b2,b3}, {x6,x7}, {%140,%141,%142,%143};\n"
        "ld.shared.v4.u32 {x4,x5,x6,x7}, [xa+128];\n"
        "tanh.approx.f32 t0, p4;\n"
        "tanh.approx.f32 t1, p6;\n"
        "fma.rn.f32 t0, p4, t0, p4;\n"
        "fma.rn.f32 t1, p6, t1, p6;\n"
        "cvt.rn.bf16x2.f32 r1, t1, t0;\n"
        "mma.sync.aligned.m16n8k8.row.col.f32.bf16.bf16.f32 {d0,d1,d2,d3}, {%177,%178}, {yb}, {fz,fz,fz,fz};\n"
        "cvt.rn.bf16x2.f32 a0, d2, d0;\n"
        "cvt.rn.bf16x2.f32 a1, d3, d1;\n"
        "mov.b32 {lo,hi}, r2;\n"
        "mov.b32 rl, {lo,lo};\n"
        "mov.b32 rh, {hi,hi};\n"
        "mul.bf16x2 x8, x8, rl;\n"
        "mul.bf16x2 x9, x9, rl;\n"
        "mul.bf16x2 x10, x10, rh;\n"
        "mul.bf16x2 x11, x11, rh;\n"
        "mma.sync.aligned.m16n8k16.row.col.f32.bf16.bf16.f32 {%144,%145,%146,%147}, {b0,b1,b2,b3}, {x8,x9}, {%144,%145,%146,%147};\n"
        "mma.sync.aligned.m16n8k16.row.col.f32.bf16.bf16.f32 {%148,%149,%150,%151}, {b0,b1,b2,b3}, {x10,x11}, {%148,%149,%150,%151};\n"
        "ld.shared.v4.u32 {x8,x9,x10,x11}, [xa+256];\n"
        "tanh.approx.f32 t0, p8;\n"
        "tanh.approx.f32 t1, p10;\n"
        "fma.rn.f32 t0, p8, t0, p8;\n"
        "fma.rn.f32 t1, p10, t1, p10;\n"
        "cvt.rn.bf16x2.f32 r2, t1, t0;\n"
        "mma.sync.aligned.m16n8k8.row.col.f32.bf16.bf16.f32 {d0,d1,d2,d3}, {%179,%180}, {yb}, {fz,fz,fz,fz};\n"
        "cvt.rn.bf16x2.f32 a2, d2, d0;\n"
        "cvt.rn.bf16x2.f32 a3, d3, d1;\n"
        "mov.b32 {lo,hi}, r3;\n"
        "mov.b32 rl, {lo,lo};\n"
        "mov.b32 rh, {hi,hi};\n"
        "mul.bf16x2 x12, x12, rl;\n"
        "mul.bf16x2 x13, x13, rl;\n"
        "mul.bf16x2 x14, x14, rh;\n"
        "mul.bf16x2 x15, x15, rh;\n"
        "mma.sync.aligned.m16n8k16.row.col.f32.bf16.bf16.f32 {%152,%153,%154,%155}, {b0,b1,b2,b3}, {x12,x13}, {%152,%153,%154,%155};\n"
        "mma.sync.aligned.m16n8k16.row.col.f32.bf16.bf16.f32 {%156,%157,%158,%159}, {b0,b1,b2,b3}, {x14,x15}, {%156,%157,%158,%159};\n"
        "ld.shared.v4.u32 {x12,x13,x14,x15}, [xa+384];\n"
        "tanh.approx.f32 t0, p12;\n"
        "tanh.approx.f32 t1, p14;\n"
        "fma.rn.f32 t0, p12, t0, p12;\n"
        "fma.rn.f32 t1, p14, t1, p14;\n"
        "cvt.rn.bf16x2.f32 r3, t1, t0;\n"
        "mov.b32 {lo,hi}, r0;\n"
        "mov.b32 rl, {lo,lo};\n"
        "mov.b32 rh, {hi,hi};\n"
        "mul.bf16x2 x0, x0, rl;\n"
        "mul.bf16x2 x1, x1, rl;\n"
        "mul.bf16x2 x2, x2, rh;\n"
        "mul.bf16x2 x3, x3, rh;\n"
        "mov.b32 {lo,hi}, r1;\n"
        "mov.b32 rl, {lo,lo};\n"
        "mov.b32 rh, {hi,hi};\n"
        "mul.bf16x2 x4, x4, rl;\n"
        "mul.bf16x2 x5, x5, rl;\n"
        "mul.bf16x2 x6, x6, rh;\n"
        "mul.bf16x2 x7, x7, rh;\n"
        "brx.idx.uni la, TA_%=;\n"
        "EXIT_%=:\n"
        "mov.u32 %160, ring;\n"
        "}\n"
        : "+f"(acc[0][0][0][0]), "+f"(acc[0][0][0][1]), "+f"(acc[0][0][0][2]), "+f"(acc[0][0][0][3]), "+f"(acc[0][0][1][0]),
          "+f"(acc[0][0][1][1]), "+f"(acc[0][0][1][2]), "+f"(acc[0][0][1][3]), "+f"(acc[0][1][0][0]), "+f"(acc[0][1][0][1]),
          "+f"(acc[0][1][0][2]), "+f"(acc[0][1][0][3]), "+f"(acc[0][1][1][0]), "+f"(acc[0][1][1][1]), "+f"(acc[0][1][1][2]),
          "+f"(acc[0][1][1][3]), "+f"(acc[0][2][0][0]), "+f"(acc[0][2][0][1]), "+f"(acc[0][2][0][2]), "+f"(acc[0][2][0][3]),
          "+f"(acc[0][2][1][0]), "+f"(acc[0][2][1][1]), "+f"(acc[0][2][1][2]), "+f"(acc[0][2][1][3]), "+f"(acc[0][3][0][0]),
          "+f"(acc[0][3][0][1]), "+f"(acc[0][3][0][2]), "+f"(acc[0][3][0][3]), "+f"(acc[0][3][1][0]), "+f"(acc[0][3][1][1]),
          "+f"(acc[0][3][1][2]), "+f"(acc[0][3][1][3]), "+f"(acc[1][0][0][0]), "+f"(acc[1][0][0][1]), "+f"(acc[1][0][0][2]),
          "+f"(acc[1][0][0][3]), "+f"(acc[1][0][1][0]), "+f"(acc[1][0][1][1]), "+f"(acc[1][0][1][2]), "+f"(acc[1][0][1][3]),
          "+f"(acc[1][1][0][0]), "+f"(acc[1][1][0][1]), "+f"(acc[1][1][0][2]), "+f"(acc[1][1][0][3]), "+f"(acc[1][1][1][0]),
          "+f"(acc[1][1][1][1]), "+f"(acc[1][1][1][2]), "+f"(acc[1][1][1][3]), "+f"(acc[1][2][0][0]), "+f"(acc[1][2][0][1]),
          "+f"(acc[1][2][0][2]), "+f"(acc[1][2][0][3]), "+f"(acc[1][2][1][0]), "+f"(acc[1][2][1][1]), "+f"(acc[1][2][1][2]),
          "+f"(acc[1][2][1][3]), "+f"(acc[1][3][0][0]), "+f"(acc[1][3][0][1]), "+f"(acc[1][3][0][2]), "+f"(acc[1][3][0][3]),
          "+f"(acc[1][3][1][0]), "+f"(acc[1][3][1][1]), "+f"(acc[1][3][1][2]), "+f"(acc[1][3][1][3]), "+f"(acc[2][0][0][0]),
          "+f"(acc[2][0][0][1]), "+f"(acc[2][0][0][2]), "+f"(acc[2][0][0][3]), "+f"(acc[2][0][1][0]), "+f"(acc[2][0][1][1]),
          "+f"(acc[2][0][1][2]), "+f"(acc[2][0][1][3]), "+f"(acc[2][1][0][0]), "+f"(acc[2][1][0][1]), "+f"(acc[2][1][0][2]),
          "+f"(acc[2][1][0][3]), "+f"(acc[2][1][1][0]), "+f"(acc[2][1][1][1]), "+f"(acc[2][1][1][2]), "+f"(acc[2][1][1][3]),
          "+f"(acc[2][2][0][0]), "+f"(acc[2][2][0][1]), "+f"(acc[2][2][0][2]), "+f"(acc[2][2][0][3]), "+f"(acc[2][2][1][0]),
          "+f"(acc[2][2][1][1]), "+f"(acc[2][2][1][2]), "+f"(acc[2][2][1][3]), "+f"(acc[2][3][0][0]), "+f"(acc[2][3][0][1]),
          "+f"(acc[2][3][0][2]), "+f"(acc[2][3][0][3]), "+f"(acc[2][3][1][0]), "+f"(acc[2][3][1][1]), "+f"(acc[2][3][1][2]),
          "+f"(acc[2][3][1][3]), "+f"(acc[3][0][0][0]), "+f"(acc[3][0][0][1]), "+f"(acc[3][0][0][2]), "+f"(acc[3][0][0][3]),
          "+f"(acc[3][0][1][0]), "+f"(acc[3][0][1][1]), "+f"(acc[3][0][1][2]), "+f"(acc[3][0][1][3]), "+f"(acc[3][1][0][0]),
          "+f"(acc[3][1][0][1]), "+f"(acc[3][1][0][2]), "+f"(acc[3][1][0][3]), "+f"(acc[3][1][1][0]), "+f"(acc[3][1][1][1]),
          "+f"(acc[3][1][1][2]), "+f"(acc[3][1][1][3]), "+f"(acc[3][2][0][0]), "+f"(acc[3][2][0][1]), "+f"(acc[3][2][0][2]),
          "+f"(acc[3][2][0][3]), "+f"(acc[3][2][1][0]), "+f"(acc[3][2][1][1]), "+f"(acc[3][2][1][2]), "+f"(acc[3][2][1][3]),
          "+f"(acc[3][3][0][0]), "+f"(acc[3][3][0][1]), "+f"(acc[3][3][0][2]), "+f"(acc[3][3][0][3]), "+f"(acc[3][3][1][0]),
          "+f"(acc[3][3][1][1]), "+f"(acc[3][3][1][2]), "+f"(acc[3][3][1][3]), "+f"(acc[4][0][0][0]), "+f"(acc[4][0][0][1]),
          "+f"(acc[4][0][0][2]), "+f"(acc[4][0][0][3]), "+f"(acc[4][0][1][0]), "+f"(acc[4][0][1][1]), "+f"(acc[4][0][1][2]),
          "+f"(acc[4][0][1][3]), "+f"(acc[4][1][0][0]), "+f"(acc[4][1][0][1]), "+f"(acc[4][1][0][2]), "+f"(acc[4][1][0][3]),
          "+f"(acc[4][1][1][0]), "+f"(acc[4][1][1][1]), "+f"(acc[4][1][1][2]), "+f"(acc[4][1][1][3]), "+f"(acc[4][2][0][0]),
          "+f"(acc[4][2][0][1]), "+f"(acc[4][2][0][2]), "+f"(acc[4][2][0][3]), "+f"(acc[4][2][1][0]), "+f"(acc[4][2][1][1]),
          "+f"(acc[4][2][1][2]), "+f"(acc[4][2][1][3]), "+f"(acc[4][3][0][0]), "+f"(acc[4][3][0][1]), "+f"(acc[4][3][0][2]),
          "+f"(acc[4][3][0][3]), "+f"(acc[4][3][1][0]), "+f"(acc[4][3][1][1]), "+f"(acc[4][3][1][2]), "+f"(acc[4][3][1][3]),
          "+r"(ring)
        : "r"(wf[0][0]), "r"(wf[0][1]), "r"(wf[0][2]), "r"(wf[0][3]), "r"(wf[1][0]), "r"(wf[1][1]), "r"(wf[1][2]), "r"(wf[1][3]),
          "r"(wf[2][0]), "r"(wf[2][1]), "r"(wf[2][2]), "r"(wf[2][3]), "r"(wf[3][0]), "r"(wf[3][1]), "r"(wf[3][2]), "r"(wf[3][3]),
          "r"(cgf[0]), "r"(cgf[1]), "r"(cgf[2]), "r"(cgf[3]), "r"(xoff), "r"(moff), "r"(rec)
        : "memory");
}

__device__ __noinline__ void generic_path(float* sagg, const __nv_bfloat16* x, const int* src, const int* dst,
                                          const __nv_bfloat16* Y, const __nv_bfloat16* ef, const __nv_bfloat16* w_rad,
                                          const __nv_bfloat16* cg, int x0, int x1) {
    const int tid = threadIdx.x, lane = tid & 31, blk = blockIdx.x;
    for (int k = 0; k < 2; k++)
        for (int r = 0; r < min(k == 0 ? x0 : x1, 32); r++) {
            uint32_t* p2 = g_mail2 + (blk * NSRC + ((tid + k * NTHR) >> 3)) * 32 + r;
            uint32_t v;
            int it = 0;
            do {
                asm volatile("ld.relaxed.gpu.global.u32 %0, [%1];" : "=r"(v) : "l"(p2) : "memory");
                if (++it > (1 << 20)) __trap();
            } while (v == 0);
            *p2 = 0;
        }
    if (tid < 8 * NG) mbar_inval(smem_u32(sagg) + (tid >> 1) * STAGE + 4 * ROWP + (tid & 1) * 8);
    __syncthreads();
    for (int i = tid; i < NPB * 512; i += NTHR) sagg[i] = 0.f;
    __syncthreads();
    for (int e0 = tid & ~31; e0 < N_EDGES; e0 += NTHR) {
        uint32_t bm = __ballot_sync(~0u, dst[e0 + lane] / NPB == blk);
        while (bm) {
            const int e = e0 + __ffs(bm) - 1, s = src[e], loc = dst[e] - blk * NPB;
            bm &= bm - 1;
            float a[4][4];
            for (int i = 0; i < 4; i++)
                for (int o = 0; o < 4; o++) {
                    a[i][o] = 0.f;
                    for (int f = 0; f < 4; f++)
                        a[i][o] += __bfloat162float(Y[e * 4 + f]) * __bfloat162float(cg[i * 16 + f * 4 + o]);
                }
#pragma unroll 1
            for (int c = lane; c < 128; c += 32) {
                float pre = 0.f;
                for (int k = 0; k < 16; k++)
                    pre += __bfloat162float(ef[e * 16 + k]) * __bfloat162float(w_rad[k * 128 + c]);
                const float R = pre / (1.f + __expf(-pre));
                for (int o = 0; o < 4; o++) {
                    float acc = 0.f;
                    for (int i = 0; i < 4; i++) acc += __bfloat162float(x[(size_t)s * 512 + c * 4 + i]) * a[i][o];
                    atomicAdd(&sagg[loc * 512 + c * 4 + o], R * acc);
                }
            }
        }
    }
    __syncthreads();
}

template <uint32_t STAGES>
__device__ __forceinline__ void init_barriers() {
    extern __shared__ __align__(1024) uint8_t smem[];
    const uint32_t sb = smem_u32(smem);
#pragma unroll
    for (int i = 0; i < 4 * NG; i++) {
        if (!((STAGES >> i) & 1)) continue;
        mbar_init(sb + i * STAGE + 4 * ROWP, 32);
        mbar_init(sb + i * STAGE + 4 * ROWP + 8, 2);
    }
}

template <int PHASES>
__global__ void __launch_bounds__(NTHR, 1)
tfn_kernel(const __nv_bfloat16* __restrict__ x, const int* __restrict__ src, const int* __restrict__ dst,
           const __nv_bfloat16* __restrict__ Y, const __nv_bfloat16* __restrict__ ef,
           const __nv_bfloat16* __restrict__ w_rad, const __nv_bfloat16* __restrict__ cg,
           const __nv_bfloat16* __restrict__ w_mix, __nv_bfloat16* __restrict__ out) {
    extern __shared__ __align__(1024) uint8_t smem[];
    const int tid = threadIdx.x, lane = tid & 31;
    const int warp = __shfl_sync(~0u, tid >> 5, 0);
    const int blk = blockIdx.x;
    uint32_t sb = smem_u32(smem);
    asm volatile("" : "+r"(sb));
    int* mi = reinterpret_cast<int*>(smem + SM_MISC);

    const int g = lane >> 2, t = lane & 3;
    const uint32_t dump = sb + SC_DUMP + lane * 4;
    int4 d4, s4;
    int d5, s5;
    const bool binner = (PHASES & 1) && blk < NSRC;
    const uint32_t ma = sb + SC_MAIL + (tid >> 3) * 144 + (tid & 7) * 16;
    if (binner) {
        const int q = min(tid, EPC / 5 - 1);
        d4 = __ldg(reinterpret_cast<const int4*>(dst + blk * EPC) + q);
        s4 = __ldg(reinterpret_cast<const int4*>(src + blk * EPC) + q);
        d5 = __ldg(dst + blk * EPC + EPC / 5 * 4 + q);
        s5 = __ldg(src + blk * EPC + EPC / 5 * 4 + q);
        const uint32_t dmy = (20 * HS + (blk & 3) * 8 + (tid & 7)) << 21;
#pragma unroll
        for (int k = 0; k < 3; k++)
            if (k < 2 || warp < 1) sts128(ma + k * 64 * 144, dmy, dmy + (32u << 21), dmy, dmy + (32u << 21));
        if (tid < NB / 4) sts128(sb + SC_CNT + tid * 16, 0, 0, 0, 0);
    }
    if (PHASES & 2) {
        if (tid == 160) { sts128(sb + SM_MISC, 0, 0, 0, 0); sts128(sb + SM_MISC + MI_NU * 4, 0, 0, 0, 0); }
        if (tid <= 21 * HS / 4) sts128(sb + SC_HIST + tid * 16, 0, 0, 0, 0);
    }
    __syncthreads();
    if (PHASES & 2) {
        if (warp >= 8) cp16(sb + SC_WR + ((tid - 256) ^ ((tid >> 4) & 6)) * 16, w_rad + (tid - 256) * 8);
        if (tid < 8) cp16(sb + SC_WR + 4096 + tid * 16, cg + tid * 8);
        asm volatile("cp.async.commit_group;" ::: "memory");
        if (tid < 2 && blk < 128) asm volatile("prefetch.global.L2 [%0];" ::"l"(w_mix + (blk * 2 + tid) * 64));
    }
    if (binner) {
        if (tid < EPC / 5) {
            const uint32_t dd[5] = {(uint32_t)d4.x, (uint32_t)d4.y, (uint32_t)d4.z, (uint32_t)d4.w, (uint32_t)d5};
            const uint32_t ss[5] = {(uint32_t)s4.x, (uint32_t)s4.y, (uint32_t)s4.z, (uint32_t)s4.w, (uint32_t)s5};
            uint32_t own[5], rk[5], v[5];
#pragma unroll
            for (int j = 0; j < 5; j++) {
                const uint32_t tm = (dd[j] * 55189) >> 20;
                own[j] = tm >> 2;
                rk[j] = atoms_inc(sb + SC_CNT + (tm & ~3u));
                const uint32_t code = dd[j] + tm - own[j] * 80;
                v[j] = (((code >> 2) * (HS * 128) + ss[j]) << 14) + (code & 3) + (j < 4 ? tid * 16 + j * 4 + 4 : tid * 4 + EPC / 5 * 16 + 4);
            }
#pragma unroll
            for (int j = 0; j < 5; j++) sts32(sb + SC_MAIL + own[j] * 144 + min(rk[j], 31u) * 4, v[j]);
            if (max(max(max(rk[0], rk[1]), max(rk[2], rk[3])), rk[4]) >= 31) {
#pragma unroll
                for (int j = 0; j < 5; j++)
                    if (rk[j] - 31 < 32)
                        asm volatile("st.relaxed.gpu.global.u32 [%0], %1;" ::"l"(g_mail2 + (own[j] * NSRC + blk) * 32 + rk[j] - 31), "r"(v[j]) : "memory");
            }
        } else if (tid == NTHR - 1) {
            uint32_t t;
            asm volatile("{\n.reg .pred p;\nsetp.ge.s32 p, %1, 0;\nmov.u32 %0, 0;\n@p mov.u32 %0, %%globaltimer_lo;\n}" : "=r"(t) : "r"(s5));
            sts32(sb + SC_CNT + NB * 4, 0xc0000000u | ((t << 7) & 0x3ffff000u));
        }
        STAMP(1);
    }
    if (PHASES & 2) {
        const uint32_t wd = sb + SM_W + (tid ^ ((tid >> 4) & 2) ^ ((tid >> 6) & 4)) * 16;
#pragma unroll
        for (int k = 0; k < 4; k++) cp16(wd + k * NTHR * 16, w_mix + tid * 8 + k * NTHR * 8);
    }
    uint4* const mo = g_mail + ((tid >> 3) * NSRC + blk) * 8 + (tid & 7);
    asm volatile("cp.async.wait_group 0;" ::: "memory");
    __syncthreads();
    if (binner) {
        const uint32_t hdr = lds32(sb + SC_CNT + NB * 4);
        uint4 mv[3];
        uint32_t mc[3];
#pragma unroll
        for (int k = 0; k < 3; k++)
            if (k < 2 || warp < 1) {
                mv[k] = lds128(ma + k * 64 * 144);
                mc[k] = lds32(sb + SC_CNT + (tid >> 3) * 4 + k * 256);
            }
#pragma unroll
        for (int k = 0; k < 3; k++)
            if (k < 2 || warp < 1)
                asm volatile("st.relaxed.gpu.global.v4.u32 [%0], {%1,%2,%3,%4};" ::"l"(mo + k * 64 * NSRC * 8),
                             "r"(mv[k].x), "r"(mv[k].y), "r"(mv[k].z), "r"((tid & 7) == 7 ? hdr | mc[k] : mv[k].w) : "memory");
        STAMP(2);
    }
    if (!(PHASES & 2)) return;
    const uint32_t tpub = (uint32_t)clock() + (blk < NSRC ? 0 : IDLE_EST);
    if (tid == 161) {
        mi[MI_SHIFT] = 0;
        *reinterpret_cast<int**>(mi + MI_SHIFT + 4) = g_lag[blk];
    }
    if (tid == 162) g_lag[blk][0] = g_lag[NB + blk][0] = 0;
    if (tid < 4 * UCAP) {
#pragma unroll
        for (int k = 0; k < 12; k++) sts32(sb + SM_REC + tid * REC + k * 4, k < 4 ? ~0u : 0x80000000u + blk * 2048 + tid * 4);
    }
    if (tid == 14 * 32) init_barriers<~6u>();
    if (tid == 15 * 32) {
        constexpr int start_ns = START_NS;
        mi[MI_GREF] = gtime() - start_ns;
        mi[MI_T0] = clock();
    }
    if (warp >= 7) {
        uint32_t f[4];
        if (warp >= 8) {
            uint32_t w[4];
#pragma unroll
            for (int j = 0; j < 4; j++)
                w[j] = mul_lo(lds32(sb + SC_WR + (2 * t + (j & 1) + (j >> 1) * 8) * 256 + ((((warp - 8) * 8 + g) * 4) ^ (t << 5))), 0x3f003f00u);
            f[0] = __byte_perm(w[0], w[1], 0x5410); f[1] = __byte_perm(w[0], w[1], 0x7632);
            f[2] = __byte_perm(w[2], w[3], 0x5410); f[3] = __byte_perm(w[2], w[3], 0x7632);
        } else {
#pragma unroll
            for (int i = 0; i < 4; i++) {
                const uint32_t ca = sb + SC_WR + 4096 + (i * 16 + (t & 1) * 8 + (g & 3)) * 2;
                f[i] = (lds16(ca) | (lds16(ca + 8) << 16)) & ((t >> 1) == (g >> 2) ? ~0u : 0u);
            }
        }
        const uint32_t d = sb + (warp == 7 ? 2 * ROWP : ((warp - 8) >> 2) * ROWP + (warp & 3) * 512) + lane * 16;
#pragma unroll
        for (int k = 0; k < 4; k++) sts128(d + k * NG * STAGE, f[0], f[1], f[2], f[3]);
    }
    asm volatile("cp.async.wait_all;" ::: "memory");
    __syncwarp();
#pragma unroll
    for (int k = 0; k < 2; k++) {
        const int i = (tid & ~1) + ((tid & 1) * 2 + k) * NTHR, c = i >> 4;
        const uint32_t a0 = sb + SM_W + c * 256 + (((i & 15) ^ ((c & 3) | (((c >> 4) & 1) << 2))) << 4);
        const uint32_t o = (tid & 1) << 4;
        uint4 u = lds128((a0 & ~16u) ^ o), v = lds128((a0 | 16u) ^ o);
        if (tid & 1) { const uint4 w = u; u = v; v = w; }
        const uint32_t s0 = (tid & 1) ? 0x7632 : 0x5410, s1 = s0 ^ 0x2222;
        sts128(a0 ^ o, __byte_perm(u.x, u.y, s0), __byte_perm(u.z, u.w, s0), __byte_perm(v.x, v.y, s0), __byte_perm(v.z, v.w, s0));
        sts128(a0 ^ o ^ 16, __byte_perm(u.x, u.y, s1), __byte_perm(u.z, u.w, s1), __byte_perm(v.x, v.y, s1), __byte_perm(v.z, v.w, s1));
    }

    uint32_t en[8], hr[8], rk[8], em[8];
    int xc[2];
    const uint32_t tref = __shfl_sync(~0u, gtime() >> 5, 0);
    {
        uint4* mp = g_mail + blk * NSRC * 8 + tid;
        int it = 0;
        bool ok;
        while ((int)((uint32_t)clock() - tpub) < POLL_DELAY) {}
        do {
#pragma unroll
            for (int k = 0; k < 2; k++)
                    asm volatile("ld.relaxed.gpu.global.v4.u32 {%0,%1,%2,%3}, [%4];"
                                 : "=r"(en[4 * k]), "=r"(en[4 * k + 1]), "=r"(en[4 * k + 2]), "=r"(en[4 * k + 3])
                                 : "l"(mp + k * NTHR) : "memory");
            uint32_t m = ~0u;
#pragma unroll
            for (int i = 0; i < 8; i++) m = min(m, en[i]);
            ok = __all_sync(~0u, m != 0);
            if (++it > (1 << 20)) __trap();
        } while (!ok);
        STAMP(3);
        const bool hd = (lane & 7) == 7;
        const uint32_t h0 = en[3], h1 = en[7];
        if (hd) en[3] = en[7] = (20 * HS + 64 + warp) << 21;
#pragma unroll
        for (int i = 0; i < 8; i++) {
            hr[i] = sb + SC_HIST + (en[i] >> 21) * 4;
            rk[i] = atoms_inc(hr[i]);
        }
#pragma unroll
        for (int i = 0; i < 8; i++) {
            em[i] = (tid >> 3) * (EPC * 4) + (i >> 2) * (NTHR / 8 * EPC * 4) - 4 + (en[i] & 0x3fff);
            en[i] = (en[i] >> 14) - (((en[i] >> 21) * 12946) >> 20) * (HS * 128);
        }
        int dt = hd ? max((int)(((h0 >> 12) - tref) << 14), (int)(((h1 >> 12) - tref) << 14)) >> 14 : -(1 << 20);
        xc[0] = hd ? max((int)(h0 & 0xfff) - 31, 0) : 0;
        xc[1] = hd ? max((int)(h1 & 0xfff) - 31, 0) : 0;
        dt = __reduce_max_sync(~0u, dt);
        asm volatile("red.shared.max.u32 [%0], %1;" ::"r"(lane == 0 ? sb + SM_MISC + MI_TMAX * 4 : dump + 128), "r"(tref + dt + (1u << 27)) : "memory");
        if (xc[0] + xc[1]) {
            uint32_t slot;
            asm volatile("atom.shared.add.u32 %0, [%1], %2;" : "=r"(slot) : "r"(sb + SM_MISC + MI_XN * 4 + (tid >> 16)), "r"(xc[0] + xc[1]) : "memory");
#pragma unroll 1
            for (int r = 0; r < xc[0] + xc[1] && slot + r < 32; r++)
                sts32(sb + SC_XTRA + (slot + r) * 4, (tid >> 3) * 32 + (r < xc[0] ? r : NTHR * 4 - xc[0] + r));
        }
#pragma unroll
        for (int k = 0; k < 2; k++)
            mp[k * NTHR] = make_uint4(0, 0, 0, 0);
    }
    __syncthreads();
    STAMP(4);
    uint32_t* hist = reinterpret_cast<uint32_t*>(smem + SC_HIST);
    const int xn = mi[MI_XN];
    uint32_t xi = 0, xv = 1;
    if (warp < 10) {
        uint32_t* hp = hist + (warp * 2 + (lane >> 4)) * HS + (lane & 15) * 5;
        int c[5], s = 0;
#pragma unroll
        for (int j = 0; j < 5; j++) { c[j] = hp[j]; s += c[j]; }
        int inc = s;
#pragma unroll
        for (int o = 1; o < 16; o <<= 1) { int v = __shfl_up_sync(~0u, inc, o, 16); if ((lane & 15) >= o) inc += v; }
        int base = 0;
        if ((lane & 15) == 15) {
            const int tm = ((warp * 2 + (lane >> 4)) * 13) >> 6;
            asm volatile("atom.shared.add.u32 %0, [%1], %2;" : "=r"(base) : "r"(sb + SM_MISC + (MI_NU + tm) * 4), "r"((inc + 3) >> 2) : "memory");
            base += tm * 256;
            hp[5] = (base + ((inc + 3) >> 2)) << 16;
        }
        const int tot = __shfl_sync(~0u, inc, 15, 16);
        base = __shfl_sync(~0u, base, 15, 16);
        int ex = inc - s;
#pragma unroll
        for (int j = 0; j < 5; j++) {
            hp[j] = (base * 4 + ex) | ((base + ((ex == tot ? ex + 3 : ex + 1) >> 2)) << 16);
            ex += c[j];
        }
    } else if (warp == 10) {
        if (lane < xn) {
            xi = reinterpret_cast<const uint32_t*>(smem + SC_XTRA)[lane];
            asm volatile("ld.relaxed.gpu.global.u32 %0, [%1];" : "=r"(xv) : "l"(g_mail2 + blk * NSRC * 32 + xi) : "memory");
        }
    } else if (warp == 12) {
        if (lane == 0) init_barriers<6u>();
    } else if (warp == 11) {
        sts32(sb + SC_GPOS + (GDUMMY + lane) * 4, (uint32_t)(4 * UCAP * REC + 128) * 0x10001u);
#pragma unroll
        for (int k = 0; k < 3; k++) hist[20 * HS + min(lane + 32 * k, NBK)] = GDUMMY * 4;
        if (lane == 0) mi[MI_T0] += ((int)(((uint32_t)mi[MI_TMAX] << 5) - mi[MI_GREF]) * 63) >> 5;
    }
    constexpr int pace = PACE_Q8, p1 = PACE_HEAD, b1 = HEAD_BK, p2 = PACE_TAIL, b2 = TAIL_BK, lead = PACE_LEAD;
    auto sched = [&](int b) { return b * pace - min(b, b1) * (pace - p1) - max(b - b2, 0) * (pace - p2) - lead; };
    const int mteam = tid / NBK, mb = tid - mteam * NBK;
    int tb0 = sched(mb);
    float tbw = (float)(sched(mb + 1) - tb0);
    uint32_t mh = sb + SC_HIST + (mteam * 5 * HS + mb) * 4 + 2, mh0 = sb + SC_HIST + mteam * 5 * HS * 4 + 2;
    asm volatile("" : "+r"(tb0), "+f"(tbw), "+r"(mh), "+r"(mh0));
    STAMP(6);
    __syncthreads();
    STAMP(10);
    int myng = mi[MI_NU + (lane & 3)];
    const bool ovf = __any_sync(~0u, myng + xn > 2 * (UCAP - 4) || xn > 32);
    if (!ovf) {
        if (warp < 10) {
            int lo[5], n[5], pos = mteam * UCAP * 2, nsum = 0;
#pragma unroll
            for (int q = 0; q < 5; q++) {
                lo[q] = lds16(mh + q * HS * 4);
                n[q] = lds16(mh + q * HS * 4 + 4) - lo[q];
                pos += lo[q] - lds16(mh0 + q * HS * 4);
                nsum += n[q];
            }
            const int step = __float2int_rz(__fdividef(tbw, (float)max(nsum, 1)));
            const int tb = tb0 + (step >> 1) - pos * step;
            const uint32_t t0 = mi[MI_T0];
            auto emit = [&](int q, int r, int nq, int slot, int pq) {
                const uint32_t ro = (pq >> 1) * REC, par = pq & 1;
                asm volatile("{\n.reg .pred p, e;\nsetp.lt.s32 p, %0, %1;\nsetp.eq.and.u32 e, %2, 0, p;\n"
                             "@p st.shared.u32 [%3], %4;\n@p st.shared.u8 [%5+48], %6;\n@e st.shared.u16 [%5+102], %7;\n}"
                             ::"r"(r), "r"(nq), "r"(par), "r"(sb + SC_GPOS + slot * 4),
                               "r"(ro * 0x10001u + par * 0x40002u + (REC | (16 << 16))), "r"(sb + SM_REC + ro + par), "r"(q),
                               "h"((uint16_t)((t0 + max(tb + pq * step, 0)) >> 2)) : "memory");
            };
#pragma unroll
            for (int q = 0, pq = pos; q < 5; pq += n[q], q++) emit(q, 0, n[q], lo[q], pq);
#pragma unroll
            for (int q = 0; q < 5; pos += n[q], q++)
#pragma unroll 1
                for (int r = 1; __any_sync(~0u, r < n[q]); r++) emit(q, r, n[q], lo[q] + r, pos + r);
        } else if (warp == 10) {
            for (int n = 0; __any_sync(~0u, xv == 0); n++) {
                if (xv == 0) asm volatile("ld.relaxed.gpu.global.u32 %0, [%1];" : "=r"(xv) : "l"(g_mail2 + blk * NSRC * 32 + xi) : "memory");
                if (n > (1 << 20)) __trap();
            }
            const uint32_t xl = (xv >> 21) / HS, xt = lane < xn ? xl / 5 : 4;
            const uint32_t same = __match_any_sync(~0u, xt);
            const int pq = __shfl_sync(~0u, myng, xt & 3) + __popc(same & ((1u << lane) - 1));
#pragma unroll
            for (int q = 0; q < 4; q++) {
                const int c = __popc(__ballot_sync(~0u, xt == q));
                if (lane == q) myng += c;
            }
            if (lane < xn) {
                g_mail2[blk * NSRC * 32 + xi] = 0;
                const uint32_t a = sb + SM_REC + (xt * UCAP + (pq >> 1)) * REC;
                sts16(a + REC + (pq & 1) * 2, (xv >> 14) - xl * (HS * 128));
                sts32(a + 16 + (pq & 1) * 4, (xi >> 5) * (EPC * 4) - 4 + (xv & 0x3fff));
                sts8(a + 48 + (pq & 1), xl - xt * 5);
                if (!(pq & 1)) sts16(a + REC + 50, ((uint32_t)mi[MI_T0] + sched(NBK - 2)) >> 2);
            }
            if (lane < 4) {
                const uint32_t a = sb + SM_REC + (lane * UCAP + (myng >> 1)) * REC + 48;
                if (myng & 1) sts8(a + 1, 0);
                sts16(a + (myng & 1) * REC, 5);
                mi[MI_END + lane] = (myng + 1) >> 1;
            }
        }
#pragma unroll
        for (int i = 0; i < 8; i++) {
            const uint32_t p = rk[i] + lds16(hr[i]);
            hr[i] = sb + SC_GPOS + (p & ~3u);
            rk[i] = (p & 3) * 0x80004u;
        }
        __syncthreads();
        STAMP(11);
#pragma unroll
        for (int i = 0; i < 8; i++) rk[i] += lds32(hr[i]);
#pragma unroll
        for (int i = 0; i < 8; i++) {
            sts16(sb + SM_REC + (rk[i] & 0xffff), en[i]);
            sts32(sb + SM_REC + (rk[i] >> 16), em[i]);
        }
    } else {
        if (tid < 4) {
            sts16(sb + SM_REC + tid * UCAP * REC + 48, 5);
            mi[MI_END + tid] = 0;
        }
        generic_path(reinterpret_cast<float*>(smem), x, src, dst, Y, ef, w_rad, cg, xc[0], xc[1]);
    }

    __syncwarp();
    if (warp >= 8) {
        asm volatile("bar.sync 3, 512;" ::: "memory");
        asm volatile("setmaxnreg.dec.sync.aligned.u32 24;");
        const int team = warp & 3;
        if (ovf) {
            asm volatile("bar.sync 2;" ::: "memory");
            if (tid == 256) init_barriers<~0u>();
            asm volatile("bar.sync 2;" ::: "memory");
        }
        STAMP(5);
        const uint32_t ring = sb + SM_RING + team * NG * STAGE;
        const uint32_t q = lane >> 3, c = lane & 7, rec = sb + SM_REC + team * UCAP * REC;
        __syncwarp();
        producer_loop(reinterpret_cast<const char*>(x) + (lane & 15) * 16, reinterpret_cast<const char*>(ef) + (c & 1) * 16, Y,
                      q * ROWP + ((c ^ (q << 1)) << 4), q * 4 + (c & 2) * 8, (c & 1) * 2 + (c >> 2), ring, rec,
                      rec + (mi[MI_END + team] + 1) * REC, warp - 8, sb + SM_MISC + MI_SHIFT * 4,
                      (lane >> 4) * ROWP + (((lane & 15) ^ ((lane >> 4) << 1)) << 4));
        uint32_t ln, sb2, cta;
        asm volatile("mov.u32 %0, %%tid.x;\nmov.u32 %1, %%ctaid.x;\nmov.u32 %2, %%dynamic_smem_size;" : "=r"(ln), "=r"(cta), "=r"(sb2));
        asm volatile("bar.arrive %0, 128;" ::"r"(4 + ((ln >> 5) & 3)) : "memory");
        if (cta == NB - 1 && ln >= NTHR - 32) {
            ln &= 31;
            sb2 += smem_u32(smem) - SM_TOTAL + SM_MISC;
            constexpr int lead = LEAD_CLK >> 2;
            const uint32_t tend = lds32(sb2 + MI_T0 * 4) + 70 * PACE_Q8;
            int sh = 0;
            for (int n = 0; n < 199 && (int)((uint32_t)clock() - tend - (sh >> 14)) < 0; n++) {
                int v;
                asm volatile("ld.relaxed.gpu.global.s32 %0, [%1];" : "=r"(v) : "l"(g_lag[ln * 4]) : "memory");
                const int err = (__reduce_add_sync(~0u, max(v, 0)) >> 5) - lead;
                const int old = sh;
                sh = min(max((sh >> 16) + (err * (err > 0 ? FB_GAIN : FB_DOWN) >> 3), FB_MIN), 2500) << 16;
                if (sh == old) continue;
#pragma unroll
                for (int k = 0; k < 5; k++)
                    asm volatile("st.relaxed.gpu.global.s32 [%0], %1;" ::"l"(g_lag[NB + min(ln + 32 * k, NB - 1u)]), "r"(sh) : "memory");
            }
        }
    } else {
        asm volatile("bar.arrive 3, 512;" ::: "memory");
        int team;
        {
            const int n0 = mi[MI_END], n1 = mi[MI_END + 1], n2 = mi[MI_END + 2], n3 = mi[MI_END + 3];
            const int d1 = abs(n0 + n1 - n2 - n3), d2 = abs(n0 + n2 - n1 - n3), d3 = abs(n0 + n3 - n1 - n2);
            const uint32_t perm = d1 < min(d2, d3) ? 0x3120 : d3 < d2 ? 0x2310 : 0x3210;
            team = __shfl_sync(~0u, (perm >> ((warp >> 1) * 4)) & 3, 0);
        }
        const int h = warp & 1;
        asm volatile("setmaxnreg.inc.sync.aligned.u32 232;");
        uint32_t ring = sb + SM_RING + team * NG * STAGE;
        uint32_t wf[4][4], cgf[4];
#pragma unroll
        for (int m = 0; m < 5; m++) {
            const uint4 v = lds128(ring + (m < 4 ? h * ROWP + m * 512 : 2 * ROWP) + lane * 16);
            uint32_t* f = m < 4 ? wf[m] : cgf;
            f[0] = v.x; f[1] = v.y; f[2] = v.z; f[3] = v.w;
        }
        float acc[5][4][2][4];
        if (!ovf) {
#pragma unroll
            for (int l = 0; l < 5; l++)
#pragma unroll
                for (int m = 0; m < 4; m++)
#pragma unroll
                    for (int p = 0; p < 2; p++)
#pragma unroll
                        for (int r = 0; r < 4; r++) acc[l][m][p][r] = 0.f;
        } else {
            const float* sagg = reinterpret_cast<const float*>(smem);
#pragma unroll
            for (int l = 0; l < 5; l++)
#pragma unroll
                for (int m = 0; m < 4; m++)
#pragma unroll
                    for (int p = 0; p < 2; p++)
#pragma unroll
                        for (int r = 0; r < 4; r++) {
                            int nd = l * 4 + (g >> 2) + (r >> 1) * 2;
                            int ch = h * 64 + m * 16 + 4 * t + (r & 1) * 2 + p;
                            acc[l][m][p][r] = nd < 19 ? sagg[(team * 19 + nd) * 512 + ch * 4 + (g & 3)] : 0.f;
                        }
            asm volatile("bar.sync 2;" ::: "memory");
            asm volatile("bar.sync 2;" ::: "memory");
        }
        const uint32_t xoff = t * ROWP + h * 512 + ((g ^ (t << 1)) << 4);
        const uint32_t mat = lane >> 3, mhi = (lane >> 2) & 1;
        const bool isy = mat < 2;
        const uint32_t ml = isy ? (t & 2) + (mat & 1) : t;
        const uint32_t moff = ml * ROWP + 2048 + (((isy ? 4 + 2 * mhi + (t & 1) : 2 * mhi + mat - 2) ^ (ml << 1)) << 4);
        __syncwarp();
        consumer_loop(acc, wf, cgf, xoff, ring, moff, sb + SM_REC + team * UCAP * REC);
        {
        int lane_;
        asm volatile("mov.u32 %0, %%laneid;" : "=r"(lane_));
        const int lane = lane_, g = lane >> 2, t = lane & 3;
        const uint32_t sb = ring - team * NG * STAGE;
        STAMP(7);
        asm volatile("bar.sync %0, 128;" ::"r"(4 + team) : "memory");
        if (lane == 0) {
            mbar_inval(ring + h * STAGE + 4 * ROWP);
            mbar_inval(ring + h * STAGE + 4 * ROWP + 8);
        }
        __syncwarp();
        {
            const int rr = ((g & 3) >> 1) * 8 + (g >> 2) * 2 + (g & 1);
#pragma unroll
            for (int l = 0; l < 5; l++)
#pragma unroll
                for (int hi = 0; hi < 2; hi++) {
                    const int R = l * 16 + rr + hi * 4;
                    const uint32_t a = sb + team * AGGT + h * 10240 + R * 128;
#pragma unroll
                    for (int c = 0; c < 2; c++) {
                        const int m = 2 * c;
                        sts128(a + (((2 * t + c) ^ (R & 7)) << 4),
                               pack_bf16(acc[l][m][0][2 * hi], acc[l][m][1][2 * hi]),
                               pack_bf16(acc[l][m][0][2 * hi + 1], acc[l][m][1][2 * hi + 1]),
                               pack_bf16(acc[l][m + 1][0][2 * hi], acc[l][m + 1][1][2 * hi]),
                               pack_bf16(acc[l][m + 1][0][2 * hi + 1], acc[l][m + 1][1][2 * hi + 1]));
                    }
                }
        }
        asm volatile("fence.proxy.async.shared::cta;" ::: "memory");
        uint32_t wa[8][4];
        {
            const int r = lane & 7, k = (lane >> 4) * 8 + r;
            const int chunk = (2 * warp + ((lane >> 3) & 1)) ^ r;
#pragma unroll
            for (int ks = 0; ks < 8; ks++) {
                const int c = (ks >> 2) * 64 + 16 * (k >> 2) + 4 * (ks & 3) + (k & 3);
                asm volatile("ldmatrix.sync.aligned.m8n8.x4.trans.shared.b16 {%0,%1,%2,%3}, [%4];"
                             : "=r"(wa[ks][0]), "=r"(wa[ks][1]), "=r"(wa[ks][2]), "=r"(wa[ks][3])
                             : "r"(sb + SM_W + c * 256 + (chunk << 4)));
            }
        }
        asm volatile("bar.sync 1, 256;" ::: "memory");
        STAMP(8);
        const int sl = (lane & 7) * 4 + (lane >> 3);
        __nv_bfloat16* op = out + (size_t)(blk * NPB + (lane >> 3)) * 512 + warp * 64 + (lane & 7) * 8;
        const int nleft = N_NODES - blk * NPB - (lane >> 3);
        uint32_t pk[20];
        auto store = [&](int tm) {
#pragma unroll
            for (int l = 0; l < 5; l++) {
                uint4 v;
                v.x = __shfl_sync(~0u, pk[4 * l + 0], sl);
                v.y = __shfl_sync(~0u, pk[4 * l + 1], sl);
                v.z = __shfl_sync(~0u, pk[4 * l + 2], sl);
                v.w = __shfl_sync(~0u, pk[4 * l + 3], sl);
                asm volatile("{\n.reg .pred p;\nsetp.lt.u32 p, %5, %6;\n@p st.global.v4.u32 [%0], {%1,%2,%3,%4};\n}"
                             ::"l"(op + (tm * 19 + l * 4) * 512), "r"(v.x), "r"(v.y), "r"(v.z), "r"(v.w), "r"(tm * 19 + l * 4),
                               "r"(l < 4 || lane < 24 ? nleft : 0) : "memory");
            }
        };
        if (warp >= 4) asm volatile("bar.sync 10, 256;" ::: "memory");
#pragma unroll 1
        for (int tm = 0; tm < 4; tm++) {
            float o[40];
            asm volatile("wgmma.fence.sync.aligned;" ::: "memory");
#pragma unroll
            for (int ks = 0; ks < 8; ks++) {
                const uint32_t a = sb + tm * AGGT + (ks >> 2) * 10240 + (ks & 3) * 32;
                const uint64_t desc = (uint64_t)((a & 0x3ffff) >> 4) | (1ull << 16) | (64ull << 32) | (1ull << 62);
                wgmma_n80(o, wa[ks], desc, ks);
            }
            asm volatile("wgmma.commit_group.sync.aligned;" ::: "memory");
            if (tm == 0 && warp < 4) asm volatile("bar.arrive 10, 256;" ::: "memory");
            asm volatile("wgmma.wait_group.sync.aligned 0;" ::: "memory");
#pragma unroll
            for (int i = 0; i < 40; i++) asm volatile("" : "+f"(o[i])::"memory");
#pragma unroll
            for (int l = 0; l < 5; l++) {
                pk[4 * l + 0] = pack_bf16(o[8 * l + 0], o[8 * l + 1]);
                pk[4 * l + 1] = pack_bf16(o[8 * l + 4], o[8 * l + 5]);
                pk[4 * l + 2] = pack_bf16(o[8 * l + 2], o[8 * l + 3]);
                pk[4 * l + 3] = pack_bf16(o[8 * l + 6], o[8 * l + 7]);
            }
            store(tm);
        }
        STAMP(9);
        }
    }
}

}

extern "C" void kernel_launch(void* const* d_in, const int* in_sizes, int n_in, void* d_out, int out_size) {
    (void)in_sizes; (void)n_in; (void)out_size;
    const __nv_bfloat16* x = (const __nv_bfloat16*)d_in[0];
    const int* src = (const int*)d_in[1];
    const int* dst = (const int*)d_in[2];
    const __nv_bfloat16* Y = (const __nv_bfloat16*)d_in[3];
    const __nv_bfloat16* ef = (const __nv_bfloat16*)d_in[4];
    const __nv_bfloat16* w_rad = (const __nv_bfloat16*)d_in[5];
    const __nv_bfloat16* cg = (const __nv_bfloat16*)d_in[6];
    const __nv_bfloat16* w_mix = (const __nv_bfloat16*)d_in[7];
    __nv_bfloat16* out = (__nv_bfloat16*)d_out;

    static int sms = 0;
    if (sms == 0) {
        int dev = 0;
        cudaGetDevice(&dev);
        cudaDeviceGetAttribute(&sms, cudaDevAttrMultiProcessorCount, dev);
        cudaFuncSetAttribute(tfn_kernel<3>, cudaFuncAttributeMaxDynamicSharedMemorySize, SM_TOTAL);
        cudaFuncSetAttribute(tfn_kernel<1>, cudaFuncAttributeMaxDynamicSharedMemorySize, SM_TOTAL);
        cudaFuncSetAttribute(tfn_kernel<2>, cudaFuncAttributeMaxDynamicSharedMemorySize, SM_TOTAL);
    }
    if (sms >= NB) {
        tfn_kernel<3><<<NB, NTHR, SM_TOTAL>>>(x, src, dst, Y, ef, w_rad, cg, w_mix, out);
    } else {
        tfn_kernel<1><<<NB, NTHR, SM_TOTAL>>>(x, src, dst, Y, ef, w_rad, cg, w_mix, out);
        tfn_kernel<2><<<NB, NTHR, SM_TOTAL>>>(x, src, dst, Y, ef, w_rad, cg, w_mix, out);
    }
}
```
